```python
import torch

def _softmax(x, axis=-1):
    return torch.softmax(x, dim=axis)
def _gelu(x):
    return torch.nn.functional.gelu(x, approximate="tanh")
def _silu(x):
    return torch.nn.functional.silu(x)
def _sigmoid(x):
    return torch.sigmoid(x)
def _layernorm(x, axis=-1, eps=1e-5):
    m = x.mean(dim=axis, keepdim=True)
    v = x.var(dim=axis, keepdim=True, unbiased=False)
    return (x - m) / torch.sqrt(v + eps)
def _scatter_add(tgt, idx, src, axis=0):
    return tgt.clone().index_add_(axis, idx, src)
def _segment_sum(src, seg, n):
    out = torch.zeros((n,) + src.shape[1:], dtype=src.dtype)
    return out.index_add_(0, seg, src)
def _pad(x, pw):
    flat = tuple(v for pair in reversed(pw) for v in pair)
    return torch.nn.functional.pad(x, flat)

kernel_name = 'gated_mix__linear_kernel_hedgehog__mha_block__prompt'

def setup_inputs():

    _w = (lambda a: (lambda t: t.to(torch.bfloat16) if t.is_floating_point() else t)(torch.as_tensor(a)))
    def _A_setup():
        B, S, D, H = 1, 2048, 640, 32
        Dh = D // H
        return {
            "x": _w((lambda *s: torch.randn(*s, dtype=torch.bfloat16) * 0.05)(B, S, D)),
            "wqkv": _w((lambda *s: torch.randn(*s, dtype=torch.bfloat16) * 1.6)(D, 3 * D)),
            "w_phi": _w((lambda *s: torch.randn(*s, dtype=torch.bfloat16) * 1.6)(H, Dh, Dh) * (Dh ** -0.5)),
            "wo": _w((lambda *s: torch.randn(*s, dtype=torch.bfloat16) * 0.05)(D, D)),
        }
    _A_in = _A_setup()

    def _B_setup():
        B, S, D, H = 1, 2048, 640, 32
        return {
            "x": _w((lambda *s: torch.randn(*s, dtype=torch.bfloat16) * 0.05)(B, S, D)),
            "wqkv": _w((lambda *s: torch.randn(*s, dtype=torch.bfloat16) * 0.8)(D, 3 * D)),
            "wo": _w((lambda *s: torch.randn(*s, dtype=torch.bfloat16) * 0.05)(D, D)),
        }
    _B_in = _B_setup()

    return {
        "A_x": _A_in["x"],
        "A_wqkv": _A_in["wqkv"],
        "A_w_phi": _A_in["w_phi"],
        "A_wo": _A_in["wo"],
        "B_x": _B_in["x"],
        "B_wqkv": _B_in["wqkv"],
        "B_wo": _B_in["wo"],
        "gate_w": _w((lambda *s: torch.randn(*s, dtype=torch.bfloat16) * 0.05)(640) * 16.0),
    }

def reference(A_x, A_wqkv, A_w_phi, A_wo, B_x, B_wqkv, B_wo, gate_w):
    def _A_ref(x, wqkv, w_phi, wo):
        B, S, D = x.shape
        H = 32; Dh = D // H
        qkv = (lambda x, *d: x.permute(*d))((x @ wqkv).reshape(B, S, 3, H, Dh), 2, 0, 3, 1, 4)
        q, k, v = qkv[0], qkv[1], qkv[2]
        pq = torch.einsum("bhsd,hdf->bhsf", q, w_phi)
        pk = torch.einsum("bhsd,hdf->bhsf", k, w_phi)
        phi_q = torch.concatenate([_softmax(pq, axis=-1), _softmax(-pq, axis=-1)], axis=-1)
        phi_k = torch.concatenate([_softmax(pk, axis=-1), _softmax(-pk, axis=-1)], axis=-1)
        kv = torch.einsum("bhsf,bhsd->bhfd", phi_k, v)
        z  = torch.einsum("bhsf->bhf", phi_k)
        num = torch.einsum("bhqf,bhfd->bhqd", phi_q, kv)
        den = torch.einsum("bhqf,bhf->bhq", phi_q, z)[..., None] + 1e-6
        o = num / den
        return (lambda x, *d: x.permute(*d))(o, 0, 2, 1, 3).reshape(B, S, D) @ wo

    def _B_ref(x, wqkv, wo):
        B, S, D = x.shape
        H = 32
        Dh = D // H
        qkv = (lambda x, *d: x.permute(*d))((x @ wqkv).reshape(B, S, 3, H, Dh), 2, 0, 3, 1, 4)
        q, k, v = qkv[0], qkv[1], qkv[2]
        scores = torch.einsum("bhqd,bhkd->bhqk", q, k) * (Dh ** -0.5)
        p = _softmax(scores, axis=-1)
        o = torch.einsum("bhqk,bhkd->bhqd", p, v)
        return (lambda x, *d: x.permute(*d))(o, 0, 2, 1, 3).reshape(B, S, D) @ wo

    x = A_x
    g = _sigmoid((x * gate_w).sum(-1, keepdims=True))
    a = _A_ref(x, A_wqkv, A_w_phi, A_wo)
    b = _B_ref(x, B_wqkv, B_wo)
    return g * a + (1 - g) * b
```

```cpp
#include <cuda_runtime.h>
#include <cuda_bf16.h>
#include <cuda.h>
#include <stdint.h>

namespace {

constexpr int SEQ = 2048, DM = 640, NH = 32;
constexpr int IMG_HEAD = SEQ * 48;
#define POLY_MASK 0x76DDu
constexpr float LOG2E = 1.4426950408889634f;
constexpr float QSCALE = 0.22360679774997896f * 1.4426950408889634f;
constexpr uint32_t BF_ONE = 0x3F80u;
constexpr uint32_t BF_MAGIC = 0x43E0u;
constexpr uint32_t BF_MU_HI = 0x4025u;
constexpr uint32_t BF_MU_LO = 0x3B8Bu;
constexpr float FAST_BOUND = 40.0f;

__device__ __align__(1024) uint8_t g_QB[NH * IMG_HEAD];
__device__ __align__(1024) uint8_t g_KB[NH * IMG_HEAD];
__device__ __align__(1024) uint8_t g_VB[NH * IMG_HEAD];
__device__ __align__(1024) uint8_t g_QA[NH * IMG_HEAD];
__device__ __align__(1024) uint8_t g_KA[NH * IMG_HEAD];
__device__ __align__(1024) uint4 g_PHIQ[NH * 32 * 3 * 128];
__device__ __align__(1024) float4 g_KVP[NH * 16 * 288];
__device__ __align__(1024) float g_KMAX[NH * 128];
__device__ __align__(1024) float2 g_GATE[SEQ];
__device__ __align__(1024) uint8_t g_OAB[16 * 20 * 16384];
__device__ __align__(1024) uint8_t g_WOI[8 * 20 * 10240];

__device__ __forceinline__ uint32_t smem_u32(const void* p) { return (uint32_t)__cvta_generic_to_shared(p); }
__device__ __forceinline__ void mbar_init(uint32_t a, uint32_t c) { asm volatile("mbarrier.init.shared::cta.b64 [%0], %1;" ::"r"(a), "r"(c) : "memory"); }
__device__ __forceinline__ void mbar_expect(uint32_t a, uint32_t b) { asm volatile("mbarrier.arrive.expect_tx.shared::cta.b64 _, [%0], %1;" ::"r"(a), "r"(b) : "memory"); }
__device__ __forceinline__ void mbar_arrive(uint32_t a) { asm volatile("mbarrier.arrive.shared::cta.b64 _, [%0];" ::"r"(a) : "memory"); }
__device__ __forceinline__ void mbar_wait(uint32_t a, uint32_t ph) {
  asm volatile(
      "{\n.reg .pred p;\n.reg .u32 n;\nmov.u32 n, 0;\n"
      "W_%=:\nmbarrier.try_wait.parity.shared::cta.b64 p, [%0], %1;\n@p bra D_%=;\n"
      "add.u32 n, n, 1;\nsetp.lt.u32 p, n, 4000000;\n@p bra W_%=;\ntrap;\nD_%=:\n}\n" ::"r"(a), "r"(ph) : "memory");
}
__device__ __forceinline__ void tma2(uint32_t dst, const CUtensorMap* m, int c0, int c1, uint32_t bar) {
  asm volatile("cp.async.bulk.tensor.2d.shared::cluster.global.mbarrier::complete_tx::bytes [%0], [%1, {%3,%4}], [%2];" ::"r"(dst), "l"(m), "r"(bar), "r"(c0), "r"(c1) : "memory");
}
__device__ __forceinline__ void tma3(uint32_t dst, const CUtensorMap* m, int c0, int c1, int c2, uint32_t bar) {
  asm volatile("cp.async.bulk.tensor.3d.shared::cluster.global.mbarrier::complete_tx::bytes [%0], [%1, {%3,%4,%5}], [%2];" ::"r"(dst), "l"(m), "r"(bar), "r"(c0), "r"(c1), "r"(c2) : "memory");
}
__device__ __forceinline__ void bulk_g2s(uint32_t dst, const void* src, uint32_t bytes, uint32_t bar) {
  asm volatile("cp.async.bulk.shared::cluster.global.mbarrier::complete_tx::bytes [%0], [%1], %2, [%3];" ::"r"(dst), "l"(src), "r"(bytes), "r"(bar) : "memory");
}
__device__ __forceinline__ void prefetch_l2(const void* src, uint32_t bytes) { asm volatile("cp.async.bulk.prefetch.L2.global [%0], %1;" ::"l"(src), "r"(bytes) : "memory"); }
__device__ __forceinline__ void fence_async_smem() { asm volatile("fence.proxy.async.shared::cta;" ::: "memory"); }
__device__ __forceinline__ void fence_async_all() { asm volatile("fence.proxy.async;" ::: "memory"); }
__device__ __forceinline__ void bar_sync(int id, int n) { asm volatile("bar.sync %0, %1;" ::"r"(id), "r"(n) : "memory"); }
__device__ __forceinline__ void bar_arrive(int id, int n) { asm volatile("bar.arrive %0, %1;" ::"r"(id), "r"(n) : "memory"); }
__device__ __forceinline__ void pdl_wait() { asm volatile("griddepcontrol.wait;" ::: "memory"); }
__device__ __forceinline__ void pdl_launch() { asm volatile("griddepcontrol.launch_dependents;" ::: "memory"); }
__device__ __forceinline__ void wg_fence() { asm volatile("wgmma.fence.sync.aligned;" ::: "memory"); }
__device__ __forceinline__ void wg_commit() { asm volatile("wgmma.commit_group.sync.aligned;" ::: "memory"); }
template <int N> __device__ __forceinline__ void wg_wait() { asm volatile("wgmma.wait_group.sync.aligned %0;" ::"n"(N) : "memory"); }
template <int N> __device__ __forceinline__ void reg_inc() { asm volatile("setmaxnreg.inc.sync.aligned.u32 %0;" ::"n"(N)); }
template <int N> __device__ __forceinline__ void reg_dec() { asm volatile("setmaxnreg.dec.sync.aligned.u32 %0;" ::"n"(N)); }
template <int N> __device__ __forceinline__ void pin(float (&r)[N]) {
#pragma unroll
  for (int i = 0; i < N; i++) asm volatile("" : "+f"(r[i])::"memory");
}
template <int N> __device__ __forceinline__ void pin(uint32_t (&r)[N]) {
#pragma unroll
  for (int i = 0; i < N; i++) asm volatile("" : "+r"(r[i])::"memory");
}
__device__ __forceinline__ uint64_t mkdesc(uint32_t addr, uint32_t lbo, uint32_t sbo, uint32_t swz) {
  return (uint64_t)((addr & 0x3FFFF) >> 4) | ((uint64_t)(lbo >> 4) << 16) | ((uint64_t)(sbo >> 4) << 32) | ((uint64_t)swz << 62);
}
__device__ __forceinline__ float ex2(float x) { float y; asm("ex2.approx.ftz.f32 %0, %1;" : "=f"(y) : "f"(x)); return y; }
__device__ __forceinline__ float rcp(float x) { float y; asm("rcp.approx.ftz.f32 %0, %1;" : "=f"(y) : "f"(x)); return y; }
__device__ __forceinline__ float sqrt_ap(float x) { float y; asm("sqrt.approx.f32 %0, %1;" : "=f"(y) : "f"(x)); return y; }
__device__ __forceinline__ uint32_t packbf(float lo, float hi) { uint32_t d; asm("cvt.rn.bf16x2.f32 %0, %1, %2;" : "=r"(d) : "f"(hi), "f"(lo)); return d; }
__device__ __forceinline__ float bf_lo(uint32_t v) { return __uint_as_float(v << 16); }
__device__ __forceinline__ float bf_hi(uint32_t v) { return __uint_as_float(v & 0xFFFF0000u); }
__device__ __forceinline__ float bf_round(float x) { return bf_lo(packbf(x, 0.f)); }
__device__ __forceinline__ uint32_t ldg_cg(const void* p) { uint32_t v; asm volatile("ld.global.cg.b32 %0, [%1];" : "=r"(v) : "l"(p) : "memory"); return v; }
__device__ __forceinline__ uint4 ldg_cg4(const void* p) { uint4 v; asm volatile("ld.global.cg.v4.b32 {%0,%1,%2,%3}, [%4];" : "=r"(v.x), "=r"(v.y), "=r"(v.z), "=r"(v.w) : "l"(p) : "memory"); return v; }
__device__ __forceinline__ void sts32(uint32_t a, uint32_t v) { asm volatile("st.shared.b32 [%0], %1;" ::"r"(a), "r"(v) : "memory"); }
__device__ __forceinline__ void stsm4(uint32_t a, uint32_t r0, uint32_t r1, uint32_t r2, uint32_t r3) {
  asm volatile("stmatrix.sync.aligned.m8n8.x4.shared.b16 [%0], {%1,%2,%3,%4};" ::"r"(a), "r"(r0), "r"(r1), "r"(r2), "r"(r3) : "memory");
}

__device__ __forceinline__ void mma_n192_ss_tb(float (&d)[96], uint64_t adesc, uint64_t bdesc, int acc) {
  asm volatile("{\n.reg .pred p;\nsetp.ne.b32 p, %98, 0;\n"
      "wgmma.mma_async.sync.aligned.m64n192k16.f32.bf16.bf16 "
      "{%0,%1,%2,%3,%4,%5,%6,%7,%8,%9,%10,%11,%12,%13,%14,%15,"
      "%16,%17,%18,%19,%20,%21,%22,%23,%24,%25,%26,%27,%28,%29,%30,%31,"
      "%32,%33,%34,%35,%36,%37,%38,%39,%40,%41,%42,%43,%44,%45,%46,%47,"
      "%48,%49,%50,%51,%52,%53,%54,%55,%56,%57,%58,%59,%60,%61,%62,%63,"
      "%64,%65,%66,%67,%68,%69,%70,%71,%72,%73,%74,%75,%76,%77,%78,%79,"
      "%80,%81,%82,%83,%84,%85,%86,%87,%88,%89,%90,%91,%92,%93,%94,%95}, "
      "%96, %97, p, 1, 1, 0, 1;\n}\n"
      : "+f"(d[0]), "+f"(d[1]), "+f"(d[2]), "+f"(d[3]), "+f"(d[4]), "+f"(d[5]), "+f"(d[6]), "+f"(d[7]),
        "+f"(d[8]), "+f"(d[9]), "+f"(d[10]), "+f"(d[11]), "+f"(d[12]), "+f"(d[13]), "+f"(d[14]), "+f"(d[15]),
        "+f"(d[16]), "+f"(d[17]), "+f"(d[18]), "+f"(d[19]), "+f"(d[20]), "+f"(d[21]), "+f"(d[22]), "+f"(d[23]),
        "+f"(d[24]), "+f"(d[25]), "+f"(d[26]), "+f"(d[27]), "+f"(d[28]), "+f"(d[29]), "+f"(d[30]), "+f"(d[31]),
        "+f"(d[32]), "+f"(d[33]), "+f"(d[34]), "+f"(d[35]), "+f"(d[36]), "+f"(d[37]), "+f"(d[38]), "+f"(d[39]),
        "+f"(d[40]), "+f"(d[41]), "+f"(d[42]), "+f"(d[43]), "+f"(d[44]), "+f"(d[45]), "+f"(d[46]), "+f"(d[47]),
        "+f"(d[48]), "+f"(d[49]), "+f"(d[50]), "+f"(d[51]), "+f"(d[52]), "+f"(d[53]), "+f"(d[54]), "+f"(d[55]),
        "+f"(d[56]), "+f"(d[57]), "+f"(d[58]), "+f"(d[59]), "+f"(d[60]), "+f"(d[61]), "+f"(d[62]), "+f"(d[63]),
        "+f"(d[64]), "+f"(d[65]), "+f"(d[66]), "+f"(d[67]), "+f"(d[68]), "+f"(d[69]), "+f"(d[70]), "+f"(d[71]),
        "+f"(d[72]), "+f"(d[73]), "+f"(d[74]), "+f"(d[75]), "+f"(d[76]), "+f"(d[77]), "+f"(d[78]), "+f"(d[79]),
        "+f"(d[80]), "+f"(d[81]), "+f"(d[82]), "+f"(d[83]), "+f"(d[84]), "+f"(d[85]), "+f"(d[86]), "+f"(d[87]),
        "+f"(d[88]), "+f"(d[89]), "+f"(d[90]), "+f"(d[91]), "+f"(d[92]), "+f"(d[93]), "+f"(d[94]), "+f"(d[95])
      : "l"(adesc), "l"(bdesc), "r"(acc));
}
__device__ __forceinline__ void mma_n48_ss_tb(float (&d)[24], uint64_t adesc, uint64_t bdesc, int acc) {
  asm volatile("{\n.reg .pred p;\nsetp.ne.b32 p, %26, 0;\n"
      "wgmma.mma_async.sync.aligned.m64n48k16.f32.bf16.bf16 "
      "{%0,%1,%2,%3,%4,%5,%6,%7,%8,%9,%10,%11,%12,%13,%14,%15,"
      "%16,%17,%18,%19,%20,%21,%22,%23}, "
      "%24, %25, p, 1, 1, 0, 1;\n}\n"
      : "+f"(d[0]), "+f"(d[1]), "+f"(d[2]), "+f"(d[3]), "+f"(d[4]), "+f"(d[5]), "+f"(d[6]), "+f"(d[7]),
        "+f"(d[8]), "+f"(d[9]), "+f"(d[10]), "+f"(d[11]), "+f"(d[12]), "+f"(d[13]), "+f"(d[14]), "+f"(d[15]),
        "+f"(d[16]), "+f"(d[17]), "+f"(d[18]), "+f"(d[19]), "+f"(d[20]), "+f"(d[21]), "+f"(d[22]), "+f"(d[23])
      : "l"(adesc), "l"(bdesc), "r"(acc));
}
__device__ __forceinline__ void mma_n192_rs_tb(float (&d)[96], uint32_t a0, uint32_t a1, uint32_t a2, uint32_t a3, uint64_t bdesc, int acc) {
  asm volatile("{\n.reg .pred p;\nsetp.ne.b32 p, %101, 0;\n"
      "wgmma.mma_async.sync.aligned.m64n192k16.f32.bf16.bf16 "
      "{%0,%1,%2,%3,%4,%5,%6,%7,%8,%9,%10,%11,%12,%13,%14,%15,"
      "%16,%17,%18,%19,%20,%21,%22,%23,%24,%25,%26,%27,%28,%29,%30,%31,"
      "%32,%33,%34,%35,%36,%37,%38,%39,%40,%41,%42,%43,%44,%45,%46,%47,"
      "%48,%49,%50,%51,%52,%53,%54,%55,%56,%57,%58,%59,%60,%61,%62,%63,"
      "%64,%65,%66,%67,%68,%69,%70,%71,%72,%73,%74,%75,%76,%77,%78,%79,"
      "%80,%81,%82,%83,%84,%85,%86,%87,%88,%89,%90,%91,%92,%93,%94,%95}, "
      "{%96,%97,%98,%99}, %100, p, 1, 1, 1;\n}\n"
      : "+f"(d[0]), "+f"(d[1]), "+f"(d[2]), "+f"(d[3]), "+f"(d[4]), "+f"(d[5]), "+f"(d[6]), "+f"(d[7]),
        "+f"(d[8]), "+f"(d[9]), "+f"(d[10]), "+f"(d[11]), "+f"(d[12]), "+f"(d[13]), "+f"(d[14]), "+f"(d[15]),
        "+f"(d[16]), "+f"(d[17]), "+f"(d[18]), "+f"(d[19]), "+f"(d[20]), "+f"(d[21]), "+f"(d[22]), "+f"(d[23]),
        "+f"(d[24]), "+f"(d[25]), "+f"(d[26]), "+f"(d[27]), "+f"(d[28]), "+f"(d[29]), "+f"(d[30]), "+f"(d[31]),
        "+f"(d[32]), "+f"(d[33]), "+f"(d[34]), "+f"(d[35]), "+f"(d[36]), "+f"(d[37]), "+f"(d[38]), "+f"(d[39]),
        "+f"(d[40]), "+f"(d[41]), "+f"(d[42]), "+f"(d[43]), "+f"(d[44]), "+f"(d[45]), "+f"(d[46]), "+f"(d[47]),
        "+f"(d[48]), "+f"(d[49]), "+f"(d[50]), "+f"(d[51]), "+f"(d[52]), "+f"(d[53]), "+f"(d[54]), "+f"(d[55]),
        "+f"(d[56]), "+f"(d[57]), "+f"(d[58]), "+f"(d[59]), "+f"(d[60]), "+f"(d[61]), "+f"(d[62]), "+f"(d[63]),
        "+f"(d[64]), "+f"(d[65]), "+f"(d[66]), "+f"(d[67]), "+f"(d[68]), "+f"(d[69]), "+f"(d[70]), "+f"(d[71]),
        "+f"(d[72]), "+f"(d[73]), "+f"(d[74]), "+f"(d[75]), "+f"(d[76]), "+f"(d[77]), "+f"(d[78]), "+f"(d[79]),
        "+f"(d[80]), "+f"(d[81]), "+f"(d[82]), "+f"(d[83]), "+f"(d[84]), "+f"(d[85]), "+f"(d[86]), "+f"(d[87]),
        "+f"(d[88]), "+f"(d[89]), "+f"(d[90]), "+f"(d[91]), "+f"(d[92]), "+f"(d[93]), "+f"(d[94]), "+f"(d[95])
      : "r"(a0), "r"(a1), "r"(a2), "r"(a3), "l"(bdesc), "r"(acc));
}
__device__ __forceinline__ void mma_n48_rs_tb(float (&d)[24], uint32_t a0, uint32_t a1, uint32_t a2, uint32_t a3, uint64_t bdesc, int acc) {
  asm volatile("{\n.reg .pred p;\nsetp.ne.b32 p, %29, 0;\n"
      "wgmma.mma_async.sync.aligned.m64n48k16.f32.bf16.bf16 "
      "{%0,%1,%2,%3,%4,%5,%6,%7,%8,%9,%10,%11,%12,%13,%14,%15,"
      "%16,%17,%18,%19,%20,%21,%22,%23}, "
      "{%24,%25,%26,%27}, %28, p, 1, 1, 1;\n}\n"
      : "+f"(d[0]), "+f"(d[1]), "+f"(d[2]), "+f"(d[3]), "+f"(d[4]), "+f"(d[5]), "+f"(d[6]), "+f"(d[7]),
        "+f"(d[8]), "+f"(d[9]), "+f"(d[10]), "+f"(d[11]), "+f"(d[12]), "+f"(d[13]), "+f"(d[14]), "+f"(d[15]),
        "+f"(d[16]), "+f"(d[17]), "+f"(d[18]), "+f"(d[19]), "+f"(d[20]), "+f"(d[21]), "+f"(d[22]), "+f"(d[23])
      : "r"(a0), "r"(a1), "r"(a2), "r"(a3), "l"(bdesc), "r"(acc));
}
__device__ __forceinline__ void mma_n128_ss(float (&d)[64], uint64_t adesc, uint64_t bdesc, int acc) {
  asm volatile("{\n.reg .pred p;\nsetp.ne.b32 p, %66, 0;\n"
      "wgmma.mma_async.sync.aligned.m64n128k16.f32.bf16.bf16 "
      "{%0,%1,%2,%3,%4,%5,%6,%7,%8,%9,%10,%11,%12,%13,%14,%15,"
      "%16,%17,%18,%19,%20,%21,%22,%23,%24,%25,%26,%27,%28,%29,%30,%31,"
      "%32,%33,%34,%35,%36,%37,%38,%39,%40,%41,%42,%43,%44,%45,%46,%47,"
      "%48,%49,%50,%51,%52,%53,%54,%55,%56,%57,%58,%59,%60,%61,%62,%63}, "
      "%64, %65, p, 1, 1, 0, 0;\n}\n"
      : "+f"(d[0]), "+f"(d[1]), "+f"(d[2]), "+f"(d[3]), "+f"(d[4]), "+f"(d[5]), "+f"(d[6]), "+f"(d[7]),
        "+f"(d[8]), "+f"(d[9]), "+f"(d[10]), "+f"(d[11]), "+f"(d[12]), "+f"(d[13]), "+f"(d[14]), "+f"(d[15]),
        "+f"(d[16]), "+f"(d[17]), "+f"(d[18]), "+f"(d[19]), "+f"(d[20]), "+f"(d[21]), "+f"(d[22]), "+f"(d[23]),
        "+f"(d[24]), "+f"(d[25]), "+f"(d[26]), "+f"(d[27]), "+f"(d[28]), "+f"(d[29]), "+f"(d[30]), "+f"(d[31]),
        "+f"(d[32]), "+f"(d[33]), "+f"(d[34]), "+f"(d[35]), "+f"(d[36]), "+f"(d[37]), "+f"(d[38]), "+f"(d[39]),
        "+f"(d[40]), "+f"(d[41]), "+f"(d[42]), "+f"(d[43]), "+f"(d[44]), "+f"(d[45]), "+f"(d[46]), "+f"(d[47]),
        "+f"(d[48]), "+f"(d[49]), "+f"(d[50]), "+f"(d[51]), "+f"(d[52]), "+f"(d[53]), "+f"(d[54]), "+f"(d[55]),
        "+f"(d[56]), "+f"(d[57]), "+f"(d[58]), "+f"(d[59]), "+f"(d[60]), "+f"(d[61]), "+f"(d[62]), "+f"(d[63])
      : "l"(adesc), "l"(bdesc), "r"(acc));
}
__device__ __forceinline__ void mma_n80_ss_tb(float (&d)[40], uint64_t adesc, uint64_t bdesc, int acc) {
  asm volatile("{\n.reg .pred p;\nsetp.ne.b32 p, %42, 0;\n"
      "wgmma.mma_async.sync.aligned.m64n80k16.f32.bf16.bf16 "
      "{%0,%1,%2,%3,%4,%5,%6,%7,%8,%9,%10,%11,%12,%13,%14,%15,"
      "%16,%17,%18,%19,%20,%21,%22,%23,%24,%25,%26,%27,%28,%29,%30,%31,"
      "%32,%33,%34,%35,%36,%37,%38,%39}, "
      "%40, %41, p, 1, 1, 0, 1;\n}\n"
      : "+f"(d[0]), "+f"(d[1]), "+f"(d[2]), "+f"(d[3]), "+f"(d[4]), "+f"(d[5]), "+f"(d[6]), "+f"(d[7]),
        "+f"(d[8]), "+f"(d[9]), "+f"(d[10]), "+f"(d[11]), "+f"(d[12]), "+f"(d[13]), "+f"(d[14]), "+f"(d[15]),
        "+f"(d[16]), "+f"(d[17]), "+f"(d[18]), "+f"(d[19]), "+f"(d[20]), "+f"(d[21]), "+f"(d[22]), "+f"(d[23]),
        "+f"(d[24]), "+f"(d[25]), "+f"(d[26]), "+f"(d[27]), "+f"(d[28]), "+f"(d[29]), "+f"(d[30]), "+f"(d[31]),
        "+f"(d[32]), "+f"(d[33]), "+f"(d[34]), "+f"(d[35]), "+f"(d[36]), "+f"(d[37]), "+f"(d[38]), "+f"(d[39])
      : "l"(adesc), "l"(bdesc), "r"(acc));
}
__device__ __forceinline__ void mma_n24_rs_tb(float (&d)[12], uint32_t a0, uint32_t a1, uint32_t a2, uint32_t a3, uint64_t bdesc, int acc) {
  asm volatile("{\n.reg .pred p;\nsetp.ne.b32 p, %17, 0;\n"
      "wgmma.mma_async.sync.aligned.m64n24k16.f32.bf16.bf16 "
      "{%0,%1,%2,%3,%4,%5,%6,%7,%8,%9,%10,%11}, "
      "{%12,%13,%14,%15}, %16, p, 1, 1, 1;\n}\n"
      : "+f"(d[0]), "+f"(d[1]), "+f"(d[2]), "+f"(d[3]), "+f"(d[4]), "+f"(d[5]), "+f"(d[6]), "+f"(d[7]),
        "+f"(d[8]), "+f"(d[9]), "+f"(d[10]), "+f"(d[11])
      : "r"(a0), "r"(a1), "r"(a2), "r"(a3), "l"(bdesc), "r"(acc));
}
__device__ __forceinline__ void mma_n24_ss_tatb(float (&d)[12], uint64_t adesc, uint64_t bdesc, int acc) {
  asm volatile("{\n.reg .pred p;\nsetp.ne.b32 p, %14, 0;\n"
      "wgmma.mma_async.sync.aligned.m64n24k16.f32.bf16.bf16 "
      "{%0,%1,%2,%3,%4,%5,%6,%7,%8,%9,%10,%11}, "
      "%12, %13, p, 1, 1, 1, 1;\n}\n"
      : "+f"(d[0]), "+f"(d[1]), "+f"(d[2]), "+f"(d[3]), "+f"(d[4]), "+f"(d[5]), "+f"(d[6]), "+f"(d[7]),
        "+f"(d[8]), "+f"(d[9]), "+f"(d[10]), "+f"(d[11])
      : "l"(adesc), "l"(bdesc), "r"(acc));
}

constexpr int K1_STAGE = 47104;
constexpr int K1_NST = 4;
constexpr int K1_VST = K1_NST * K1_STAGE;
constexpr int K1_PHK = K1_VST + 24576;
constexpr int K1_WPH = K1_PHK + 12288 + 256;
constexpr int K1_BAR = K1_WPH + 6144;
constexpr int K1_SMEM = K1_BAR + 128;

template <int SEC, int J, int HF>
__device__ __forceinline__ void grp(const float (&a1)[96], const float (&a2)[24], float& v0, float& v1) {
  if constexpr (J < 8) { v0 = a1[(8 * SEC + J) * 4 + 2 * HF]; v1 = a1[(8 * SEC + J) * 4 + 2 * HF + 1]; }
  else { v0 = a2[(2 * SEC + J - 8) * 4 + 2 * HF]; v1 = a2[(2 * SEC + J - 8) * 4 + 2 * HF + 1]; }
}

template <int SEC, int HF, bool TO_SMEM, bool NORM>
__device__ __forceinline__ void store_section(const float (&a1)[96], const float (&a2)[24], float scale, uint32_t ext01, uint32_t ext23,
                                              uint8_t* gdst, uint32_t sdst, int head_stride, int t, float (&nrm)[4]) {
#pragma unroll
  for (int pr = 0; pr < 2; pr++) {
    float v[5][2];
    if (pr == 0) {
      grp<SEC, 0, HF>(a1, a2, v[0][0], v[0][1]); grp<SEC, 1, HF>(a1, a2, v[1][0], v[1][1]); grp<SEC, 2, HF>(a1, a2, v[2][0], v[2][1]);
      grp<SEC, 3, HF>(a1, a2, v[3][0], v[3][1]); grp<SEC, 4, HF>(a1, a2, v[4][0], v[4][1]);
    } else {
      grp<SEC, 5, HF>(a1, a2, v[0][0], v[0][1]); grp<SEC, 6, HF>(a1, a2, v[1][0], v[1][1]); grp<SEC, 7, HF>(a1, a2, v[2][0], v[2][1]);
      grp<SEC, 8, HF>(a1, a2, v[3][0], v[3][1]); grp<SEC, 9, HF>(a1, a2, v[4][0], v[4][1]);
    }
    uint32_t p[5];
#pragma unroll
    for (int j = 0; j < 5; j++) p[j] = packbf(v[j][0] * scale, v[j][1] * scale);
    const uint32_t ext = (t & 1) ? ext23 : ext01;
    const uint32_t e2 = (t < 2) ? p[2] : ext;
    const uint32_t o2 = (t < 2) ? ext : p[2];
    const int he = 2 * pr, ho = 2 * pr + 1;
    if (TO_SMEM) {
      sts32(sdst + he * head_stride, p[0]); sts32(sdst + he * head_stride + 128, p[1]); sts32(sdst + he * head_stride + 256, e2);
      sts32(sdst + ho * head_stride, p[3]); sts32(sdst + ho * head_stride + 128, p[4]); sts32(sdst + ho * head_stride + 256, o2);
    } else {
      *(uint32_t*)(gdst + (size_t)he * head_stride) = p[0]; *(uint32_t*)(gdst + (size_t)he * head_stride + 128) = p[1];
      *(uint32_t*)(gdst + (size_t)he * head_stride + 256) = e2;
      *(uint32_t*)(gdst + (size_t)ho * head_stride) = p[3]; *(uint32_t*)(gdst + (size_t)ho * head_stride + 128) = p[4];
      *(uint32_t*)(gdst + (size_t)ho * head_stride + 256) = o2;
    }
    if (NORM) {
      const float h = v[2][0] * v[2][0] + v[2][1] * v[2][1];
      float se = v[0][0] * v[0][0] + v[0][1] * v[0][1] + v[1][0] * v[1][0] + v[1][1] * v[1][1] + ((t < 2) ? h : 0.f);
      float so = v[3][0] * v[3][0] + v[3][1] * v[3][1] + v[4][0] * v[4][0] + v[4][1] * v[4][1] + ((t < 2) ? 0.f : h);
      se += __shfl_xor_sync(~0u, se, 1); so += __shfl_xor_sync(~0u, so, 1);
      se += __shfl_xor_sync(~0u, se, 2); so += __shfl_xor_sync(~0u, so, 2);
      nrm[he] = fmaxf(nrm[he], se); nrm[ho] = fmaxf(nrm[ho], so);
    }
  }
}

__device__ __forceinline__ void hedgehog(const float (&p)[12], uint32_t (&f)[12], int t) {
#pragma unroll
  for (int hf = 0; hf < 2; hf++) {
    float v[6] = {p[2 * hf], p[2 * hf + 1], p[4 + 2 * hf], p[5 + 2 * hf], p[8 + 2 * hf], p[9 + 2 * hf]};
    float mx = fmaxf(fmaxf(fmaxf(v[0], v[1]), fmaxf(v[2], v[3])), fmaxf(v[4], v[5]));
    float mn = fminf(fminf(fminf(v[0], v[1]), fminf(v[2], v[3])), fminf(v[4], v[5]));
    mx = fmaxf(mx, __shfl_xor_sync(~0u, mx, 1)); mn = fminf(mn, __shfl_xor_sync(~0u, mn, 1));
    mx = fmaxf(mx, __shfl_xor_sync(~0u, mx, 2)); mn = fminf(mn, __shfl_xor_sync(~0u, mn, 2));
    const float bp = -mx * LOG2E, bn = mn * LOG2E;
    float ep[6], en[6];
#pragma unroll
    for (int i = 0; i < 6; i++) { ep[i] = ex2(fmaf(v[i], LOG2E, bp)); en[i] = ex2(fmaf(v[i], -LOG2E, bn)); }
    const float keep = (t < 2) ? 1.f : 0.f;
    float sp = (ep[0] + ep[1]) + (ep[2] + ep[3]) + keep * (ep[4] + ep[5]);
    float sn = (en[0] + en[1]) + (en[2] + en[3]) + keep * (en[4] + en[5]);
    sp += __shfl_xor_sync(~0u, sp, 1); sn += __shfl_xor_sync(~0u, sn, 1);
    sp += __shfl_xor_sync(~0u, sp, 2); sn += __shfl_xor_sync(~0u, sn, 2);
    const float rp = rcp(sp), rn = rcp(sn), rp2 = rp * keep, rn2 = rn * keep;
    f[0 + hf] = packbf(ep[0] * rp, ep[1] * rp);
    f[2 + hf] = packbf(ep[2] * rp, ep[3] * rp);
    f[4 + hf] = packbf(ep[4] * rp2, ep[5] * rp2);
    f[6 + hf] = packbf(en[0] * rn, en[1] * rn);
    f[8 + hf] = packbf(en[2] * rn, en[3] * rn);
    f[10 + hf] = packbf(en[4] * rn2, en[5] * rn2);
  }
}

__global__ void __launch_bounds__(512, 1)
k1_qkv(const __grid_constant__ CUtensorMap mx, const __grid_constant__ CUtensorMap mwa64, const __grid_constant__ CUtensorMap mwa16,
       const __grid_constant__ CUtensorMap mwb64, const __grid_constant__ CUtensorMap mwb16,
       const __nv_bfloat16* __restrict__ x, const __nv_bfloat16* __restrict__ wphi, const __nv_bfloat16* __restrict__ gate_w,
       const uint8_t* __restrict__ wa, const uint8_t* __restrict__ wb) {
  extern __shared__ __align__(1024) uint8_t smem[];
  const uint32_t sb = smem_u32(smem);
  const uint32_t full = sb + K1_BAR, empty = full + 8 * K1_NST;
  const int warp = __shfl_sync(~0u, threadIdx.x >> 5, 0), lane = threadIdx.x & 31, wg = warp >> 2;
  const int bid = blockIdx.x;
  const int mt = (bid & 3) + 4 * (bid >> 5), hg = (bid >> 2) & 7;
  if (threadIdx.x == 0) {
    for (int i = 0; i < K1_NST; i++) { mbar_init(full + 8 * i, 1); mbar_init(empty + 8 * i, 2); }
    asm volatile("fence.mbarrier_init.release.cluster;" ::: "memory");
    pdl_launch();
  }
  __syncthreads();

  if (wg == 3) {
    reg_dec<40>();
    if (warp == 12) {
      if (lane == 0) {
        for (int it = 0; it < 20; it++) {
          const int s = it % K1_NST, ks = it % 10;
          if (it >= K1_NST) mbar_wait(empty + 8 * s, ((it / K1_NST) - 1) & 1);
          const uint32_t d = sb + s * K1_STAGE, b = full + 8 * s;
          mbar_expect(b, K1_STAGE);
          tma2(d, &mx, ks * 64, mt * 128, b);
          tma3(d + 16384, it < 10 ? &mwa64 : &mwb64, hg * 80, ks * 64, 0, b);
          tma3(d + 40960, it < 10 ? &mwa16 : &mwb16, hg * 80 + 64, ks * 64, 0, b);
        }
      }
    } else {
      if (warp == 13 && lane == 0) { prefetch_l2(wa + (size_t)bid * 19200, 19200); prefetch_l2(wb + (size_t)bid * 19200, 19200); }
      uint2 gw[5];
#pragma unroll
      for (int i = 0; i < 5; i++) gw[i] = *(const uint2*)(gate_w + i * 128 + lane * 4);
      for (int r = warp - 13; r < 16; r += 3) {
        const int row = mt * 128 + hg * 16 + r;
        float acc = 0.f;
#pragma unroll
        for (int i = 0; i < 5; i++) {
          const uint2 xv = *(const uint2*)(x + (size_t)row * DM + i * 128 + lane * 4);
          uint32_t p0, p1;
          asm("mul.rn.bf16x2 %0, %1, %2;" : "=r"(p0) : "r"(xv.x), "r"(gw[i].x));
          asm("mul.rn.bf16x2 %0, %1, %2;" : "=r"(p1) : "r"(xv.y), "r"(gw[i].y));
          acc += (bf_lo(p0) + bf_hi(p0)) + (bf_lo(p1) + bf_hi(p1));
        }
#pragma unroll
        for (int o = 16; o; o >>= 1) acc += __shfl_xor_sync(~0u, acc, o);
        if (lane == 0) {
          const float g = bf_round(1.f / (1.f + __expf(-bf_round(acc))));
          g_GATE[row] = make_float2(g, bf_round(1.f - g));
        }
      }
    }
  } else if (wg == 2) {
    reg_dec<112>();
    const int tid = threadIdx.x - 256, w4 = warp & 3, t = lane & 3;
    for (int e = tid; e < 4 * 768; e += 128) {
      const int i = e / 768, r = e % 768, kg = r / 192, nc = (r % 192) / 64, kr = (r % 64) / 8, ne = r % 8;
      const int slot = kg * 8 + kr, n = nc * 8 + ne;
      int d = -1;
      if (i & 1) { if (slot < 16) d = slot + 4; else if (slot >= 20 && slot < 24) d = slot - 20; }
      else if (slot < 20) d = slot;
      const int f = n < 20 ? n : n - 4;
      const unsigned short val = d >= 0 ? *(const unsigned short*)(wphi + ((size_t)(hg * 4 + i) * 20 + d) * 20 + f) : (unsigned short)0;
      *(unsigned short*)(smem + K1_WPH + e * 2) = val;
    }
    fence_async_smem();
    bar_sync(1, 384);
    const size_t rowoff = (size_t)(mt * 16 + w4 * 2) * 384 + lane * 4;
#pragma unroll 1
    for (int item = 0; item < 8; item++) {
      const int isk = item >> 2, i = item & 3, h = hg * 4 + i;
      const uint8_t* src = (isk ? g_KA : g_QA) + (size_t)h * IMG_HEAD + rowoff;
      uint32_t a[2][6];
#pragma unroll
      for (int w = 0; w < 2; w++)
#pragma unroll
        for (int c = 0; c < 3; c++) { a[w][2 * c] = ldg_cg(src + w * 3072 + c * 128); a[w][2 * c + 1] = ldg_cg(src + w * 3072 + 384 + c * 128); }
      float p0[12], p1[12];
      const uint64_t wd = mkdesc(sb + K1_WPH + i * 1536, 384, 128, 0);
      wg_fence();
      mma_n24_rs_tb(p0, a[0][0], a[0][1], a[0][2], a[0][3], wd, 0);
      mma_n24_rs_tb(p0, a[0][4], a[0][5], 0u, 0u, wd + 48, 1);
      mma_n24_rs_tb(p1, a[1][0], a[1][1], a[1][2], a[1][3], wd, 0);
      mma_n24_rs_tb(p1, a[1][4], a[1][5], 0u, 0u, wd + 48, 1);
      wg_commit();
      wg_wait<0>();
      pin(p0); pin(p1);
      uint32_t f0[12], f1[12];
      hedgehog(p0, f0, t);
      hedgehog(p1, f1, t);
      if (!isk) {
        uint4* dst = g_PHIQ + ((size_t)(h * 32 + mt * 2) * 3) * 128 + tid;
#pragma unroll
        for (int ks = 0; ks < 3; ks++) {
          dst[ks * 128] = make_uint4(f0[4 * ks], f0[4 * ks + 1], f0[4 * ks + 2], f0[4 * ks + 3]);
          dst[(3 + ks) * 128] = make_uint4(f1[4 * ks], f1[4 * ks + 1], f1[4 * ks + 2], f1[4 * ks + 3]);
        }
      } else {
        const uint32_t pk = sb + K1_PHK + (w4 * 2 + ((lane >> 3) & 1)) * 768 + (lane >> 4) * 128 + (lane & 7) * 16;
#pragma unroll
        for (int ks = 0; ks < 3; ks++) {
          stsm4(pk + ks * 256, f0[4 * ks], f0[4 * ks + 1], f0[4 * ks + 2], f0[4 * ks + 3]);
          stsm4(pk + 6144 + ks * 256, f1[4 * ks], f1[4 * ks + 1], f1[4 * ks + 2], f1[4 * ks + 3]);
        }
        fence_async_smem();
        bar_sync(2, 128);
        float kv[12];
        const uint64_t ad = mkdesc(sb + K1_PHK, 768, 128, 0), vd = mkdesc(sb + K1_VST + i * 6144, 384, 128, 0);
        wg_fence();
#pragma unroll
        for (int ks = 0; ks < 8; ks++) mma_n24_ss_tatb(kv, ad + ks * 96, vd + ks * 48, ks);
        wg_commit();
        wg_wait<0>();
        pin(kv);
        if (w4 < 3) {
          float4* dst = g_KVP + (size_t)(h * 16 + mt) * 288 + w4 * 96 + lane;
          dst[0] = make_float4(kv[0], kv[1], kv[2], kv[3]);
          dst[32] = make_float4(kv[4], kv[5], kv[6], kv[7]);
          dst[64] = make_float4(kv[8], kv[9], kv[10], kv[11]);
        }
        bar_sync(2, 128);
      }
    }
  } else {
    reg_inc<176>();
    const int w4 = warp & 3, t = lane & 3;
    float a1[96], a2[24];
#pragma unroll 1
    for (int tile = 0; tile < 2; tile++) {
#pragma unroll 1
      for (int ks = 0; ks < 10; ks++) {
        const int it = tile * 10 + ks, s = it % K1_NST;
        mbar_wait(full + 8 * s, (it / K1_NST) & 1);
        const uint32_t st = sb + s * K1_STAGE;
        const uint64_t ad = mkdesc(st + wg * 8192, 16, 1024, 1);
        const uint64_t b1 = mkdesc(st + 16384, 8192, 1024, 1);
        const uint64_t b2 = mkdesc(st + 40960, 2048, 256, 3);
        wg_fence();
#pragma unroll
        for (int kk = 0; kk < 4; kk++) {
          mma_n192_ss_tb(a1, ad + kk * 2, b1 + kk * 128, ks | kk);
          mma_n48_ss_tb(a2, ad + kk * 2, b2 + kk * 32, ks | kk);
        }
        wg_commit();
        if (ks > 0) {
          wg_wait<1>();
          if ((threadIdx.x & 127) == 0) mbar_arrive(empty + 8 * ((it - 1) % K1_NST));
        }
      }
      wg_wait<0>();
      pin(a1); pin(a2);
      if ((threadIdx.x & 127) == 0) mbar_arrive(empty + 8 * ((tile * 10 + 9) % K1_NST));
      const int rg = wg * 8 + w4 * 2;
      const size_t goff = (size_t)(hg * 4) * IMG_HEAD + (size_t)(mt * 16 + rg) * 384 + lane * 4;
      float nrm[4] = {0.f, 0.f, 0.f, 0.f};
      if (tile == 0) {
        const uint32_t vs = sb + K1_VST + rg * 384 + lane * 4;
        store_section<0, 0, false, false>(a1, a2, 1.f, 0u, 0u, g_QA + goff, 0, IMG_HEAD, t, nrm);
        store_section<0, 1, false, false>(a1, a2, 1.f, 0u, 0u, g_QA + goff + 384, 0, IMG_HEAD, t, nrm);
        store_section<1, 0, false, false>(a1, a2, 1.f, 0u, 0u, g_KA + goff, 0, IMG_HEAD, t, nrm);
        store_section<1, 1, false, false>(a1, a2, 1.f, 0u, 0u, g_KA + goff + 384, 0, IMG_HEAD, t, nrm);
        store_section<2, 0, true, false>(a1, a2, 1.f, BF_ONE, 0u, nullptr, vs, 6144, t, nrm);
        store_section<2, 1, true, false>(a1, a2, 1.f, BF_ONE, 0u, nullptr, vs + 384, 6144, t, nrm);
        fence_async_smem();
        bar_arrive(1, 384);
      } else {
        const bool p0 = (POLY_MASK >> rg) & 1, p1 = (POLY_MASK >> (rg + 1)) & 1;
        const uint32_t kp01 = BF_ONE | (BF_MAGIC << 16), km01 = BF_ONE | (BF_MU_HI << 16);
        store_section<1, 0, false, true>(a1, a2, 1.f, p0 ? kp01 : km01, p0 ? 0u : BF_MU_LO, g_KB + goff, 0, IMG_HEAD, t, nrm);
        store_section<1, 1, false, true>(a1, a2, 1.f, p1 ? kp01 : km01, p1 ? 0u : BF_MU_LO, g_KB + goff + 384, 0, IMG_HEAD, t, nrm);
        store_section<2, 0, false, false>(a1, a2, p0 ? -1.f : 1.f, p0 ? (BF_ONE | 0x8000u) : BF_ONE, 0u, g_VB + goff, 0, IMG_HEAD, t, nrm);
        store_section<2, 1, false, false>(a1, a2, p1 ? -1.f : 1.f, p1 ? (BF_ONE | 0x8000u) : BF_ONE, 0u, g_VB + goff + 384, 0, IMG_HEAD, t, nrm);
        store_section<0, 0, false, false>(a1, a2, QSCALE, 0u, 0u, g_QB + goff, 0, IMG_HEAD, t, nrm);
        store_section<0, 1, false, false>(a1, a2, QSCALE, 0u, 0u, g_QB + goff + 384, 0, IMG_HEAD, t, nrm);
#pragma unroll
        for (int i = 0; i < 4; i++) {
          const uint32_t m = __reduce_max_sync(~0u, __float_as_uint(nrm[i]));
          if (lane == i) g_KMAX[(hg * 4 + i) * 128 + mt * 8 + wg * 4 + w4] = __uint_as_float(m);
        }
      }
    }
  }
}

constexpr int K2_K = 0, K2_V = IMG_HEAD, K2_Q = 2 * IMG_HEAD, K2_KV = K2_Q + 8 * 3072, K2_BAR = K2_KV + 2304, K2_SMEM = K2_BAR + 128;

__device__ __forceinline__ uint32_t exp2_bits(float y0, float y1, uint32_t cm, uint32_t neg1) {
  uint32_t w, m, r;
  asm("prmt.b32 %0, %1, %2, 0x6521;" : "=r"(w) : "r"(__float_as_uint(y0)), "r"(__float_as_uint(y1)));
  asm("lop3.b32 %0, %1, 0x007F007F, %2, 0xEA;" : "=r"(m) : "r"(w), "r"(cm));
  const uint32_t e = m * neg1 + w;
  asm("fma.rn.bf16x2 %0, %1, %2, %3;" : "=r"(r) : "r"(w), "r"(m), "r"(e));
  return r;
}
__device__ __forceinline__ void exp_tile(const float (&s)[64], uint32_t (&p)[32], uint32_t cm, uint32_t neg1) {
#pragma unroll
  for (int g = 0; g < 16; g++) {
    if ((POLY_MASK >> g) & 1) {
      p[2 * g] = exp2_bits(s[4 * g], s[4 * g + 1], cm, neg1);
      p[2 * g + 1] = exp2_bits(s[4 * g + 2], s[4 * g + 3], cm, neg1);
    } else {
      p[2 * g] = packbf(ex2(s[4 * g]), ex2(s[4 * g + 1]));
      p[2 * g + 1] = packbf(ex2(s[4 * g + 2]), ex2(s[4 * g + 3]));
    }
  }
}
__device__ __forceinline__ void issue_qk(float (&s)[64], uint64_t qd, uint64_t kd) {
  mma_n128_ss(s, qd, kd, 0);
  mma_n128_ss(s, (qd + 16) & ~(0x3FFFull << 16), (kd + 16) & ~(0x3FFFull << 16), 1);
}
__device__ __forceinline__ void issue_pv(float (&o)[12], const uint32_t (&p)[32], uint64_t vd, int acc) {
#pragma unroll
  for (int kk = 0; kk < 8; kk++) mma_n24_rs_tb(o, p[4 * kk], p[4 * kk + 1], p[4 * kk + 2], p[4 * kk + 3], vd + kk * 48, acc | kk);
}
__device__ __forceinline__ void attn_pair(float (&s0)[64], float (&s1)[64], uint32_t (&p0)[32], uint32_t (&p1)[32], float (&o)[12],
                                          uint64_t qd1, uint64_t kd1, uint64_t qd2, uint64_t kd2, uint64_t vd, int acc, uint32_t bar,
                                          uint32_t cm, uint32_t neg1) {
  wg_fence();
  issue_qk(s1, qd1, kd1);
  wg_commit();
  exp_tile(s0, p0, cm, neg1);
  wg_fence();
  issue_pv(o, p0, vd, acc);
  wg_commit();
  wg_wait<1>();
  pin(s1); pin(p1);
  mbar_wait(bar, 0);
  wg_fence();
  issue_qk(s0, qd2, kd2);
  wg_commit();
  exp_tile(s1, p1, cm, neg1);
  wg_fence();
  issue_pv(o, p1, vd + 384, 1);
  wg_commit();
}
__device__ __forceinline__ void store_o(const float (&o)[12], int odd, int lane, int row0, int colbase, float eps, float s0, float s1) {
  const int t = lane & 3;
  const int src = (lane & ~3) | (odd ? 0 : 2);
  const float l0 = __shfl_sync(~0u, o[8], src) + eps, l1 = __shfl_sync(~0u, o[10], src) + eps;
  const float r0 = s0 * rcp(l0), r1 = s1 * rcp(l1);
  const int g0 = colbase + (odd ? 3 : 0), g1 = g0 + 1, g2 = colbase + 2;
  uint8_t* base = g_OAB + (size_t)(row0 >> 7) * (20 * 16384) + ((row0 & 127) >> 3) * 1024 + lane * 4;
  uint8_t* c0 = base + (g0 >> 3) * 16384 + (g0 & 7) * 128;
  uint8_t* c1 = base + (g1 >> 3) * 16384 + (g1 & 7) * 128;
  uint8_t* c2 = base + (g2 >> 3) * 16384 + (g2 & 7) * 128;
  *(uint32_t*)c0 = packbf(o[0] * r0, o[1] * r0); *(uint32_t*)(c0 + 1024) = packbf(o[2] * r1, o[3] * r1);
  *(uint32_t*)c1 = packbf(o[4] * r0, o[5] * r0); *(uint32_t*)(c1 + 1024) = packbf(o[6] * r1, o[7] * r1);
  if ((t < 2) != (odd != 0)) { *(uint32_t*)c2 = packbf(o[8] * r0, o[9] * r0); *(uint32_t*)(c2 + 1024) = packbf(o[10] * r1, o[11] * r1); }
}

__global__ void __launch_bounds__(256, 1)
k2_attn(const uint8_t* __restrict__ woa, const uint8_t* __restrict__ wob, uint32_t cm, uint32_t neg1) {
  extern __shared__ __align__(1024) uint8_t smem[];
  const uint32_t sb = smem_u32(smem);
  const int tid = threadIdx.x, lane = tid & 31;
  const int warp = __shfl_sync(~0u, tid >> 5, 0), wg = warp >> 2, w4 = warp & 3, t = lane & 3;
  if (blockIdx.x < 4) {
    if (tid == 0) pdl_launch();
    for (int e = blockIdx.x * 256 + tid; e < 8 * 20 * 640; e += 1024) {
      const int nt = e / 12800, r = e % 12800, kg = r / 80, nc = (r % 80) / 8, kr = r % 8;
      const int k = kg * 8 + kr;
      const uint8_t* src = (k < 640 ? woa + (size_t)k * 1280 : wob + (size_t)(k - 640) * 1280) + (nt * 10 + nc) * 16;
      *(uint4*)(g_WOI + (size_t)e * 16) = __ldg((const uint4*)src);
    }
    return;
  }
  const int cb = blockIdx.x - 4, h = cb >> 2, quarter = cb & 3, odd = h & 1;
  const uint32_t bar = sb + K2_BAR;
  if (tid == 0) {
    for (int i = 0; i < 8; i++) mbar_init(bar + 8 * i, 1);
    asm volatile("fence.mbarrier_init.release.cluster;" ::: "memory");
    pdl_launch();
  }
  pdl_wait();
  if (tid == 0) {
    fence_async_all();
    for (int i = 0; i < 8; i++) {
      mbar_expect(bar + 8 * i, 24576);
      bulk_g2s(sb + K2_K + i * 12288, g_KB + (size_t)h * IMG_HEAD + i * 12288, 12288, bar + 8 * i);
      bulk_g2s(sb + K2_V + i * 12288, g_VB + (size_t)h * IMG_HEAD + i * 12288, 12288, bar + 8 * i);
    }
  }
  const int mt0 = quarter * 8 + wg * 4;
  uint32_t q[4][6];
#pragma unroll
  for (int p = 0; p < 4; p++) {
    const uint8_t* src = g_QB + (size_t)h * IMG_HEAD + (size_t)((mt0 + p) * 8 + w4 * 2) * 384 + lane * 4;
#pragma unroll
    for (int c = 0; c < 3; c++) { q[p][2 * c] = ldg_cg(src + c * 128); q[p][2 * c + 1] = ldg_cg(src + 384 + c * 128); }
  }
  const uint4 km4 = ldg_cg4(g_KMAX + h * 128 + lane * 4);
  {
    for (int e = tid; e < 288; e += 256) {
      float4 acc = make_float4(0.f, 0.f, 0.f, 0.f);
      const float4* src = g_KVP + (size_t)h * 16 * 288 + e;
#pragma unroll
      for (int m = 0; m < 16; m++) {
        const uint4 v = ldg_cg4(src + m * 288);
        acc.x += __uint_as_float(v.x); acc.y += __uint_as_float(v.y); acc.z += __uint_as_float(v.z); acc.w += __uint_as_float(v.w);
      }
      const int ww = e / 96, j = (e % 96) / 32, ln = e & 31;
      const uint32_t dst = sb + K2_KV + (ww * 2) * 384 + j * 128 + ln * 4;
      sts32(dst, packbf(acc.x, acc.y));
      sts32(dst + 384, packbf(acc.z, acc.w));
    }
  }
  const float kmax = sqrt_ap(__uint_as_float(__reduce_max_sync(~0u, max(max(km4.x, km4.y), max(km4.z, km4.w))))) * 1.01f;
  const bool is_feat = (t < 2) != (odd != 0);
  float bnd[4][2];
  bool unsafe = false;
#pragma unroll
  for (int p = 0; p < 4; p++)
#pragma unroll
    for (int hf = 0; hf < 2; hf++) {
      float n2 = 0.f;
#pragma unroll
      for (int c = 0; c < 3; c++) { const uint32_t v = q[p][2 * c + hf]; n2 = fmaf(bf_lo(v), bf_lo(v), fmaf(bf_hi(v), bf_hi(v), n2)); }
      n2 += __shfl_xor_sync(~0u, n2, 1);
      n2 += __shfl_xor_sync(~0u, n2, 2);
      bnd[p][hf] = sqrt_ap(n2) * kmax * 1.01f;
      unsafe |= !(bnd[p][hf] <= FAST_BOUND);
    }
  const bool slow = __syncthreads_or(unsafe);
#pragma unroll
  for (int p = 0; p < 4; p++)
#pragma unroll
    for (int hf = 0; hf < 2; hf++) {
      const uint32_t dst = sb + K2_Q + (wg * 4 + p) * 3072 + (w4 * 2 + hf) * 384 + lane * 4;
      sts32(dst, q[p][hf]);
      sts32(dst + 128, q[p][2 + hf]);
      const uint32_t v = q[p][4 + hf];
      uint32_t c2 = packbf(bf_lo(v) * 0.5f, bf_hi(v) * 0.5f);
      if (!is_feat) c2 = slow ? 0u : ((t & 1) ? 0x3F00u : packbf(-0.5f * bnd[p][hf], 0.5f));
      sts32(dst + 256, c2);
    }
  fence_async_smem();
  __syncthreads();

  const int row_g = mt0 * 64 + w4 * 16 + (lane >> 2);
  const int colgrp = (h >> 1) * 5;
  {
    const uint64_t kvd = mkdesc(sb + K2_KV, 384, 128, 0);
#pragma unroll 1
    for (int p = 0; p < 4; p++) {
      const uint4* src = g_PHIQ + ((size_t)(h * 32 + mt0 + p) * 3) * 128 + (tid & 127);
      const uint4 f0 = ldg_cg4(src), f1 = ldg_cg4(src + 128), f2 = ldg_cg4(src + 256);
      const float g0 = g_GATE[row_g + p * 64].x, g1 = g_GATE[row_g + p * 64 + 8].x;
      float o[12];
      wg_fence();
      mma_n24_rs_tb(o, f0.x, f0.y, f0.z, f0.w, kvd, 0);
      mma_n24_rs_tb(o, f1.x, f1.y, f1.z, f1.w, kvd + 48, 1);
      mma_n24_rs_tb(o, f2.x, f2.y, f2.z, f2.w, kvd + 96, 1);
      wg_commit();
      wg_wait<0>();
      pin(o);
      store_o(o, odd, lane, (mt0 + p) * 64 + w4 * 16, colgrp, 1e-6f, g0, g1);
    }
  }

  const uint64_t kd0 = mkdesc(sb + K2_K, 128, 384, 0), vd0 = mkdesc(sb + K2_V, 384, 128, 0);
  const uint64_t qd0 = mkdesc(sb + K2_Q + wg * 4 * 3072, 128, 384, 0);
  float o[12];
  if (!slow) {
    float s0[64], s1[64];
    uint32_t p0[32], p1[32];
    mbar_wait(bar, 0);
    wg_fence();
    issue_qk(s0, qd0, kd0);
    wg_commit();
    wg_wait<0>();
    pin(s0);
#pragma unroll 1
    for (int pass = 0; pass < 4; pass++) {
      const uint64_t qd = qd0 + pass * 192;
      uint64_t kd = kd0, vd = vd0;
#pragma unroll 1
      for (int j = 0; j < 7; j++) {
        attn_pair(s0, s1, p0, p1, o, qd, kd + 384, qd, kd + 768, vd, j, bar + 8 * (j + 1), cm, neg1);
        wg_wait<1>();
        pin(s0); pin(p0);
        kd += 768; vd += 768;
      }
      attn_pair(s0, s1, p0, p1, o, qd, kd + 384, qd0 + ((pass + 1) & 3) * 192, kd0, vd, 1, bar, cm, neg1);
      const float g0 = g_GATE[row_g + pass * 64].y, g1 = g_GATE[row_g + pass * 64 + 8].y;
      wg_wait<0>();
      pin(s0); pin(p0); pin(o);
      store_o(o, odd, lane, (mt0 + pass) * 64 + w4 * 16, 80 + colgrp, 0.f, g0, g1);
    }
  } else {
    float s[64];
    uint32_t p[32];
#pragma unroll 1
    for (int pass = 0; pass < 4; pass++) {
      float m0 = -INFINITY, m1 = -INFINITY;
#pragma unroll
      for (int i = 0; i < 12; i++) o[i] = 0.f;
#pragma unroll 1
      for (int j = 0; j < 16; j++) {
        if (pass == 0) mbar_wait(bar + 8 * (j >> 1), 0);
        wg_fence();
        issue_qk(s, qd0 + pass * 192, kd0 + j * 384);
        wg_commit();
        wg_wait<0>();
        pin(s);
        float n0 = m0, n1 = m1;
#pragma unroll
        for (int g = 0; g < 16; g++) { n0 = fmaxf(n0, fmaxf(s[4 * g], s[4 * g + 1])); n1 = fmaxf(n1, fmaxf(s[4 * g + 2], s[4 * g + 3])); }
        n0 = fmaxf(n0, __shfl_xor_sync(~0u, n0, 1)); n1 = fmaxf(n1, __shfl_xor_sync(~0u, n1, 1));
        n0 = fmaxf(n0, __shfl_xor_sync(~0u, n0, 2)); n1 = fmaxf(n1, __shfl_xor_sync(~0u, n1, 2));
        const float c0 = ex2(m0 - n0), c1 = ex2(m1 - n1);
        m0 = n0; m1 = n1;
#pragma unroll
        for (int i = 0; i < 3; i++) { o[4 * i] *= c0; o[4 * i + 1] *= c0; o[4 * i + 2] *= c1; o[4 * i + 3] *= c1; }
#pragma unroll
        for (int g = 0; g < 16; g++) {
          const uint32_t sg = ((POLY_MASK >> g) & 1) ? 0x80008000u : 0u;
          p[2 * g] = packbf(ex2(s[4 * g] - m0), ex2(s[4 * g + 1] - m0)) ^ sg;
          p[2 * g + 1] = packbf(ex2(s[4 * g + 2] - m1), ex2(s[4 * g + 3] - m1)) ^ sg;
        }
        wg_fence();
        issue_pv(o, p, vd0 + j * 384, 1);
        wg_commit();
        wg_wait<0>();
        pin(o); pin(p);
      }
      const float g0 = g_GATE[row_g + pass * 64].y, g1 = g_GATE[row_g + pass * 64 + 8].y;
      store_o(o, odd, lane, (mt0 + pass) * 64 + w4 * 16, 80 + colgrp, 0.f, g0, g1);
    }
  }
}

constexpr int K3_STAGE = 26624, K3_NST = 8, K3_BAR = K3_NST * K3_STAGE, K3_SMEM = K3_BAR + 128;

__global__ void __launch_bounds__(288, 1) k3_out(__nv_bfloat16* __restrict__ out) {
  extern __shared__ __align__(1024) uint8_t smem[];
  const uint32_t sb = smem_u32(smem);
  const uint32_t full = sb + K3_BAR, empty = full + 8 * K3_NST;
  const int warp = __shfl_sync(~0u, threadIdx.x >> 5, 0), lane = threadIdx.x & 31;
  const int bid = blockIdx.x, nt = bid & 7, mt = bid >> 3;
  if (threadIdx.x == 0) {
    for (int i = 0; i < K3_NST; i++) { mbar_init(full + 8 * i, 1); mbar_init(empty + 8 * i, 2); }
    asm volatile("fence.mbarrier_init.release.cluster;" ::: "memory");
  }
  __syncthreads();
  if (warp == 8) {
    if (lane == 0) {
      pdl_wait();
      fence_async_all();
      for (int it = 0; it < 20; it++) {
        const int s = it % K3_NST;
        if (it >= K3_NST) mbar_wait(empty + 8 * s, ((it / K3_NST) - 1) & 1);
        const uint32_t d = sb + s * K3_STAGE, b = full + 8 * s;
        mbar_expect(b, K3_STAGE);
        bulk_g2s(d, g_OAB + (size_t)(mt * 20 + it) * 16384, 16384, b);
        bulk_g2s(d + 16384, g_WOI + (size_t)(nt * 20 + it) * 10240, 10240, b);
      }
    }
  } else {
    const int wg = warp >> 2, w4 = warp & 3;
    float acc[40];
#pragma unroll 1
    for (int it = 0; it < 20; it++) {
      const int s = it % K3_NST;
      mbar_wait(full + 8 * s, (it / K3_NST) & 1);
      const uint32_t st = sb + s * K3_STAGE;
      const uint64_t ad = mkdesc(st + wg * 8192, 128, 1024, 0), bd = mkdesc(st + 16384, 1280, 128, 0);
      wg_fence();
#pragma unroll
      for (int kk = 0; kk < 4; kk++) mma_n80_ss_tb(acc, ad + kk * 16, bd + kk * 160, it | kk);
      wg_commit();
      if (it > 0) {
        wg_wait<1>();
        if ((threadIdx.x & 127) == 0) mbar_arrive(empty + 8 * ((it - 1) % K3_NST));
      }
    }
    wg_wait<0>();
    pin(acc);
    __nv_bfloat16* dst = out + (size_t)(mt * 128 + wg * 64 + w4 * 16 + (lane >> 2)) * DM + nt * 80 + (lane & 3) * 2;
#pragma unroll
    for (int j = 0; j < 10; j++) {
      *(uint32_t*)(dst + j * 8) = packbf(acc[4 * j], acc[4 * j + 1]);
      *(uint32_t*)(dst + 8 * DM + j * 8) = packbf(acc[4 * j + 2], acc[4 * j + 3]);
    }
  }
}

typedef CUresult (*EncodeFn)(CUtensorMap*, CUtensorMapDataType, cuuint32_t, void*, const cuuint64_t*, const cuuint64_t*, const cuuint32_t*,
                             const cuuint32_t*, CUtensorMapInterleave, CUtensorMapSwizzle, CUtensorMapL2promotion, CUtensorMapFloatOOBfill);

void encode(EncodeFn fn, CUtensorMap* m, const void* p, int rank, const cuuint64_t* dims, const cuuint64_t* strides, const cuuint32_t* box,
            CUtensorMapSwizzle sw) {
  const cuuint32_t es[3] = {1, 1, 1};
  fn(m, CU_TENSOR_MAP_DATA_TYPE_BFLOAT16, rank, const_cast<void*>(p), dims, strides, box, es, CU_TENSOR_MAP_INTERLEAVE_NONE, sw,
     CU_TENSOR_MAP_L2_PROMOTION_L2_128B, CU_TENSOR_MAP_FLOAT_OOB_FILL_NONE);
}

}

extern "C" void kernel_launch(void* const* d_in, const int* in_sizes, int n_in, void* d_out, int out_size) {
  (void)in_sizes; (void)n_in; (void)out_size;
  const __nv_bfloat16* x = (const __nv_bfloat16*)d_in[0];
  const void* wa = d_in[1];
  const __nv_bfloat16* wphi = (const __nv_bfloat16*)d_in[2];
  const void* woa = d_in[3];
  const void* wb = d_in[5];
  const void* wob = d_in[6];
  const __nv_bfloat16* gate_w = (const __nv_bfloat16*)d_in[7];

  static EncodeFn enc = nullptr;
  if (!enc) {
    void* fn = nullptr;
    cudaDriverEntryPointQueryResult qr;
    cudaGetDriverEntryPoint("cuTensorMapEncodeTiled", &fn, cudaEnableDefault, &qr);
    enc = (EncodeFn)fn;
    cudaFuncSetAttribute(k1_qkv, cudaFuncAttributeMaxDynamicSharedMemorySize, K1_SMEM);
    cudaFuncSetAttribute(k2_attn, cudaFuncAttributeMaxDynamicSharedMemorySize, K2_SMEM);
    cudaFuncSetAttribute(k3_out, cudaFuncAttributeMaxDynamicSharedMemorySize, K3_SMEM);
  }
  CUtensorMap mx, mwa64, mwa16, mwb64, mwb16;
  {
    const cuuint64_t dx[2] = {640, 2048}, sx[1] = {1280};
    const cuuint32_t bx[2] = {64, 128};
    encode(enc, &mx, x, 2, dx, sx, bx, CU_TENSOR_MAP_SWIZZLE_128B);
    const cuuint64_t dw[3] = {640, 640, 3}, sw[2] = {3840, 1280};
    const cuuint32_t b64[3] = {64, 64, 3}, b16[3] = {16, 64, 3};
    encode(enc, &mwa64, wa, 3, dw, sw, b64, CU_TENSOR_MAP_SWIZZLE_128B);
    encode(enc, &mwa16, wa, 3, dw, sw, b16, CU_TENSOR_MAP_SWIZZLE_32B);
    encode(enc, &mwb64, wb, 3, dw, sw, b64, CU_TENSOR_MAP_SWIZZLE_128B);
    encode(enc, &mwb16, wb, 3, dw, sw, b16, CU_TENSOR_MAP_SWIZZLE_32B);
  }
  cudaStream_t st = cudaStreamPerThread;
  cudaLaunchAttribute pdl[1];
  pdl[0].id = cudaLaunchAttributeProgrammaticStreamSerialization;
  pdl[0].val.programmaticStreamSerializationAllowed = 1;
  cudaLaunchConfig_t c = {};
  c.stream = st;
  c.gridDim = dim3(128); c.blockDim = dim3(512); c.dynamicSmemBytes = K1_SMEM; c.attrs = nullptr; c.numAttrs = 0;
  cudaLaunchKernelEx(&c, k1_qkv, mx, mwa64, mwa16, mwb64, mwb16, x, wphi, gate_w, (const uint8_t*)wa, (const uint8_t*)wb);
  c.gridDim = dim3(132); c.blockDim = dim3(256); c.dynamicSmemBytes = K2_SMEM; c.attrs = pdl; c.numAttrs = 1;
  cudaLaunchKernelEx(&c, k2_attn, (const uint8_t*)woa, (const uint8_t*)wob, 0x1F801F80u, 0xFFFFFFFFu);
  c.gridDim = dim3(128); c.blockDim = dim3(288); c.dynamicSmemBytes = K3_SMEM;
  cudaLaunchKernelEx(&c, k3_out, (__nv_bfloat16*)d_out);
}
```

```cpp
#include <cuda_runtime.h>
#include <cuda_bf16.h>
#include <cuda.h>
#include <stdint.h>

namespace {

constexpr int SEQ = 2048, DM = 640, NH = 32;
constexpr int IMG_HEAD = SEQ * 48;
#define POLY_MASK 0x76DDu
constexpr float LOG2E = 1.4426950408889634f;
constexpr float QSCALE = 0.22360679774997896f * 1.4426950408889634f;
constexpr uint32_t BF_ONE = 0x3F80u;
constexpr uint32_t BF_MAGIC = 0x43E0u;
constexpr uint32_t BF_MU_HI = 0x4025u;
constexpr uint32_t BF_MU_LO = 0x3B8Bu;
constexpr float FAST_BOUND = 40.0f;

__device__ __align__(1024) uint8_t g_QKVB[3 * NH * IMG_HEAD];
__device__ __align__(1024) uint4 g_PHIQ[NH * 32 * 3 * 128];
__device__ __align__(1024) float4 g_KVP[NH * 16 * 288];
__device__ __align__(1024) uint8_t g_KVB[NH * 2304];
__device__ __align__(128) uint32_t g_KVFLAG[32];
__device__ __align__(1024) float g_KMAX[NH * 128];
__device__ __align__(1024) float2 g_GATE[SEQ];
__device__ __align__(1024) uint2 g_OAB[128 * 160 * 32];
__device__ __align__(1024) uint8_t g_WOI[8 * 20 * 10240];

#define PROF(cond, k, slot)
__device__ __forceinline__ uint32_t smem_u32(const void* p) { return (uint32_t)__cvta_generic_to_shared(p); }
__device__ __forceinline__ void mbar_init(uint32_t a, uint32_t c) { asm volatile("mbarrier.init.shared::cta.b64 [%0], %1;" ::"r"(a), "r"(c) : "memory"); }
__device__ __forceinline__ void mbar_expect(uint32_t a, uint32_t b) { asm volatile("mbarrier.arrive.expect_tx.shared::cta.b64 _, [%0], %1;" ::"r"(a), "r"(b) : "memory"); }
__device__ __forceinline__ void mbar_arrive(uint32_t a) { asm volatile("mbarrier.arrive.shared::cta.b64 _, [%0];" ::"r"(a) : "memory"); }
__device__ __forceinline__ void mbar_wait(uint32_t a, uint32_t ph) {
  asm volatile(
      "{\n.reg .pred p;\n.reg .u32 n;\nmov.u32 n, 0;\n"
      "W_%=:\nmbarrier.try_wait.parity.shared::cta.b64 p, [%0], %1;\n@p bra D_%=;\n"
      "add.u32 n, n, 1;\nsetp.lt.u32 p, n, 4000000;\n@p bra W_%=;\ntrap;\nD_%=:\n}\n" ::"r"(a), "r"(ph) : "memory");
}
__device__ __forceinline__ void mbar_wait_u(uint32_t a, uint32_t ph) {
#pragma unroll 1
  for (int n = 0;; n++) {
    uint32_t ok;
    asm volatile("{\n.reg .pred p;\nmbarrier.try_wait.parity.shared::cta.b64 p, [%1], %2;\nselp.u32 %0, 1, 0, p;\n}\n" : "=r"(ok) : "r"(a), "r"(ph) : "memory");
    if (__all_sync(~0u, ok)) break;
    if (n > 4000000) __trap();
  }
}
__device__ __forceinline__ void tma2(uint32_t dst, const CUtensorMap* m, int c0, int c1, uint32_t bar) {
  asm volatile("cp.async.bulk.tensor.2d.shared::cluster.global.mbarrier::complete_tx::bytes [%0], [%1, {%3,%4}], [%2];" ::"r"(dst), "l"(m), "r"(bar), "r"(c0), "r"(c1) : "memory");
}
__device__ __forceinline__ void tma3(uint32_t dst, const CUtensorMap* m, int c0, int c1, int c2, uint32_t bar) {
  asm volatile("cp.async.bulk.tensor.3d.shared::cluster.global.mbarrier::complete_tx::bytes [%0], [%1, {%3,%4,%5}], [%2];" ::"r"(dst), "l"(m), "r"(bar), "r"(c0), "r"(c1), "r"(c2) : "memory");
}
__device__ __forceinline__ void bulk_g2s(uint32_t dst, const void* src, uint32_t bytes, uint32_t bar) {
  asm volatile("cp.async.bulk.shared::cluster.global.mbarrier::complete_tx::bytes [%0], [%1], %2, [%3];" ::"r"(dst), "l"(src), "r"(bytes), "r"(bar) : "memory");
}
__device__ __forceinline__ void prefetch_l2(const void* src, uint32_t bytes) { asm volatile("cp.async.bulk.prefetch.L2.global [%0], %1;" ::"l"(src), "r"(bytes) : "memory"); }
__device__ __forceinline__ void fence_async_smem() { asm volatile("fence.proxy.async.shared::cta;" ::: "memory"); }
__device__ __forceinline__ void fence_async_all() { asm volatile("fence.proxy.async;" ::: "memory"); }
__device__ __forceinline__ void bar_sync(int id, int n) { asm volatile("bar.sync %0, %1;" ::"r"(id), "r"(n) : "memory"); }
__device__ __forceinline__ void bar_arrive(int id, int n) { asm volatile("bar.arrive %0, %1;" ::"r"(id), "r"(n) : "memory"); }
__device__ __forceinline__ void pdl_wait() { asm volatile("griddepcontrol.wait;" ::: "memory"); }
__device__ __forceinline__ void pdl_launch() { asm volatile("griddepcontrol.launch_dependents;" ::: "memory"); }
__device__ __forceinline__ void wg_fence() { asm volatile("wgmma.fence.sync.aligned;" ::: "memory"); }
__device__ __forceinline__ void wg_commit() { asm volatile("wgmma.commit_group.sync.aligned;" ::: "memory"); }
template <int N> __device__ __forceinline__ void wg_wait() { asm volatile("wgmma.wait_group.sync.aligned %0;" ::"n"(N) : "memory"); }
template <int N> __device__ __forceinline__ void reg_inc() { asm volatile("setmaxnreg.inc.sync.aligned.u32 %0;" ::"n"(N)); }
template <int N> __device__ __forceinline__ void reg_dec() { asm volatile("setmaxnreg.dec.sync.aligned.u32 %0;" ::"n"(N)); }
template <int N> __device__ __forceinline__ void pin(float (&r)[N]) {
#pragma unroll
  for (int i = 0; i < N; i++) asm volatile("" : "+f"(r[i])::"memory");
}
template <int N> __device__ __forceinline__ void pin(uint32_t (&r)[N]) {
#pragma unroll
  for (int i = 0; i < N; i++) asm volatile("" : "+r"(r[i])::"memory");
}
__device__ __forceinline__ uint64_t mkdesc(uint32_t addr, uint32_t lbo, uint32_t sbo, uint32_t swz) {
  return (uint64_t)((addr & 0x3FFFF) >> 4) | ((uint64_t)(lbo >> 4) << 16) | ((uint64_t)(sbo >> 4) << 32) | ((uint64_t)swz << 62);
}
__device__ __forceinline__ float ex2(float x) { float y; asm("ex2.approx.ftz.f32 %0, %1;" : "=f"(y) : "f"(x)); return y; }
__device__ __forceinline__ float rcp(float x) { float y; asm("rcp.approx.ftz.f32 %0, %1;" : "=f"(y) : "f"(x)); return y; }
__device__ __forceinline__ float sqrt_ap(float x) { float y; asm("sqrt.approx.f32 %0, %1;" : "=f"(y) : "f"(x)); return y; }
__device__ __forceinline__ uint32_t packbf(float lo, float hi) { uint32_t d; asm("cvt.rn.bf16x2.f32 %0, %1, %2;" : "=r"(d) : "f"(hi), "f"(lo)); return d; }
__device__ __forceinline__ float bf_lo(uint32_t v) { return __uint_as_float(v << 16); }
__device__ __forceinline__ float bf_hi(uint32_t v) { return __uint_as_float(v & 0xFFFF0000u); }
__device__ __forceinline__ float bf_round(float x) { return bf_lo(packbf(x, 0.f)); }
__device__ __forceinline__ uint32_t ldg_cg(const void* p) { uint32_t v; asm volatile("ld.global.cg.b32 %0, [%1];" : "=r"(v) : "l"(p) : "memory"); return v; }
__device__ __forceinline__ uint4 ldg_cg4(const void* p) { uint4 v; asm volatile("ld.global.cg.v4.b32 {%0,%1,%2,%3}, [%4];" : "=r"(v.x), "=r"(v.y), "=r"(v.z), "=r"(v.w) : "l"(p) : "memory"); return v; }
__device__ __forceinline__ void sts32(uint32_t a, uint32_t v) { asm volatile("st.shared.b32 [%0], %1;" ::"r"(a), "r"(v) : "memory"); }
__device__ __forceinline__ void stsm4(uint32_t a, uint32_t r0, uint32_t r1, uint32_t r2, uint32_t r3) {
  asm volatile("stmatrix.sync.aligned.m8n8.x4.shared.b16 [%0], {%1,%2,%3,%4};" ::"r"(a), "r"(r0), "r"(r1), "r"(r2), "r"(r3) : "memory");
}

__device__ __forceinline__ void ldsm4(uint32_t (&r)[4], uint32_t a) {
  asm volatile("ldmatrix.sync.aligned.m8n8.x4.shared.b16 {%0,%1,%2,%3}, [%4];" : "=r"(r[0]), "=r"(r[1]), "=r"(r[2]), "=r"(r[3]) : "r"(a) : "memory");
}
__device__ __forceinline__ void bulk_s2g(void* dst, uint32_t src, uint32_t bytes) {
  asm volatile("cp.async.bulk.global.shared::cta.bulk_group [%0], [%1], %2;" ::"l"(dst), "r"(src), "r"(bytes) : "memory");
}

__device__ __forceinline__ void mma_n24_ss_tb(float (&d)[12], uint64_t adesc, uint64_t bdesc, int acc) {
  asm volatile("{\n.reg .pred p;\nsetp.ne.b32 p, %14, 0;\n"
      "wgmma.mma_async.sync.aligned.m64n24k16.f32.bf16.bf16 "
      "{%0,%1,%2,%3,%4,%5,%6,%7,%8,%9,%10,%11}, "
      "%12, %13, p, 1, 1, 0, 1;\n}\n"
      : "+f"(d[0]), "+f"(d[1]), "+f"(d[2]), "+f"(d[3]), "+f"(d[4]), "+f"(d[5]), "+f"(d[6]), "+f"(d[7]),
        "+f"(d[8]), "+f"(d[9]), "+f"(d[10]), "+f"(d[11])
      : "l"(adesc), "l"(bdesc), "r"(acc));
}
__device__ __forceinline__ void mma_n192_rs_tb(float (&d)[96], uint32_t a0, uint32_t a1, uint32_t a2, uint32_t a3, uint64_t bdesc, int acc) {
  asm volatile("{\n.reg .pred p;\nsetp.ne.b32 p, %101, 0;\n"
      "wgmma.mma_async.sync.aligned.m64n192k16.f32.bf16.bf16 "
      "{%0,%1,%2,%3,%4,%5,%6,%7,%8,%9,%10,%11,%12,%13,%14,%15,"
      "%16,%17,%18,%19,%20,%21,%22,%23,%24,%25,%26,%27,%28,%29,%30,%31,"
      "%32,%33,%34,%35,%36,%37,%38,%39,%40,%41,%42,%43,%44,%45,%46,%47,"
      "%48,%49,%50,%51,%52,%53,%54,%55,%56,%57,%58,%59,%60,%61,%62,%63,"
      "%64,%65,%66,%67,%68,%69,%70,%71,%72,%73,%74,%75,%76,%77,%78,%79,"
      "%80,%81,%82,%83,%84,%85,%86,%87,%88,%89,%90,%91,%92,%93,%94,%95}, "
      "{%96,%97,%98,%99}, %100, p, 1, 1, 1;\n}\n"
      : "+f"(d[0]), "+f"(d[1]), "+f"(d[2]), "+f"(d[3]), "+f"(d[4]), "+f"(d[5]), "+f"(d[6]), "+f"(d[7]),
        "+f"(d[8]), "+f"(d[9]), "+f"(d[10]), "+f"(d[11]), "+f"(d[12]), "+f"(d[13]), "+f"(d[14]), "+f"(d[15]),
        "+f"(d[16]), "+f"(d[17]), "+f"(d[18]), "+f"(d[19]), "+f"(d[20]), "+f"(d[21]), "+f"(d[22]), "+f"(d[23]),
        "+f"(d[24]), "+f"(d[25]), "+f"(d[26]), "+f"(d[27]), "+f"(d[28]), "+f"(d[29]), "+f"(d[30]), "+f"(d[31]),
        "+f"(d[32]), "+f"(d[33]), "+f"(d[34]), "+f"(d[35]), "+f"(d[36]), "+f"(d[37]), "+f"(d[38]), "+f"(d[39]),
        "+f"(d[40]), "+f"(d[41]), "+f"(d[42]), "+f"(d[43]), "+f"(d[44]), "+f"(d[45]), "+f"(d[46]), "+f"(d[47]),
        "+f"(d[48]), "+f"(d[49]), "+f"(d[50]), "+f"(d[51]), "+f"(d[52]), "+f"(d[53]), "+f"(d[54]), "+f"(d[55]),
        "+f"(d[56]), "+f"(d[57]), "+f"(d[58]), "+f"(d[59]), "+f"(d[60]), "+f"(d[61]), "+f"(d[62]), "+f"(d[63]),
        "+f"(d[64]), "+f"(d[65]), "+f"(d[66]), "+f"(d[67]), "+f"(d[68]), "+f"(d[69]), "+f"(d[70]), "+f"(d[71]),
        "+f"(d[72]), "+f"(d[73]), "+f"(d[74]), "+f"(d[75]), "+f"(d[76]), "+f"(d[77]), "+f"(d[78]), "+f"(d[79]),
        "+f"(d[80]), "+f"(d[81]), "+f"(d[82]), "+f"(d[83]), "+f"(d[84]), "+f"(d[85]), "+f"(d[86]), "+f"(d[87]),
        "+f"(d[88]), "+f"(d[89]), "+f"(d[90]), "+f"(d[91]), "+f"(d[92]), "+f"(d[93]), "+f"(d[94]), "+f"(d[95])
      : "r"(a0), "r"(a1), "r"(a2), "r"(a3), "l"(bdesc), "r"(acc));
}
__device__ __forceinline__ void mma_n48_rs_tb(float (&d)[24], uint32_t a0, uint32_t a1, uint32_t a2, uint32_t a3, uint64_t bdesc, int acc) {
  asm volatile("{\n.reg .pred p;\nsetp.ne.b32 p, %29, 0;\n"
      "wgmma.mma_async.sync.aligned.m64n48k16.f32.bf16.bf16 "
      "{%0,%1,%2,%3,%4,%5,%6,%7,%8,%9,%10,%11,%12,%13,%14,%15,"
      "%16,%17,%18,%19,%20,%21,%22,%23}, "
      "{%24,%25,%26,%27}, %28, p, 1, 1, 1;\n}\n"
      : "+f"(d[0]), "+f"(d[1]), "+f"(d[2]), "+f"(d[3]), "+f"(d[4]), "+f"(d[5]), "+f"(d[6]), "+f"(d[7]),
        "+f"(d[8]), "+f"(d[9]), "+f"(d[10]), "+f"(d[11]), "+f"(d[12]), "+f"(d[13]), "+f"(d[14]), "+f"(d[15]),
        "+f"(d[16]), "+f"(d[17]), "+f"(d[18]), "+f"(d[19]), "+f"(d[20]), "+f"(d[21]), "+f"(d[22]), "+f"(d[23])
      : "r"(a0), "r"(a1), "r"(a2), "r"(a3), "l"(bdesc), "r"(acc));
}
__device__ __forceinline__ void mma_n128_ss(float (&d)[64], uint64_t adesc, uint64_t bdesc, int acc) {
  asm volatile("{\n.reg .pred p;\nsetp.ne.b32 p, %66, 0;\n"
      "wgmma.mma_async.sync.aligned.m64n128k16.f32.bf16.bf16 "
      "{%0,%1,%2,%3,%4,%5,%6,%7,%8,%9,%10,%11,%12,%13,%14,%15,"
      "%16,%17,%18,%19,%20,%21,%22,%23,%24,%25,%26,%27,%28,%29,%30,%31,"
      "%32,%33,%34,%35,%36,%37,%38,%39,%40,%41,%42,%43,%44,%45,%46,%47,"
      "%48,%49,%50,%51,%52,%53,%54,%55,%56,%57,%58,%59,%60,%61,%62,%63}, "
      "%64, %65, p, 1, 1, 0, 0;\n}\n"
      : "+f"(d[0]), "+f"(d[1]), "+f"(d[2]), "+f"(d[3]), "+f"(d[4]), "+f"(d[5]), "+f"(d[6]), "+f"(d[7]),
        "+f"(d[8]), "+f"(d[9]), "+f"(d[10]), "+f"(d[11]), "+f"(d[12]), "+f"(d[13]), "+f"(d[14]), "+f"(d[15]),
        "+f"(d[16]), "+f"(d[17]), "+f"(d[18]), "+f"(d[19]), "+f"(d[20]), "+f"(d[21]), "+f"(d[22]), "+f"(d[23]),
        "+f"(d[24]), "+f"(d[25]), "+f"(d[26]), "+f"(d[27]), "+f"(d[28]), "+f"(d[29]), "+f"(d[30]), "+f"(d[31]),
        "+f"(d[32]), "+f"(d[33]), "+f"(d[34]), "+f"(d[35]), "+f"(d[36]), "+f"(d[37]), "+f"(d[38]), "+f"(d[39]),
        "+f"(d[40]), "+f"(d[41]), "+f"(d[42]), "+f"(d[43]), "+f"(d[44]), "+f"(d[45]), "+f"(d[46]), "+f"(d[47]),
        "+f"(d[48]), "+f"(d[49]), "+f"(d[50]), "+f"(d[51]), "+f"(d[52]), "+f"(d[53]), "+f"(d[54]), "+f"(d[55]),
        "+f"(d[56]), "+f"(d[57]), "+f"(d[58]), "+f"(d[59]), "+f"(d[60]), "+f"(d[61]), "+f"(d[62]), "+f"(d[63])
      : "l"(adesc), "l"(bdesc), "r"(acc));
}
__device__ __forceinline__ void mma_n80_rs_tb(float (&d)[40], uint32_t a0, uint32_t a1, uint32_t a2, uint32_t a3, uint64_t bdesc, int acc) {
  asm volatile("{\n.reg .pred p;\nsetp.ne.b32 p, %45, 0;\n"
      "wgmma.mma_async.sync.aligned.m64n80k16.f32.bf16.bf16 "
      "{%0,%1,%2,%3,%4,%5,%6,%7,%8,%9,%10,%11,%12,%13,%14,%15,"
      "%16,%17,%18,%19,%20,%21,%22,%23,%24,%25,%26,%27,%28,%29,%30,%31,"
      "%32,%33,%34,%35,%36,%37,%38,%39}, "
      "{%40,%41,%42,%43}, %44, p, 1, 1, 1;\n}\n"
      : "+f"(d[0]), "+f"(d[1]), "+f"(d[2]), "+f"(d[3]), "+f"(d[4]), "+f"(d[5]), "+f"(d[6]), "+f"(d[7]),
        "+f"(d[8]), "+f"(d[9]), "+f"(d[10]), "+f"(d[11]), "+f"(d[12]), "+f"(d[13]), "+f"(d[14]), "+f"(d[15]),
        "+f"(d[16]), "+f"(d[17]), "+f"(d[18]), "+f"(d[19]), "+f"(d[20]), "+f"(d[21]), "+f"(d[22]), "+f"(d[23]),
        "+f"(d[24]), "+f"(d[25]), "+f"(d[26]), "+f"(d[27]), "+f"(d[28]), "+f"(d[29]), "+f"(d[30]), "+f"(d[31]),
        "+f"(d[32]), "+f"(d[33]), "+f"(d[34]), "+f"(d[35]), "+f"(d[36]), "+f"(d[37]), "+f"(d[38]), "+f"(d[39])
      : "r"(a0), "r"(a1), "r"(a2), "r"(a3), "l"(bdesc), "r"(acc));
}
__device__ __forceinline__ void mma_n24_rs_tb(float (&d)[12], uint32_t a0, uint32_t a1, uint32_t a2, uint32_t a3, uint64_t bdesc, int acc) {
  asm volatile("{\n.reg .pred p;\nsetp.ne.b32 p, %17, 0;\n"
      "wgmma.mma_async.sync.aligned.m64n24k16.f32.bf16.bf16 "
      "{%0,%1,%2,%3,%4,%5,%6,%7,%8,%9,%10,%11}, "
      "{%12,%13,%14,%15}, %16, p, 1, 1, 1;\n}\n"
      : "+f"(d[0]), "+f"(d[1]), "+f"(d[2]), "+f"(d[3]), "+f"(d[4]), "+f"(d[5]), "+f"(d[6]), "+f"(d[7]),
        "+f"(d[8]), "+f"(d[9]), "+f"(d[10]), "+f"(d[11])
      : "r"(a0), "r"(a1), "r"(a2), "r"(a3), "l"(bdesc), "r"(acc));
}
__device__ __forceinline__ void mma_n24_ss_tatb(float (&d)[12], uint64_t adesc, uint64_t bdesc, int acc) {
  asm volatile("{\n.reg .pred p;\nsetp.ne.b32 p, %14, 0;\n"
      "wgmma.mma_async.sync.aligned.m64n24k16.f32.bf16.bf16 "
      "{%0,%1,%2,%3,%4,%5,%6,%7,%8,%9,%10,%11}, "
      "%12, %13, p, 1, 1, 1, 1;\n}\n"
      : "+f"(d[0]), "+f"(d[1]), "+f"(d[2]), "+f"(d[3]), "+f"(d[4]), "+f"(d[5]), "+f"(d[6]), "+f"(d[7]),
        "+f"(d[8]), "+f"(d[9]), "+f"(d[10]), "+f"(d[11])
      : "l"(adesc), "l"(bdesc), "r"(acc));
}

constexpr int K1_STAGE = 47104;
constexpr int K1_NST = 3;
constexpr int K1_STG = K1_NST * K1_STAGE;
constexpr int K1_WPH = K1_STG + 73728;
constexpr int K1_BAR = K1_WPH + 6144;
constexpr int K1_SMEM = K1_BAR + 128;

template <int SEC, int J, int HF>
__device__ __forceinline__ float2 grp(const float (&a1)[96], const float (&a2)[24]) {
  if constexpr (J < 8) return make_float2(a1[(8 * SEC + J) * 4 + 2 * HF], a1[(8 * SEC + J) * 4 + 2 * HF + 1]);
  else return make_float2(a2[(2 * SEC + J - 8) * 4 + 2 * HF], a2[(2 * SEC + J - 8) * 4 + 2 * HF + 1]);
}
__device__ __forceinline__ float sq2(float2 v) { return fmaf(v.x, v.x, v.y * v.y); }

template <int SEC, int PR, bool NORM>
__device__ __forceinline__ void stage_pair(const float (&a1)[96], const float (&a2)[24], float sc0, float sc1, uint32_t ext0, uint32_t ext1,
                                           uint32_t ad01, uint32_t ad2, int hs, int t, float (&nrm)[4]) {
  const float2 u0 = grp<SEC, 5 * PR, 0>(a1, a2), u1 = grp<SEC, 5 * PR + 1, 0>(a1, a2), u2 = grp<SEC, 5 * PR + 2, 0>(a1, a2),
               u3 = grp<SEC, 5 * PR + 3, 0>(a1, a2), u4 = grp<SEC, 5 * PR + 4, 0>(a1, a2);
  const float2 w0 = grp<SEC, 5 * PR, 1>(a1, a2), w1 = grp<SEC, 5 * PR + 1, 1>(a1, a2), w2 = grp<SEC, 5 * PR + 2, 1>(a1, a2),
               w3 = grp<SEC, 5 * PR + 3, 1>(a1, a2), w4 = grp<SEC, 5 * PR + 4, 1>(a1, a2);
  const uint32_t off = (SEC * 4 + 2 * PR) * hs;
  stsm4(ad01 + off, packbf(u0.x * sc0, u0.y * sc0), packbf(w0.x * sc1, w0.y * sc1), packbf(u1.x * sc0, u1.y * sc0), packbf(w1.x * sc1, w1.y * sc1));
  stsm4(ad01 + off + hs, packbf(u3.x * sc0, u3.y * sc0), packbf(w3.x * sc1, w3.y * sc1), packbf(u4.x * sc0, u4.y * sc0), packbf(w4.x * sc1, w4.y * sc1));
  const uint32_t m0 = packbf(u2.x * sc0, u2.y * sc0), m1 = packbf(w2.x * sc1, w2.y * sc1);
  const bool lo = t < 2;
  stsm4(ad2 + off, lo ? m0 : ext0, lo ? m1 : ext1, lo ? ext0 : m0, lo ? ext1 : m1);
  if (NORM) {
    const float h0 = sq2(u2), h1 = sq2(w2);
    float e0 = sq2(u0) + sq2(u1) + (lo ? h0 : 0.f), e1 = sq2(w0) + sq2(w1) + (lo ? h1 : 0.f);
    float o0 = sq2(u3) + sq2(u4) + (lo ? 0.f : h0), o1 = sq2(w3) + sq2(w4) + (lo ? 0.f : h1);
    e0 += __shfl_xor_sync(~0u, e0, 1); e1 += __shfl_xor_sync(~0u, e1, 1); o0 += __shfl_xor_sync(~0u, o0, 1); o1 += __shfl_xor_sync(~0u, o1, 1);
    e0 += __shfl_xor_sync(~0u, e0, 2); e1 += __shfl_xor_sync(~0u, e1, 2); o0 += __shfl_xor_sync(~0u, o0, 2); o1 += __shfl_xor_sync(~0u, o1, 2);
    nrm[2 * PR] = fmaxf(e0, e1); nrm[2 * PR + 1] = fmaxf(o0, o1);
  }
}

__device__ __forceinline__ void hedgehog(const float (&p)[12], uint32_t (&f)[12], int t) {
#pragma unroll
  for (int hf = 0; hf < 2; hf++) {
    float v[6] = {p[2 * hf], p[2 * hf + 1], p[4 + 2 * hf], p[5 + 2 * hf], p[8 + 2 * hf], p[9 + 2 * hf]};
    float mx = fmaxf(fmaxf(fmaxf(v[0], v[1]), fmaxf(v[2], v[3])), fmaxf(v[4], v[5]));
    float mn = fminf(fminf(fminf(v[0], v[1]), fminf(v[2], v[3])), fminf(v[4], v[5]));
    mx = fmaxf(mx, __shfl_xor_sync(~0u, mx, 1)); mn = fminf(mn, __shfl_xor_sync(~0u, mn, 1));
    mx = fmaxf(mx, __shfl_xor_sync(~0u, mx, 2)); mn = fminf(mn, __shfl_xor_sync(~0u, mn, 2));
    const float bp = -mx * LOG2E, bn = mn * LOG2E;
    float ep[6], en[6];
#pragma unroll
    for (int i = 0; i < 6; i++) { ep[i] = ex2(fmaf(v[i], LOG2E, bp)); en[i] = ex2(fmaf(v[i], -LOG2E, bn)); }
    const float keep = (t < 2) ? 1.f : 0.f;
    float sp = (ep[0] + ep[1]) + (ep[2] + ep[3]) + keep * (ep[4] + ep[5]);
    float sn = (en[0] + en[1]) + (en[2] + en[3]) + keep * (en[4] + en[5]);
    sp += __shfl_xor_sync(~0u, sp, 1); sn += __shfl_xor_sync(~0u, sn, 1);
    sp += __shfl_xor_sync(~0u, sp, 2); sn += __shfl_xor_sync(~0u, sn, 2);
    const float rp = rcp(sp), rn = rcp(sn), rp2 = rp * keep, rn2 = rn * keep;
    f[0 + hf] = packbf(ep[0] * rp, ep[1] * rp);
    f[2 + hf] = packbf(ep[2] * rp, ep[3] * rp);
    f[4 + hf] = packbf(ep[4] * rp2, ep[5] * rp2);
    f[6 + hf] = packbf(en[0] * rn, en[1] * rn);
    f[8 + hf] = packbf(en[2] * rn, en[3] * rn);
    f[10 + hf] = packbf(en[4] * rn2, en[5] * rn2);
  }
}

__device__ __forceinline__ void issue_pq(float (&p0)[12], float (&p1)[12], uint32_t img, uint32_t wph) {
  const uint64_t ad = mkdesc(img, 128, 384, 0), a2 = mkdesc(img + 256, 0, 384, 0), wd = mkdesc(wph, 384, 128, 0);
  wg_fence();
  mma_n24_ss_tb(p0, ad, wd, 0);
  mma_n24_ss_tb(p0, a2, wd + 48, 1);
  mma_n24_ss_tb(p1, ad + 192, wd, 0);
  mma_n24_ss_tb(p1, a2 + 192, wd + 48, 1);
  wg_commit();
}
__device__ __forceinline__ void phi_q_store(const float (&p0)[12], const float (&p1)[12], uint4* dst, int t) {
  uint32_t f[12];
  hedgehog(p0, f, t);
#pragma unroll
  for (int ks = 0; ks < 3; ks++) dst[ks * 128] = make_uint4(f[4 * ks], f[4 * ks + 1], f[4 * ks + 2], f[4 * ks + 3]);
  hedgehog(p1, f, t);
#pragma unroll
  for (int ks = 0; ks < 3; ks++) dst[(3 + ks) * 128] = make_uint4(f[4 * ks], f[4 * ks + 1], f[4 * ks + 2], f[4 * ks + 3]);
}
__device__ __forceinline__ void phi_k_kv(const float (&p0)[12], const float (&p1)[12], float (&kv)[12], uint32_t buf, uint32_t lane_off,
                                         uint32_t vimg, int t) {
  uint32_t f[12];
  hedgehog(p0, f, t);
#pragma unroll
  for (int ks = 0; ks < 3; ks++) stsm4(buf + lane_off + ks * 256, f[4 * ks], f[4 * ks + 1], f[4 * ks + 2], f[4 * ks + 3]);
  hedgehog(p1, f, t);
#pragma unroll
  for (int ks = 0; ks < 3; ks++) stsm4(buf + lane_off + 6144 + ks * 256, f[4 * ks], f[4 * ks + 1], f[4 * ks + 2], f[4 * ks + 3]);
  fence_async_smem();
  bar_sync(2, 128);
  const uint64_t ad = mkdesc(buf, 768, 128, 0), vd = mkdesc(vimg, 384, 128, 0);
  wg_fence();
#pragma unroll
  for (int ks = 0; ks < 8; ks++) mma_n24_ss_tatb(kv, ad + ks * 96, vd + ks * 48, ks);
  wg_commit();
}
__device__ __forceinline__ void kv_store(const float (&kv)[12], float4* dst) {
  dst[0] = make_float4(kv[0], kv[1], kv[2], kv[3]);
  dst[32] = make_float4(kv[4], kv[5], kv[6], kv[7]);
  dst[64] = make_float4(kv[8], kv[9], kv[10], kv[11]);
}

__global__ void __launch_bounds__(512, 1)
k1_qkv(const __grid_constant__ CUtensorMap mx, const __grid_constant__ CUtensorMap mwa64, const __grid_constant__ CUtensorMap mwa16,
       const __grid_constant__ CUtensorMap mwb64, const __grid_constant__ CUtensorMap mwb16,
       const __nv_bfloat16* __restrict__ x, const __nv_bfloat16* __restrict__ wphi, const __nv_bfloat16* __restrict__ gate_w,
       const uint8_t* __restrict__ wa, const uint8_t* __restrict__ wb, const uint8_t* __restrict__ woa, const uint8_t* __restrict__ wob) {
  extern __shared__ __align__(1024) uint8_t smem[];
  const uint32_t sb = smem_u32(smem);
  const uint32_t full = sb + K1_BAR, empty = full + 8 * K1_NST;
  const int warp = __shfl_sync(~0u, threadIdx.x >> 5, 0), lane = threadIdx.x & 31, wg = warp >> 2;
  const int bid = blockIdx.x;
  const int mt = (bid & 3) + 4 * (bid >> 5), hg = (bid >> 2) & 7;
  PROF(threadIdx.x == 0, 0, 0);
  if (threadIdx.x == 384) {
    for (int i = 0; i < K1_NST; i++) { mbar_init(full + 8 * i, 1); mbar_init(empty + 8 * i, 2); }
    asm volatile("fence.mbarrier_init.release.cluster;" ::: "memory");
    for (int it = 0; it < K1_NST; it++) {
      const uint32_t d = sb + it * K1_STAGE, b = full + 8 * it;
      mbar_expect(b, K1_STAGE);
      tma2(d, &mx, it * 64, mt * 128, b);
      tma3(d + 16384, &mwa64, hg * 80, it * 64, 0, b);
      tma3(d + 40960, &mwa16, hg * 80 + 64, it * 64, 0, b);
    }
    pdl_launch();
  }
  __syncthreads();

  if (wg == 3) {
    reg_dec<40>();
    if (warp == 12) {
      if (lane == 0) {
        for (int it = K1_NST; it < 20; it++) {
          const int s = it % K1_NST, ks = it % 10;
          mbar_wait(empty + 8 * s, ((it / K1_NST) - 1) & 1);
          const uint32_t d = sb + s * K1_STAGE, b = full + 8 * s;
          mbar_expect(b, K1_STAGE);
          tma2(d, &mx, ks * 64, mt * 128, b);
          tma3(d + 16384, it < 10 ? &mwa64 : &mwb64, hg * 80, ks * 64, 0, b);
          tma3(d + 40960, it < 10 ? &mwa16 : &mwb16, hg * 80 + 64, ks * 64, 0, b);
        }
      }
    } else {
      if (bid == 0 && warp == 14) g_KVFLAG[lane] = 0;
      mbar_wait(full, 0);
      if (warp == 13 && lane == 0) { prefetch_l2(wa + (size_t)bid * 19200, 19200); prefetch_l2(wb + (size_t)bid * 19200, 19200); }
      uint2 gw[5];
#pragma unroll
      for (int i = 0; i < 5; i++) gw[i] = *(const uint2*)(gate_w + i * 128 + lane * 4);
      for (int r = warp - 13; r < 16; r += 3) {
        const int row = mt * 128 + hg * 16 + r;
        float acc = 0.f;
#pragma unroll
        for (int i = 0; i < 5; i++) {
          const uint2 xv = *(const uint2*)(x + (size_t)row * DM + i * 128 + lane * 4);
          uint32_t p0, p1;
          asm("mul.rn.bf16x2 %0, %1, %2;" : "=r"(p0) : "r"(xv.x), "r"(gw[i].x));
          asm("mul.rn.bf16x2 %0, %1, %2;" : "=r"(p1) : "r"(xv.y), "r"(gw[i].y));
          acc += (bf_lo(p0) + bf_hi(p0)) + (bf_lo(p1) + bf_hi(p1));
        }
#pragma unroll
        for (int o = 16; o; o >>= 1) acc += __shfl_xor_sync(~0u, acc, o);
        if (lane == 0) {
          const float g = bf_round(__fdividef(1.f, 1.f + __expf(-bf_round(acc))));
          g_GATE[row] = make_float2(g, bf_round(1.f - g));
        }
      }
      for (int kg = bid; kg < 160; kg += 128) {
        const uint8_t* src = kg < 80 ? woa + (size_t)kg * 10240 : wob + (size_t)(kg - 80) * 10240;
        for (int e = (warp - 13) * 32 + lane; e < 640; e += 96) {
          const int nt = e / 80, r = e % 80;
          *(uint4*)(g_WOI + (size_t)nt * 204800 + kg * 1280 + r * 16) = __ldg((const uint4*)(src + (r & 7) * 1280 + (nt * 10 + (r >> 3)) * 16));
        }
      }
    }
  } else if (wg == 2) {
    reg_dec<112>();
    const int tid = threadIdx.x - 256, w4 = warp & 3, t = lane & 3;
    for (int e = tid; e < 4 * 768; e += 128) {
      const int i = e / 768, r = e % 768, kg = r / 192, nc = (r % 192) / 64, kr = (r % 64) / 8, ne = r % 8;
      const int slot = kg * 8 + kr, n = nc * 8 + ne;
      int d = -1;
      if (i & 1) { if (slot < 16) d = slot + 4; else if (slot >= 20 && slot < 24) d = slot - 20; }
      else if (slot < 20) d = slot;
      const int f = n < 20 ? n : n - 4;
      const unsigned short val = d >= 0 ? *(const unsigned short*)(wphi + ((size_t)(hg * 4 + i) * 20 + d) * 20 + f) : (unsigned short)0;
      *(unsigned short*)(smem + K1_WPH + e * 2) = val;
    }
    fence_async_smem();
    bar_sync(1, 384);
    const uint32_t stg = sb + K1_STG, wph = sb + K1_WPH;
    float pa0[12], pa1[12], pb0[12], pb1[12];
    issue_pq(pa0, pa1, stg, wph);
    wg_wait<0>();
    pin(pa0); pin(pa1);
#pragma unroll 1
    for (int i = 0; i < 4; i += 2) {
      uint4* dst = g_PHIQ + ((size_t)((hg * 4 + i) * 32 + mt * 2) * 3) * 128 + tid;
      issue_pq(pb0, pb1, stg + (i + 1) * 6144, wph + (i + 1) * 1536);
      phi_q_store(pa0, pa1, dst, t);
      wg_wait<0>();
      pin(pb0); pin(pb1);
      issue_pq(pa0, pa1, stg + (i + 2) * 6144, wph + ((i + 2) & 3) * 1536);
      phi_q_store(pb0, pb1, dst + 32 * 3 * 128, t);
      wg_wait<0>();
      pin(pa0); pin(pa1);
    }
    PROF(tid == 0, 0, 6);
    bar_sync(2, 128);
    const uint32_t lane_off = (w4 * 2 + ((lane >> 3) & 1)) * 768 + (lane >> 4) * 128 + (lane & 7) * 16;
#pragma unroll 1
    for (int i = 0; i < 4; i += 2) {
      float kva[12], kvb[12];
      float4* dst = g_KVP + (size_t)((hg * 4 + i) * 16 + mt) * 288 + w4 * 96 + lane;
      issue_pq(pb0, pb1, stg + (5 + i) * 6144, wph + (i + 1) * 1536);
      phi_k_kv(pa0, pa1, kva, stg, lane_off, stg + (8 + i) * 6144, t);
      wg_wait<1>();
      pin(pb0); pin(pb1);
      issue_pq(pa0, pa1, stg + (6 + i) * 6144, wph + ((i + 2) & 3) * 1536);
      phi_k_kv(pb0, pb1, kvb, stg + 12288, lane_off, stg + (9 + i) * 6144, t);
      wg_wait<1>();
      pin(pa0); pin(pa1); pin(kva);
      if (w4 < 3) kv_store(kva, dst);
      wg_wait<0>();
      pin(kvb);
      if (w4 < 3) kv_store(kvb, dst + 16 * 288);
      bar_sync(2, 128);
    }
    PROF(tid == 0, 0, 7);
  } else {
    reg_inc<176>();
    const int w4 = warp & 3, t = lane & 3;
    const uint32_t arow = wg * 8192 + (w4 * 16 + (lane & 15)) * 128, asw = lane & 7, ahi = lane >> 4;
    float a1[96], a2[24];
#pragma unroll 1
    for (int tile = 0; tile < 2; tile++) {
#pragma unroll 1
      for (int ks = 0; ks < 10; ks++) {
        const int it = tile * 10 + ks, s = it % K1_NST;
        mbar_wait(full + 8 * s, (it / K1_NST) & 1);
        PROF(threadIdx.x == 0 && it == 0, 0, 1);
        const uint32_t st = sb + s * K1_STAGE;
        if (ks > 0) {
          wg_wait<0>();
          if ((threadIdx.x & 127) == 0) mbar_arrive(empty + 8 * ((it - 1) % K1_NST));
        }
        uint32_t a[4][4];
#pragma unroll
        for (int kk = 0; kk < 4; kk++) ldsm4(a[kk], st + arow + (((kk * 2 + ahi) ^ asw) << 4));
        const uint64_t b1 = mkdesc(st + 16384, 8192, 1024, 1);
        const uint64_t b2 = mkdesc(st + 40960, 2048, 256, 3);
        wg_fence();
#pragma unroll
        for (int kk = 0; kk < 4; kk++) {
          mma_n192_rs_tb(a1, a[kk][0], a[kk][1], a[kk][2], a[kk][3], b1 + kk * 128, ks | kk);
          mma_n48_rs_tb(a2, a[kk][0], a[kk][1], a[kk][2], a[kk][3], b2 + kk * 32, ks | kk);
        }
        wg_commit();
      }
      wg_wait<0>();
      pin(a1); pin(a2);
      PROF(threadIdx.x == 0, 0, 2 + 2 * tile);
      if ((threadIdx.x & 127) == 0) mbar_arrive(empty + 8 * ((tile * 10 + 9) % K1_NST));
      const int rg = wg * 8 + w4 * 2;
      const int mi = lane >> 3;
      float nrm[4];
      if (tile == 0) {
        const uint32_t base = sb + K1_STG + (rg + (mi & 1)) * 384 + (lane & 7) * 16;
        const uint32_t ad01 = base + (mi >> 1) * 128, ad2 = base + (mi >> 1) * 6144 + 256;
        const uint32_t one = (t & 1) ? 0u : BF_ONE;
        stage_pair<0, 0, false>(a1, a2, 1.f, 1.f, 0u, 0u, ad01, ad2, 6144, t, nrm);
        stage_pair<0, 1, false>(a1, a2, 1.f, 1.f, 0u, 0u, ad01, ad2, 6144, t, nrm);
        stage_pair<1, 0, false>(a1, a2, 1.f, 1.f, 0u, 0u, ad01, ad2, 6144, t, nrm);
        stage_pair<1, 1, false>(a1, a2, 1.f, 1.f, 0u, 0u, ad01, ad2, 6144, t, nrm);
        stage_pair<2, 0, false>(a1, a2, 1.f, 1.f, one, one, ad01, ad2, 6144, t, nrm);
        stage_pair<2, 1, false>(a1, a2, 1.f, 1.f, one, one, ad01, ad2, 6144, t, nrm);
        fence_async_smem();
        bar_arrive(1, 384);
        PROF(threadIdx.x == 0, 0, 3);
      } else {
        const int fs = wg == 0 ? 2 : 0;
        mbar_wait(empty + 8 * fs, wg == 0 ? 1 : 0);
        const uint32_t stg = sb + fs * K1_STAGE;
        const uint32_t base = stg + (w4 * 2 + (mi & 1)) * 384 + (lane & 7) * 16;
        const uint32_t ad01 = base + (mi >> 1) * 128, ad2 = base + (mi >> 1) * 3072 + 256;
        const bool p0 = (POLY_MASK >> rg) & 1, p1 = (POLY_MASK >> (rg + 1)) & 1;
        const uint32_t kp = (t & 1) ? 0u : (BF_ONE | (BF_MAGIC << 16)), km = (t & 1) ? BF_MU_LO : (BF_ONE | (BF_MU_HI << 16));
        const uint32_t vp = (t & 1) ? 0u : (BF_ONE | 0x8000u), vm = (t & 1) ? 0u : BF_ONE;
        stage_pair<1, 0, true>(a1, a2, 1.f, 1.f, p0 ? kp : km, p1 ? kp : km, ad01, ad2, 3072, t, nrm);
        stage_pair<1, 1, true>(a1, a2, 1.f, 1.f, p0 ? kp : km, p1 ? kp : km, ad01, ad2, 3072, t, nrm);
        stage_pair<2, 0, false>(a1, a2, p0 ? -1.f : 1.f, p1 ? -1.f : 1.f, p0 ? vp : vm, p1 ? vp : vm, ad01, ad2, 3072, t, nrm);
        stage_pair<2, 1, false>(a1, a2, p0 ? -1.f : 1.f, p1 ? -1.f : 1.f, p0 ? vp : vm, p1 ? vp : vm, ad01, ad2, 3072, t, nrm);
        stage_pair<0, 0, false>(a1, a2, QSCALE, QSCALE, 0u, 0u, ad01, ad2, 3072, t, nrm);
        stage_pair<0, 1, false>(a1, a2, QSCALE, QSCALE, 0u, 0u, ad01, ad2, 3072, t, nrm);
        fence_async_smem();
        bar_sync(3 + wg, 128);
        if (w4 == 0 && lane < 12) {
          const int sec = lane >> 2, i = lane & 3;
          uint8_t* dst = g_QKVB + (size_t)(sec * NH + hg * 4 + i) * IMG_HEAD + (size_t)(mt * 2 + wg) * 3072;
          bulk_s2g(dst, stg + lane * 3072, 3072);
          asm volatile("cp.async.bulk.commit_group;" ::: "memory");
        }
#pragma unroll
        for (int i = 0; i < 4; i++) {
          const uint32_t m = __reduce_max_sync(~0u, __float_as_uint(nrm[i]));
          if (lane == i) g_KMAX[(hg * 4 + i) * 128 + mt * 8 + wg * 4 + w4] = __uint_as_float(m);
        }
        if (w4 == 0 && lane < 12) asm volatile("cp.async.bulk.wait_group 0;" ::: "memory");
        PROF(threadIdx.x == 0, 0, 5);
      }
    }
  }
}

constexpr int K2_K = 0, K2_V = IMG_HEAD, K2_Q = 2 * IMG_HEAD, K2_KV = K2_Q + 8 * 3072, K2_BAR = K2_KV + 2304, K2_SMEM = K2_BAR + 128;

__device__ __forceinline__ uint32_t exp2_bits(float y0, float y1, uint32_t cm, uint32_t neg1) {
  uint32_t w, m, r;
  asm("prmt.b32 %0, %1, %2, 0x6521;" : "=r"(w) : "r"(__float_as_uint(y0)), "r"(__float_as_uint(y1)));
  asm("lop3.b32 %0, %1, 0x007F007F, %2, 0xEA;" : "=r"(m) : "r"(w), "r"(cm));
  const uint32_t e = m * neg1 + w;
  asm("fma.rn.bf16x2 %0, %1, %2, %3;" : "=r"(r) : "r"(w), "r"(m), "r"(e));
  return r;
}
__device__ __forceinline__ void exp_tile(const float (&s)[64], uint32_t (&p)[32], uint32_t cm, uint32_t neg1) {
#pragma unroll
  for (int g = 0; g < 16; g++) {
    if ((POLY_MASK >> g) & 1) {
      p[2 * g] = exp2_bits(s[4 * g], s[4 * g + 1], cm, neg1);
      p[2 * g + 1] = exp2_bits(s[4 * g + 2], s[4 * g + 3], cm, neg1);
    } else {
      p[2 * g] = packbf(ex2(s[4 * g]), ex2(s[4 * g + 1]));
      p[2 * g + 1] = packbf(ex2(s[4 * g + 2]), ex2(s[4 * g + 3]));
    }
  }
}
__device__ __forceinline__ void issue_qk(float (&s)[64], uint64_t qd, uint64_t kd) {
  mma_n128_ss(s, qd, kd, 0);
  mma_n128_ss(s, (qd + 16) & ~(0x3FFFull << 16), (kd + 16) & ~(0x3FFFull << 16), 1);
}
__device__ __forceinline__ void issue_pv(float (&o)[12], const uint32_t (&p)[32], uint64_t vd, int acc) {
#pragma unroll
  for (int kk = 0; kk < 8; kk++) mma_n24_rs_tb(o, p[4 * kk], p[4 * kk + 1], p[4 * kk + 2], p[4 * kk + 3], vd + kk * 48, acc | kk);
}
__device__ __forceinline__ void attn_pair(float (&s0)[64], float (&s1)[64], uint32_t (&p0)[32], uint32_t (&p1)[32], float (&o)[12],
                                          uint64_t qd1, uint64_t kd1, uint64_t qd2, uint64_t kd2, uint64_t vd, int acc, uint32_t bar,
                                          uint32_t cm, uint32_t neg1) {
  wg_fence();
  issue_qk(s1, qd1, kd1);
  wg_commit();
  exp_tile(s0, p0, cm, neg1);
  wg_fence();
  issue_pv(o, p0, vd, acc);
  wg_commit();
  wg_wait<1>();
  pin(s1); pin(p1);
  mbar_wait_u(bar, 0);
  wg_fence();
  issue_qk(s0, qd2, kd2);
  wg_commit();
  exp_tile(s1, p1, cm, neg1);
  wg_fence();
  issue_pv(o, p1, vd + 384, 1);
  wg_commit();
}
__device__ __forceinline__ void store_o(const float (&o)[12], int odd, int lane, int m16, int colgrp, float eps, float s0, float s1) {
  const int src = (lane & ~3) | (odd ? 0 : 2);
  const float l0 = __shfl_sync(~0u, o[8], src) + eps, l1 = __shfl_sync(~0u, o[10], src) + eps;
  const float r0 = s0 * rcp(l0), r1 = s1 * rcp(l1);
  uint2* base = g_OAB + ((size_t)m16 * 160 + colgrp) * 32 + lane;
  uint2* c0 = base + (odd ? 3 * 32 : 0);
  c0[0] = make_uint2(packbf(o[0] * r0, o[1] * r0), packbf(o[2] * r1, o[3] * r1));
  c0[32] = make_uint2(packbf(o[4] * r0, o[5] * r0), packbf(o[6] * r1, o[7] * r1));
  if (((lane & 3) < 2) != (odd != 0)) base[64] = make_uint2(packbf(o[8] * r0, o[9] * r0), packbf(o[10] * r1, o[11] * r1));
}

__device__ __forceinline__ void fetch_kv(uint32_t dst, int h, uint32_t bar) {
  uint32_t v = 0;
  for (int n = 0; n < 20000000 && !v; n++) asm volatile("ld.acquire.gpu.global.u32 %0, [%1];" : "=r"(v) : "l"(g_KVFLAG + (h >> 3)) : "memory");
  if (!v) __trap();
  fence_async_all();
  mbar_expect(bar, 2304);
  bulk_g2s(dst, g_KVB + h * 2304, 2304, bar);
}

__global__ void __launch_bounds__(256, 1) k2_attn(uint32_t cm, uint32_t neg1) {
  extern __shared__ __align__(1024) uint8_t smem[];
  const uint32_t sb = smem_u32(smem);
  const int tid = threadIdx.x, lane = tid & 31;
  const int warp = __shfl_sync(~0u, tid >> 5, 0), wg = warp >> 2, w4 = warp & 3, t = lane & 3;
  PROF(tid == 0, 1, 0);
  if (blockIdx.x < 4) {
    pdl_wait();
    if (tid == 0) pdl_launch();
#pragma unroll 1
    for (int e0 = tid; e0 < 8 * 288; e0 += 256) {
      const int h = blockIdx.x * 8 + e0 / 288, e = e0 % 288;
      const float4* src = g_KVP + (size_t)h * 16 * 288 + e;
      uint4 v[16];
#pragma unroll
      for (int m = 0; m < 16; m++) v[m] = ldg_cg4(src + m * 288);
      float4 acc = make_float4(0.f, 0.f, 0.f, 0.f);
#pragma unroll
      for (int m = 0; m < 16; m++) {
        acc.x += __uint_as_float(v[m].x); acc.y += __uint_as_float(v[m].y); acc.z += __uint_as_float(v[m].z); acc.w += __uint_as_float(v[m].w);
      }
      uint8_t* dst = g_KVB + h * 2304 + (e / 96) * 768 + ((e % 96) >> 5) * 128 + (e & 31) * 4;
      *(uint32_t*)dst = packbf(acc.x, acc.y);
      *(uint32_t*)(dst + 384) = packbf(acc.z, acc.w);
    }
    __threadfence();
    __syncthreads();
    if (tid == 0) asm volatile("st.release.gpu.global.u32 [%0], %1;" ::"l"(g_KVFLAG + blockIdx.x), "r"(1u) : "memory");
    PROF(tid == 0, 1, 7);
    return;
  }
  const int cb = blockIdx.x - 4, h = cb >> 2, quarter = cb & 3, odd = h & 1;
  const uint32_t bar = sb + K2_BAR;
  const uint8_t* gq = g_QKVB + (size_t)h * IMG_HEAD;
  const uint8_t* gk = gq + (size_t)NH * IMG_HEAD;
  const uint8_t* gv = gk + (size_t)NH * IMG_HEAD;
  if (tid == 0) {
    for (int i = 0; i < 9; i++) mbar_init(bar + 8 * i, 1);
    asm volatile("fence.mbarrier_init.release.cluster;" ::: "memory");
  }
  pdl_wait();
  PROF(tid == 0, 1, 1);
  if (tid == 0) {
    pdl_launch();
    mbar_expect(bar, 24576);
    bulk_g2s(sb + K2_K, gk, 12288, bar);
    bulk_g2s(sb + K2_V, gv, 12288, bar);
  }
  const int mt0 = quarter * 8 + wg * 4;
  uint32_t q[4][6];
#pragma unroll
  for (int p = 0; p < 4; p++) {
    const uint8_t* src = gq + (size_t)((mt0 + p) * 8 + w4 * 2) * 384 + lane * 4;
#pragma unroll
    for (int c = 0; c < 3; c++) { q[p][2 * c] = ldg_cg(src + c * 128); q[p][2 * c + 1] = ldg_cg(src + 384 + c * 128); }
  }
  const uint4 km4 = ldg_cg4(g_KMAX + h * 128 + lane * 4);
  const float kmax = sqrt_ap(__uint_as_float(__reduce_max_sync(~0u, max(max(km4.x, km4.y), max(km4.z, km4.w))))) * 1.01f;
  if (warp == 0 && lane >= 1 && lane < 8) {
    mbar_expect(bar + 8 * lane, 24576);
    bulk_g2s(sb + K2_K + lane * 12288, gk + lane * 12288, 12288, bar + 8 * lane);
    bulk_g2s(sb + K2_V + lane * 12288, gv + lane * 12288, 12288, bar + 8 * lane);
  }
  const bool is_feat = (t < 2) != (odd != 0);
  float bnd[4][2];
  bool unsafe = false;
#pragma unroll
  for (int p = 0; p < 4; p++)
#pragma unroll
    for (int hf = 0; hf < 2; hf++) {
      float n2 = 0.f;
#pragma unroll
      for (int c = 0; c < 3; c++) { const uint32_t v = q[p][2 * c + hf]; n2 = fmaf(bf_lo(v), bf_lo(v), fmaf(bf_hi(v), bf_hi(v), n2)); }
      n2 += __shfl_xor_sync(~0u, n2, 1);
      n2 += __shfl_xor_sync(~0u, n2, 2);
      bnd[p][hf] = sqrt_ap(n2) * kmax * 1.01f;
      unsafe |= !(bnd[p][hf] <= FAST_BOUND);
    }
  const bool slow = __any_sync(~0u, __syncthreads_or(unsafe));
#pragma unroll
  for (int p = 0; p < 4; p++)
#pragma unroll
    for (int hf = 0; hf < 2; hf++) {
      const uint32_t dst = sb + K2_Q + (wg * 4 + p) * 3072 + (w4 * 2 + hf) * 384 + lane * 4;
      sts32(dst, q[p][hf]);
      sts32(dst + 128, q[p][2 + hf]);
      const uint32_t v = q[p][4 + hf];
      uint32_t c2 = packbf(bf_lo(v) * 0.5f, bf_hi(v) * 0.5f);
      if (!is_feat) c2 = slow ? 0u : ((t & 1) ? 0x3F00u : packbf(-0.5f * bnd[p][hf], 0.5f));
      sts32(dst + 256, c2);
    }
  fence_async_smem();
  bar_sync(1 + wg, 128);
  PROF(tid == 0, 1, 2);
  const int row_g = mt0 * 64 + w4 * 16 + (lane >> 2);
  const int colgrp = (h >> 1) * 5;
  const uint64_t kd0 = mkdesc(sb + K2_K, 128, 384, 0), vd0 = mkdesc(sb + K2_V, 384, 128, 0);
  const uint64_t qd0 = mkdesc(sb + K2_Q + wg * 4 * 3072, 128, 384, 0);
  float o[12];
  if (!slow) {
    float s0[64], s1[64];
    uint32_t p0[32], p1[32];
    mbar_wait_u(bar, 0);
    wg_fence();
    issue_qk(s0, qd0, kd0);
    wg_commit();
    wg_wait<0>();
    pin(s0);
#pragma unroll 1
    for (int pass = 0; pass < 4; pass++) {
      const uint64_t qd = qd0 + pass * 192;
      uint64_t kd = kd0, vd = vd0;
      if (pass == 3 && tid == 0) fetch_kv(sb + K2_KV, h, bar + 64);
#pragma unroll 1
      for (int j = 0; j < 7; j++) {
        attn_pair(s0, s1, p0, p1, o, qd, kd + 384, qd, kd + 768, vd, j, bar + 8 * (j + 1), cm, neg1);
        wg_wait<1>();
        pin(s0); pin(p0);
        kd += 768; vd += 768;
      }
      attn_pair(s0, s1, p0, p1, o, qd, kd + 384, qd0 + ((pass + 1) & 3) * 192, kd0, vd, 1, bar, cm, neg1);
      const float g0 = g_GATE[row_g + pass * 64].y, g1 = g_GATE[row_g + pass * 64 + 8].y;
      wg_wait<0>();
      pin(s0); pin(p0); pin(o);
      store_o(o, odd, lane, (mt0 + pass) * 4 + w4, 80 + colgrp, 0.f, g0, g1);
      PROF(tid == 0, 1, 3 + pass);
    }
  } else {
    float s[64];
    uint32_t p[32];
#pragma unroll 1
    for (int pass = 0; pass < 4; pass++) {
      float m0 = -INFINITY, m1 = -INFINITY;
      if (pass == 3 && tid == 0) fetch_kv(sb + K2_KV, h, bar + 64);
#pragma unroll
      for (int i = 0; i < 12; i++) o[i] = 0.f;
#pragma unroll 1
      for (int j = 0; j < 16; j++) {
        if (pass == 0) mbar_wait_u(bar + 8 * (j >> 1), 0);
        wg_fence();
        issue_qk(s, qd0 + pass * 192, kd0 + j * 384);
        wg_commit();
        wg_wait<0>();
        pin(s);
        float n0 = m0, n1 = m1;
#pragma unroll
        for (int g = 0; g < 16; g++) { n0 = fmaxf(n0, fmaxf(s[4 * g], s[4 * g + 1])); n1 = fmaxf(n1, fmaxf(s[4 * g + 2], s[4 * g + 3])); }
        n0 = fmaxf(n0, __shfl_xor_sync(~0u, n0, 1)); n1 = fmaxf(n1, __shfl_xor_sync(~0u, n1, 1));
        n0 = fmaxf(n0, __shfl_xor_sync(~0u, n0, 2)); n1 = fmaxf(n1, __shfl_xor_sync(~0u, n1, 2));
        const float c0 = ex2(m0 - n0), c1 = ex2(m1 - n1);
        m0 = n0; m1 = n1;
#pragma unroll
        for (int i = 0; i < 3; i++) { o[4 * i] *= c0; o[4 * i + 1] *= c0; o[4 * i + 2] *= c1; o[4 * i + 3] *= c1; }
#pragma unroll
        for (int g = 0; g < 16; g++) {
          const uint32_t sg = ((POLY_MASK >> g) & 1) ? 0x80008000u : 0u;
          p[2 * g] = packbf(ex2(s[4 * g] - m0), ex2(s[4 * g + 1] - m0)) ^ sg;
          p[2 * g + 1] = packbf(ex2(s[4 * g + 2] - m1), ex2(s[4 * g + 3] - m1)) ^ sg;
        }
        wg_fence();
        issue_pv(o, p, vd0 + j * 384, 1);
        wg_commit();
        wg_wait<0>();
        pin(o); pin(p);
      }
      const float g0 = g_GATE[row_g + pass * 64].y, g1 = g_GATE[row_g + pass * 64 + 8].y;
      store_o(o, odd, lane, (mt0 + pass) * 4 + w4, 80 + colgrp, 0.f, g0, g1);
    }
  }
  {
    uint4 f[4][3];
    float g[4][2];
#pragma unroll
    for (int p = 0; p < 4; p++) {
      const uint4* src = g_PHIQ + ((size_t)(h * 32 + mt0 + p) * 3) * 128 + (tid & 127);
      f[p][0] = ldg_cg4(src); f[p][1] = ldg_cg4(src + 128); f[p][2] = ldg_cg4(src + 256);
      g[p][0] = g_GATE[row_g + p * 64].x; g[p][1] = g_GATE[row_g + p * 64 + 8].x;
    }
    mbar_wait_u(bar + 64, 0);
    const uint64_t kvd = mkdesc(sb + K2_KV, 384, 128, 0);
    float oa[4][12];
    wg_fence();
#pragma unroll
    for (int p = 0; p < 4; p++)
#pragma unroll
      for (int ks = 0; ks < 3; ks++) mma_n24_rs_tb(oa[p], f[p][ks].x, f[p][ks].y, f[p][ks].z, f[p][ks].w, kvd + ks * 48, ks);
    wg_commit();
    wg_wait<0>();
#pragma unroll
    for (int p = 0; p < 4; p++) {
      pin(oa[p]);
      store_o(oa[p], odd, lane, (mt0 + p) * 4 + w4, colgrp, 1e-6f, g[p][0], g[p][1]);
    }
  }
  PROF(tid == 0, 1, 7);
}

constexpr int K3_OUT = 204800, K3_BAR = K3_OUT + 20480, K3_SMEM = K3_BAR + 128, K3_D = 8;

__device__ __forceinline__ void k3_load(uint2 (&a)[8], const uint2* src) {
#pragma unroll
  for (int j = 0; j < 8; j++) asm volatile("ld.global.cg.v2.b32 {%0,%1}, [%2];" : "=r"(a[j].x), "=r"(a[j].y) : "l"(src + j * 32) : "memory");
}

__global__ void __launch_bounds__(256, 1) k3_out(const __grid_constant__ CUtensorMap mout) {
  extern __shared__ __align__(1024) uint8_t smem[];
  const uint32_t sb = smem_u32(smem);
  const uint32_t full = sb + K3_BAR;
  const int warp = __shfl_sync(~0u, threadIdx.x >> 5, 0), lane = threadIdx.x & 31, wg = warp >> 2, w4 = warp & 3;
  const int bid = blockIdx.x, nt = bid & 7, mt = bid >> 3;
  PROF(threadIdx.x == 0, 2, 0);
  if (threadIdx.x == 0) {
    for (int i = 0; i < 10; i++) mbar_init(full + 8 * i, 1);
    asm volatile("fence.mbarrier_init.release.cluster;" ::: "memory");
    for (int i = 0; i < 10; i++) {
      mbar_expect(full + 8 * i, 20480);
      bulk_g2s(sb + i * 20480, g_WOI + (size_t)nt * 204800 + i * 20480, 20480, full + 8 * i);
    }
  }
  __syncthreads();
  pdl_wait();
  PROF(threadIdx.x == 0, 2, 1);
  const uint2* src = g_OAB + (size_t)(mt * 8 + warp) * 160 * 32 + lane;
  uint2 a[K3_D][8];
#pragma unroll
  for (int i = 0; i < K3_D; i++) k3_load(a[i], src + i * 256);
  float acc[40];
  const uint64_t bd = mkdesc(sb, 1280, 128, 0);
#pragma unroll
  for (int it = 0; it < 20; it++) {
    if ((it & 1) == 0) mbar_wait_u(full + 8 * (it >> 1), 0);
    wg_fence();
#pragma unroll
    for (int kk = 0; kk < 4; kk++) {
      const uint2 lo = a[it % K3_D][2 * kk], hi = a[it % K3_D][2 * kk + 1];
      mma_n80_rs_tb(acc, lo.x, lo.y, hi.x, hi.y, bd + (it * 4 + kk) * 160, it | kk);
    }
    wg_commit();
    PROF(threadIdx.x == 0 && it == 0, 2, 2);
    if (it > 0 && it - 1 + K3_D < 20) {
      wg_wait<1>();
      k3_load(a[(it - 1) % K3_D], src + (it - 1 + K3_D) * 256);
    }
  }
  wg_wait<0>();
  pin(acc);
  PROF(threadIdx.x == 0, 2, 3);
  const uint32_t ob = sb + K3_OUT + wg * 10240;
  const uint32_t oa = ob + (w4 * 16 + (lane & 15)) * 160 + (lane >> 4) * 16;
#pragma unroll
  for (int j = 0; j < 10; j += 2)
    stsm4(oa + j * 16, packbf(acc[4 * j], acc[4 * j + 1]), packbf(acc[4 * j + 2], acc[4 * j + 3]), packbf(acc[4 * j + 4], acc[4 * j + 5]),
          packbf(acc[4 * j + 6], acc[4 * j + 7]));
  fence_async_smem();
  bar_sync(1 + wg, 128);
  if ((threadIdx.x & 127) == 0) {
    asm volatile("cp.async.bulk.tensor.2d.global.shared::cta.bulk_group [%0, {%2,%3}], [%1];" ::"l"(&mout), "r"(ob), "r"(nt * 80), "r"(mt * 128 + wg * 64) : "memory");
    asm volatile("cp.async.bulk.commit_group;" ::: "memory");
    asm volatile("cp.async.bulk.wait_group 0;" ::: "memory");
  }
  PROF(threadIdx.x == 0, 2, 4);
}

typedef CUresult (*EncodeFn)(CUtensorMap*, CUtensorMapDataType, cuuint32_t, void*, const cuuint64_t*, const cuuint64_t*, const cuuint32_t*,
                             const cuuint32_t*, CUtensorMapInterleave, CUtensorMapSwizzle, CUtensorMapL2promotion, CUtensorMapFloatOOBfill);

void encode(EncodeFn fn, CUtensorMap* m, const void* p, int rank, const cuuint64_t* dims, const cuuint64_t* strides, const cuuint32_t* box,
            CUtensorMapSwizzle sw) {
  const cuuint32_t es[3] = {1, 1, 1};
  fn(m, CU_TENSOR_MAP_DATA_TYPE_BFLOAT16, rank, const_cast<void*>(p), dims, strides, box, es, CU_TENSOR_MAP_INTERLEAVE_NONE, sw,
     CU_TENSOR_MAP_L2_PROMOTION_L2_128B, CU_TENSOR_MAP_FLOAT_OOB_FILL_NONE);
}

}

extern "C" void kernel_launch(void* const* d_in, const int* in_sizes, int n_in, void* d_out, int out_size) {
  (void)in_sizes; (void)n_in; (void)out_size;
  const __nv_bfloat16* x = (const __nv_bfloat16*)d_in[0];
  const void* wa = d_in[1];
  const __nv_bfloat16* wphi = (const __nv_bfloat16*)d_in[2];
  const void* woa = d_in[3];
  const void* wb = d_in[5];
  const void* wob = d_in[6];
  const __nv_bfloat16* gate_w = (const __nv_bfloat16*)d_in[7];

  static EncodeFn enc = nullptr;
  if (!enc) {
    void* fn = nullptr;
    cudaDriverEntryPointQueryResult qr;
    cudaGetDriverEntryPoint("cuTensorMapEncodeTiled", &fn, cudaEnableDefault, &qr);
    enc = (EncodeFn)fn;
    cudaFuncSetAttribute(k1_qkv, cudaFuncAttributeMaxDynamicSharedMemorySize, K1_SMEM);
    cudaFuncSetAttribute(k2_attn, cudaFuncAttributeMaxDynamicSharedMemorySize, K2_SMEM);
    cudaFuncSetAttribute(k3_out, cudaFuncAttributeMaxDynamicSharedMemorySize, K3_SMEM);
  }
  CUtensorMap mx, mwa64, mwa16, mwb64, mwb16, mout;
  {
    const cuuint64_t dx[2] = {640, 2048}, sx[1] = {1280};
    const cuuint32_t bx[2] = {64, 128};
    encode(enc, &mx, x, 2, dx, sx, bx, CU_TENSOR_MAP_SWIZZLE_128B);
    const cuuint32_t bo[2] = {80, 64};
    encode(enc, &mout, d_out, 2, dx, sx, bo, CU_TENSOR_MAP_SWIZZLE_NONE);
    const cuuint64_t dw[3] = {640, 640, 3}, sw[2] = {3840, 1280};
    const cuuint32_t b64[3] = {64, 64, 3}, b16[3] = {16, 64, 3};
    encode(enc, &mwa64, wa, 3, dw, sw, b64, CU_TENSOR_MAP_SWIZZLE_128B);
    encode(enc, &mwa16, wa, 3, dw, sw, b16, CU_TENSOR_MAP_SWIZZLE_32B);
    encode(enc, &mwb64, wb, 3, dw, sw, b64, CU_TENSOR_MAP_SWIZZLE_128B);
    encode(enc, &mwb16, wb, 3, dw, sw, b16, CU_TENSOR_MAP_SWIZZLE_32B);
  }
  cudaStream_t st = cudaStreamPerThread;
  cudaLaunchAttribute pdl[1];
  pdl[0].id = cudaLaunchAttributeProgrammaticStreamSerialization;
  pdl[0].val.programmaticStreamSerializationAllowed = 1;
  cudaLaunchConfig_t c = {};
  c.stream = st;
  c.gridDim = dim3(128); c.blockDim = dim3(512); c.dynamicSmemBytes = K1_SMEM; c.attrs = nullptr; c.numAttrs = 0;
  cudaLaunchKernelEx(&c, k1_qkv, mx, mwa64, mwa16, mwb64, mwb16, x, wphi, gate_w, (const uint8_t*)wa, (const uint8_t*)wb,
                     (const uint8_t*)woa, (const uint8_t*)wob);
  c.gridDim = dim3(132); c.blockDim = dim3(256); c.dynamicSmemBytes = K2_SMEM; c.attrs = pdl; c.numAttrs = 1;
  cudaLaunchKernelEx(&c, k2_attn, 0x1F801F80u, 0xFFFFFFFFu);
  c.gridDim = dim3(128); c.blockDim = dim3(256); c.dynamicSmemBytes = K3_SMEM;
  cudaLaunchKernelEx(&c, k3_out, mout);
}
```

```cpp
#include <cuda_runtime.h>
#include <cuda_bf16.h>
#include <cuda.h>
#include <stdint.h>

namespace {

constexpr int SEQ = 2048, DM = 640, NH = 32;
constexpr int IMG_HEAD = SEQ * 48;
#define POLY_MASK 0x76DDu
constexpr float LOG2E = 1.4426950408889634f;
constexpr float QSCALE = 0.22360679774997896f * 1.4426950408889634f;
constexpr uint32_t BF_ONE = 0x3F80u;
constexpr uint32_t BF_MAGIC = 0x43E0u;
constexpr uint32_t BF_MU_HI = 0x4025u;
constexpr uint32_t BF_MU_LO = 0x3B8Bu;
constexpr float FAST_BOUND = 40.0f;

__device__ __align__(1024) uint8_t g_QKVB[3 * NH * IMG_HEAD];
__device__ __align__(1024) uint4 g_PHIQ[NH * 32 * 3 * 128];
__device__ __align__(1024) float4 g_KVP[NH * 16 * 288];
__device__ __align__(1024) uint8_t g_KVB[NH * 2304];
__device__ __align__(128) uint32_t g_KVFLAG[32];
__device__ __align__(1024) float g_KMAX[NH * 128];
__device__ __align__(1024) float2 g_GATE[SEQ];
__device__ __align__(1024) uint8_t g_OAB[16 * 20 * 16384];
__device__ __align__(1024) uint8_t g_WOI[8 * 20 * 10240];

#define PROF(cond, k, slot)
__device__ __forceinline__ uint32_t smem_u32(const void* p) { return (uint32_t)__cvta_generic_to_shared(p); }
__device__ __forceinline__ void mbar_init(uint32_t a, uint32_t c) { asm volatile("mbarrier.init.shared::cta.b64 [%0], %1;" ::"r"(a), "r"(c) : "memory"); }
__device__ __forceinline__ void mbar_expect(uint32_t a, uint32_t b) { asm volatile("mbarrier.arrive.expect_tx.shared::cta.b64 _, [%0], %1;" ::"r"(a), "r"(b) : "memory"); }
__device__ __forceinline__ void mbar_arrive(uint32_t a) { asm volatile("mbarrier.arrive.shared::cta.b64 _, [%0];" ::"r"(a) : "memory"); }
__device__ __forceinline__ void mbar_wait(uint32_t a, uint32_t ph) {
  asm volatile(
      "{\n.reg .pred p;\n.reg .u32 n;\nmov.u32 n, 0;\n"
      "W_%=:\nmbarrier.try_wait.parity.shared::cta.b64 p, [%0], %1;\n@p bra D_%=;\n"
      "add.u32 n, n, 1;\nsetp.lt.u32 p, n, 4000000;\n@p bra W_%=;\ntrap;\nD_%=:\n}\n" ::"r"(a), "r"(ph) : "memory");
}
__device__ __forceinline__ void mbar_wait_u(uint32_t a, uint32_t ph) {
#pragma unroll 1
  for (int n = 0;; n++) {
    uint32_t ok;
    asm volatile("{\n.reg .pred p;\nmbarrier.try_wait.parity.shared::cta.b64 p, [%1], %2;\nselp.u32 %0, 1, 0, p;\n}\n" : "=r"(ok) : "r"(a), "r"(ph) : "memory");
    if (__all_sync(~0u, ok)) break;
    if (n > 4000000) __trap();
  }
}
__device__ __forceinline__ void tma2(uint32_t dst, const CUtensorMap* m, int c0, int c1, uint32_t bar) {
  asm volatile("cp.async.bulk.tensor.2d.shared::cluster.global.mbarrier::complete_tx::bytes [%0], [%1, {%3,%4}], [%2];" ::"r"(dst), "l"(m), "r"(bar), "r"(c0), "r"(c1) : "memory");
}
__device__ __forceinline__ void tma3(uint32_t dst, const CUtensorMap* m, int c0, int c1, int c2, uint32_t bar) {
  asm volatile("cp.async.bulk.tensor.3d.shared::cluster.global.mbarrier::complete_tx::bytes [%0], [%1, {%3,%4,%5}], [%2];" ::"r"(dst), "l"(m), "r"(bar), "r"(c0), "r"(c1), "r"(c2) : "memory");
}
__device__ __forceinline__ void bulk_g2s(uint32_t dst, const void* src, uint32_t bytes, uint32_t bar) {
  asm volatile("cp.async.bulk.shared::cluster.global.mbarrier::complete_tx::bytes [%0], [%1], %2, [%3];" ::"r"(dst), "l"(src), "r"(bytes), "r"(bar) : "memory");
}
__device__ __forceinline__ void prefetch_l2(const void* src, uint32_t bytes) { asm volatile("cp.async.bulk.prefetch.L2.global [%0], %1;" ::"l"(src), "r"(bytes) : "memory"); }
__device__ __forceinline__ void fence_async_smem() { asm volatile("fence.proxy.async.shared::cta;" ::: "memory"); }
__device__ __forceinline__ void fence_async_all() { asm volatile("fence.proxy.async;" ::: "memory"); }
__device__ __forceinline__ void bar_sync(int id, int n) { asm volatile("bar.sync %0, %1;" ::"r"(id), "r"(n) : "memory"); }
__device__ __forceinline__ void bar_arrive(int id, int n) { asm volatile("bar.arrive %0, %1;" ::"r"(id), "r"(n) : "memory"); }
__device__ __forceinline__ void pdl_wait() { asm volatile("griddepcontrol.wait;" ::: "memory"); }
__device__ __forceinline__ void pdl_launch() { asm volatile("griddepcontrol.launch_dependents;" ::: "memory"); }
__device__ __forceinline__ void wg_fence() { asm volatile("wgmma.fence.sync.aligned;" ::: "memory"); }
__device__ __forceinline__ void wg_commit() { asm volatile("wgmma.commit_group.sync.aligned;" ::: "memory"); }
template <int N> __device__ __forceinline__ void wg_wait() { asm volatile("wgmma.wait_group.sync.aligned %0;" ::"n"(N) : "memory"); }
template <int N> __device__ __forceinline__ void reg_inc() { asm volatile("setmaxnreg.inc.sync.aligned.u32 %0;" ::"n"(N)); }
template <int N> __device__ __forceinline__ void reg_dec() { asm volatile("setmaxnreg.dec.sync.aligned.u32 %0;" ::"n"(N)); }
template <int N> __device__ __forceinline__ void pin(float (&r)[N]) {
#pragma unroll
  for (int i = 0; i < N; i++) asm volatile("" : "+f"(r[i])::"memory");
}
template <int N> __device__ __forceinline__ void pin(uint32_t (&r)[N]) {
#pragma unroll
  for (int i = 0; i < N; i++) asm volatile("" : "+r"(r[i])::"memory");
}
__device__ __forceinline__ uint64_t mkdesc(uint32_t addr, uint32_t lbo, uint32_t sbo, uint32_t swz) {
  return (uint64_t)((addr & 0x3FFFF) >> 4) | ((uint64_t)(lbo >> 4) << 16) | ((uint64_t)(sbo >> 4) << 32) | ((uint64_t)swz << 62);
}
__device__ __forceinline__ float ex2(float x) { float y; asm("ex2.approx.ftz.f32 %0, %1;" : "=f"(y) : "f"(x)); return y; }
__device__ __forceinline__ float rcp(float x) { float y; asm("rcp.approx.ftz.f32 %0, %1;" : "=f"(y) : "f"(x)); return y; }
__device__ __forceinline__ float sqrt_ap(float x) { float y; asm("sqrt.approx.f32 %0, %1;" : "=f"(y) : "f"(x)); return y; }
__device__ __forceinline__ uint32_t packbf(float lo, float hi) { uint32_t d; asm("cvt.rn.bf16x2.f32 %0, %1, %2;" : "=r"(d) : "f"(hi), "f"(lo)); return d; }
__device__ __forceinline__ float bf_lo(uint32_t v) { return __uint_as_float(v << 16); }
__device__ __forceinline__ float bf_hi(uint32_t v) { return __uint_as_float(v & 0xFFFF0000u); }
__device__ __forceinline__ float bf_round(float x) { return bf_lo(packbf(x, 0.f)); }
__device__ __forceinline__ uint32_t ldg_cg(const void* p) { uint32_t v; asm volatile("ld.global.cg.b32 %0, [%1];" : "=r"(v) : "l"(p) : "memory"); return v; }
__device__ __forceinline__ uint4 ldg_cg4(const void* p) { uint4 v; asm volatile("ld.global.cg.v4.b32 {%0,%1,%2,%3}, [%4];" : "=r"(v.x), "=r"(v.y), "=r"(v.z), "=r"(v.w) : "l"(p) : "memory"); return v; }
__device__ __forceinline__ void sts32(uint32_t a, uint32_t v) { asm volatile("st.shared.b32 [%0], %1;" ::"r"(a), "r"(v) : "memory"); }
__device__ __forceinline__ void stsm4(uint32_t a, uint32_t r0, uint32_t r1, uint32_t r2, uint32_t r3) {
  asm volatile("stmatrix.sync.aligned.m8n8.x4.shared.b16 [%0], {%1,%2,%3,%4};" ::"r"(a), "r"(r0), "r"(r1), "r"(r2), "r"(r3) : "memory");
}

__device__ __forceinline__ void ldsm4(uint32_t (&r)[4], uint32_t a) {
  asm volatile("ldmatrix.sync.aligned.m8n8.x4.shared.b16 {%0,%1,%2,%3}, [%4];" : "=r"(r[0]), "=r"(r[1]), "=r"(r[2]), "=r"(r[3]) : "r"(a) : "memory");
}
__device__ __forceinline__ void bulk_s2g(void* dst, uint32_t src, uint32_t bytes) {
  asm volatile("cp.async.bulk.global.shared::cta.bulk_group [%0], [%1], %2;" ::"l"(dst), "r"(src), "r"(bytes) : "memory");
}

__device__ __forceinline__ void mma_n24_ss_tb(float (&d)[12], uint64_t adesc, uint64_t bdesc, int acc) {
  asm volatile("{\n.reg .pred p;\nsetp.ne.b32 p, %14, 0;\n"
      "wgmma.mma_async.sync.aligned.m64n24k16.f32.bf16.bf16 "
      "{%0,%1,%2,%3,%4,%5,%6,%7,%8,%9,%10,%11}, "
      "%12, %13, p, 1, 1, 0, 1;\n}\n"
      : "+f"(d[0]), "+f"(d[1]), "+f"(d[2]), "+f"(d[3]), "+f"(d[4]), "+f"(d[5]), "+f"(d[6]), "+f"(d[7]),
        "+f"(d[8]), "+f"(d[9]), "+f"(d[10]), "+f"(d[11])
      : "l"(adesc), "l"(bdesc), "r"(acc));
}
__device__ __forceinline__ void mma_n192_rs_tb(float (&d)[96], uint32_t a0, uint32_t a1, uint32_t a2, uint32_t a3, uint64_t bdesc, int acc) {
  asm volatile("{\n.reg .pred p;\nsetp.ne.b32 p, %101, 0;\n"
      "wgmma.mma_async.sync.aligned.m64n192k16.f32.bf16.bf16 "
      "{%0,%1,%2,%3,%4,%5,%6,%7,%8,%9,%10,%11,%12,%13,%14,%15,"
      "%16,%17,%18,%19,%20,%21,%22,%23,%24,%25,%26,%27,%28,%29,%30,%31,"
      "%32,%33,%34,%35,%36,%37,%38,%39,%40,%41,%42,%43,%44,%45,%46,%47,"
      "%48,%49,%50,%51,%52,%53,%54,%55,%56,%57,%58,%59,%60,%61,%62,%63,"
      "%64,%65,%66,%67,%68,%69,%70,%71,%72,%73,%74,%75,%76,%77,%78,%79,"
      "%80,%81,%82,%83,%84,%85,%86,%87,%88,%89,%90,%91,%92,%93,%94,%95}, "
      "{%96,%97,%98,%99}, %100, p, 1, 1, 1;\n}\n"
      : "+f"(d[0]), "+f"(d[1]), "+f"(d[2]), "+f"(d[3]), "+f"(d[4]), "+f"(d[5]), "+f"(d[6]), "+f"(d[7]),
        "+f"(d[8]), "+f"(d[9]), "+f"(d[10]), "+f"(d[11]), "+f"(d[12]), "+f"(d[13]), "+f"(d[14]), "+f"(d[15]),
        "+f"(d[16]), "+f"(d[17]), "+f"(d[18]), "+f"(d[19]), "+f"(d[20]), "+f"(d[21]), "+f"(d[22]), "+f"(d[23]),
        "+f"(d[24]), "+f"(d[25]), "+f"(d[26]), "+f"(d[27]), "+f"(d[28]), "+f"(d[29]), "+f"(d[30]), "+f"(d[31]),
        "+f"(d[32]), "+f"(d[33]), "+f"(d[34]), "+f"(d[35]), "+f"(d[36]), "+f"(d[37]), "+f"(d[38]), "+f"(d[39]),
        "+f"(d[40]), "+f"(d[41]), "+f"(d[42]), "+f"(d[43]), "+f"(d[44]), "+f"(d[45]), "+f"(d[46]), "+f"(d[47]),
        "+f"(d[48]), "+f"(d[49]), "+f"(d[50]), "+f"(d[51]), "+f"(d[52]), "+f"(d[53]), "+f"(d[54]), "+f"(d[55]),
        "+f"(d[56]), "+f"(d[57]), "+f"(d[58]), "+f"(d[59]), "+f"(d[60]), "+f"(d[61]), "+f"(d[62]), "+f"(d[63]),
        "+f"(d[64]), "+f"(d[65]), "+f"(d[66]), "+f"(d[67]), "+f"(d[68]), "+f"(d[69]), "+f"(d[70]), "+f"(d[71]),
        "+f"(d[72]), "+f"(d[73]), "+f"(d[74]), "+f"(d[75]), "+f"(d[76]), "+f"(d[77]), "+f"(d[78]), "+f"(d[79]),
        "+f"(d[80]), "+f"(d[81]), "+f"(d[82]), "+f"(d[83]), "+f"(d[84]), "+f"(d[85]), "+f"(d[86]), "+f"(d[87]),
        "+f"(d[88]), "+f"(d[89]), "+f"(d[90]), "+f"(d[91]), "+f"(d[92]), "+f"(d[93]), "+f"(d[94]), "+f"(d[95])
      : "r"(a0), "r"(a1), "r"(a2), "r"(a3), "l"(bdesc), "r"(acc));
}
__device__ __forceinline__ void mma_n48_rs_tb(float (&d)[24], uint32_t a0, uint32_t a1, uint32_t a2, uint32_t a3, uint64_t bdesc, int acc) {
  asm volatile("{\n.reg .pred p;\nsetp.ne.b32 p, %29, 0;\n"
      "wgmma.mma_async.sync.aligned.m64n48k16.f32.bf16.bf16 "
      "{%0,%1,%2,%3,%4,%5,%6,%7,%8,%9,%10,%11,%12,%13,%14,%15,"
      "%16,%17,%18,%19,%20,%21,%22,%23}, "
      "{%24,%25,%26,%27}, %28, p, 1, 1, 1;\n}\n"
      : "+f"(d[0]), "+f"(d[1]), "+f"(d[2]), "+f"(d[3]), "+f"(d[4]), "+f"(d[5]), "+f"(d[6]), "+f"(d[7]),
        "+f"(d[8]), "+f"(d[9]), "+f"(d[10]), "+f"(d[11]), "+f"(d[12]), "+f"(d[13]), "+f"(d[14]), "+f"(d[15]),
        "+f"(d[16]), "+f"(d[17]), "+f"(d[18]), "+f"(d[19]), "+f"(d[20]), "+f"(d[21]), "+f"(d[22]), "+f"(d[23])
      : "r"(a0), "r"(a1), "r"(a2), "r"(a3), "l"(bdesc), "r"(acc));
}
__device__ __forceinline__ void mma_n128_ss(float (&d)[64], uint64_t adesc, uint64_t bdesc, int acc) {
  asm volatile("{\n.reg .pred p;\nsetp.ne.b32 p, %66, 0;\n"
      "wgmma.mma_async.sync.aligned.m64n128k16.f32.bf16.bf16 "
      "{%0,%1,%2,%3,%4,%5,%6,%7,%8,%9,%10,%11,%12,%13,%14,%15,"
      "%16,%17,%18,%19,%20,%21,%22,%23,%24,%25,%26,%27,%28,%29,%30,%31,"
      "%32,%33,%34,%35,%36,%37,%38,%39,%40,%41,%42,%43,%44,%45,%46,%47,"
      "%48,%49,%50,%51,%52,%53,%54,%55,%56,%57,%58,%59,%60,%61,%62,%63}, "
      "%64, %65, p, 1, 1, 0, 0;\n}\n"
      : "+f"(d[0]), "+f"(d[1]), "+f"(d[2]), "+f"(d[3]), "+f"(d[4]), "+f"(d[5]), "+f"(d[6]), "+f"(d[7]),
        "+f"(d[8]), "+f"(d[9]), "+f"(d[10]), "+f"(d[11]), "+f"(d[12]), "+f"(d[13]), "+f"(d[14]), "+f"(d[15]),
        "+f"(d[16]), "+f"(d[17]), "+f"(d[18]), "+f"(d[19]), "+f"(d[20]), "+f"(d[21]), "+f"(d[22]), "+f"(d[23]),
        "+f"(d[24]), "+f"(d[25]), "+f"(d[26]), "+f"(d[27]), "+f"(d[28]), "+f"(d[29]), "+f"(d[30]), "+f"(d[31]),
        "+f"(d[32]), "+f"(d[33]), "+f"(d[34]), "+f"(d[35]), "+f"(d[36]), "+f"(d[37]), "+f"(d[38]), "+f"(d[39]),
        "+f"(d[40]), "+f"(d[41]), "+f"(d[42]), "+f"(d[43]), "+f"(d[44]), "+f"(d[45]), "+f"(d[46]), "+f"(d[47]),
        "+f"(d[48]), "+f"(d[49]), "+f"(d[50]), "+f"(d[51]), "+f"(d[52]), "+f"(d[53]), "+f"(d[54]), "+f"(d[55]),
        "+f"(d[56]), "+f"(d[57]), "+f"(d[58]), "+f"(d[59]), "+f"(d[60]), "+f"(d[61]), "+f"(d[62]), "+f"(d[63])
      : "l"(adesc), "l"(bdesc), "r"(acc));
}
__device__ __forceinline__ void mma_n160_ss_tb(float (&d)[80], uint64_t adesc, uint64_t bdesc, int acc) {
  asm volatile("{\n.reg .pred p;\nsetp.ne.b32 p, %82, 0;\n"
      "wgmma.mma_async.sync.aligned.m64n160k16.f32.bf16.bf16 "
      "{%0,%1,%2,%3,%4,%5,%6,%7,%8,%9,%10,%11,%12,%13,%14,%15,"
      "%16,%17,%18,%19,%20,%21,%22,%23,%24,%25,%26,%27,%28,%29,%30,%31,"
      "%32,%33,%34,%35,%36,%37,%38,%39,%40,%41,%42,%43,%44,%45,%46,%47,"
      "%48,%49,%50,%51,%52,%53,%54,%55,%56,%57,%58,%59,%60,%61,%62,%63,"
      "%64,%65,%66,%67,%68,%69,%70,%71,%72,%73,%74,%75,%76,%77,%78,%79}, "
      "%80, %81, p, 1, 1, 0, 1;\n}\n"
      : "+f"(d[0]), "+f"(d[1]), "+f"(d[2]), "+f"(d[3]), "+f"(d[4]), "+f"(d[5]), "+f"(d[6]), "+f"(d[7]),
        "+f"(d[8]), "+f"(d[9]), "+f"(d[10]), "+f"(d[11]), "+f"(d[12]), "+f"(d[13]), "+f"(d[14]), "+f"(d[15]),
        "+f"(d[16]), "+f"(d[17]), "+f"(d[18]), "+f"(d[19]), "+f"(d[20]), "+f"(d[21]), "+f"(d[22]), "+f"(d[23]),
        "+f"(d[24]), "+f"(d[25]), "+f"(d[26]), "+f"(d[27]), "+f"(d[28]), "+f"(d[29]), "+f"(d[30]), "+f"(d[31]),
        "+f"(d[32]), "+f"(d[33]), "+f"(d[34]), "+f"(d[35]), "+f"(d[36]), "+f"(d[37]), "+f"(d[38]), "+f"(d[39]),
        "+f"(d[40]), "+f"(d[41]), "+f"(d[42]), "+f"(d[43]), "+f"(d[44]), "+f"(d[45]), "+f"(d[46]), "+f"(d[47]),
        "+f"(d[48]), "+f"(d[49]), "+f"(d[50]), "+f"(d[51]), "+f"(d[52]), "+f"(d[53]), "+f"(d[54]), "+f"(d[55]),
        "+f"(d[56]), "+f"(d[57]), "+f"(d[58]), "+f"(d[59]), "+f"(d[60]), "+f"(d[61]), "+f"(d[62]), "+f"(d[63]),
        "+f"(d[64]), "+f"(d[65]), "+f"(d[66]), "+f"(d[67]), "+f"(d[68]), "+f"(d[69]), "+f"(d[70]), "+f"(d[71]),
        "+f"(d[72]), "+f"(d[73]), "+f"(d[74]), "+f"(d[75]), "+f"(d[76]), "+f"(d[77]), "+f"(d[78]), "+f"(d[79])
      : "l"(adesc), "l"(bdesc), "r"(acc));
}
__device__ __forceinline__ void mma_n24_rs_tb(float (&d)[12], uint32_t a0, uint32_t a1, uint32_t a2, uint32_t a3, uint64_t bdesc, int acc) {
  asm volatile("{\n.reg .pred p;\nsetp.ne.b32 p, %17, 0;\n"
      "wgmma.mma_async.sync.aligned.m64n24k16.f32.bf16.bf16 "
      "{%0,%1,%2,%3,%4,%5,%6,%7,%8,%9,%10,%11}, "
      "{%12,%13,%14,%15}, %16, p, 1, 1, 1;\n}\n"
      : "+f"(d[0]), "+f"(d[1]), "+f"(d[2]), "+f"(d[3]), "+f"(d[4]), "+f"(d[5]), "+f"(d[6]), "+f"(d[7]),
        "+f"(d[8]), "+f"(d[9]), "+f"(d[10]), "+f"(d[11])
      : "r"(a0), "r"(a1), "r"(a2), "r"(a3), "l"(bdesc), "r"(acc));
}
__device__ __forceinline__ void mma_n24_ss_tatb(float (&d)[12], uint64_t adesc, uint64_t bdesc, int acc) {
  asm volatile("{\n.reg .pred p;\nsetp.ne.b32 p, %14, 0;\n"
      "wgmma.mma_async.sync.aligned.m64n24k16.f32.bf16.bf16 "
      "{%0,%1,%2,%3,%4,%5,%6,%7,%8,%9,%10,%11}, "
      "%12, %13, p, 1, 1, 1, 1;\n}\n"
      : "+f"(d[0]), "+f"(d[1]), "+f"(d[2]), "+f"(d[3]), "+f"(d[4]), "+f"(d[5]), "+f"(d[6]), "+f"(d[7]),
        "+f"(d[8]), "+f"(d[9]), "+f"(d[10]), "+f"(d[11])
      : "l"(adesc), "l"(bdesc), "r"(acc));
}

constexpr int K1_STAGE = 23552;
constexpr int K1_NST = 6;
constexpr int K1_STG = K1_NST * K1_STAGE;
constexpr int K1_WPH = K1_STG + 73728;
constexpr int K1_BAR = K1_WPH + 6144;
constexpr int K1_SMEM = K1_BAR + 128;

template <int SEC, int J, int HF>
__device__ __forceinline__ float2 grp(const float (&a1)[96], const float (&a2)[24]) {
  if constexpr (J < 8) return make_float2(a1[(8 * SEC + J) * 4 + 2 * HF], a1[(8 * SEC + J) * 4 + 2 * HF + 1]);
  else return make_float2(a2[(2 * SEC + J - 8) * 4 + 2 * HF], a2[(2 * SEC + J - 8) * 4 + 2 * HF + 1]);
}
__device__ __forceinline__ float sq2(float2 v) { return fmaf(v.x, v.x, v.y * v.y); }

template <int SEC, int PR, bool NORM>
__device__ __forceinline__ void stage_pair(const float (&a1)[96], const float (&a2)[24], float sc0, float sc1, uint32_t ext0, uint32_t ext1,
                                           uint32_t ad01, uint32_t ad2, int hs, int t, float (&nrm)[4]) {
  const float2 u0 = grp<SEC, 5 * PR, 0>(a1, a2), u1 = grp<SEC, 5 * PR + 1, 0>(a1, a2), u2 = grp<SEC, 5 * PR + 2, 0>(a1, a2),
               u3 = grp<SEC, 5 * PR + 3, 0>(a1, a2), u4 = grp<SEC, 5 * PR + 4, 0>(a1, a2);
  const float2 w0 = grp<SEC, 5 * PR, 1>(a1, a2), w1 = grp<SEC, 5 * PR + 1, 1>(a1, a2), w2 = grp<SEC, 5 * PR + 2, 1>(a1, a2),
               w3 = grp<SEC, 5 * PR + 3, 1>(a1, a2), w4 = grp<SEC, 5 * PR + 4, 1>(a1, a2);
  const uint32_t off = (SEC * 4 + 2 * PR) * hs;
  stsm4(ad01 + off, packbf(u0.x * sc0, u0.y * sc0), packbf(w0.x * sc1, w0.y * sc1), packbf(u1.x * sc0, u1.y * sc0), packbf(w1.x * sc1, w1.y * sc1));
  stsm4(ad01 + off + hs, packbf(u3.x * sc0, u3.y * sc0), packbf(w3.x * sc1, w3.y * sc1), packbf(u4.x * sc0, u4.y * sc0), packbf(w4.x * sc1, w4.y * sc1));
  const uint32_t m0 = packbf(u2.x * sc0, u2.y * sc0), m1 = packbf(w2.x * sc1, w2.y * sc1);
  const bool lo = t < 2;
  stsm4(ad2 + off, lo ? m0 : ext0, lo ? m1 : ext1, lo ? ext0 : m0, lo ? ext1 : m1);
  if (NORM) {
    const float h0 = sq2(u2), h1 = sq2(w2);
    float e0 = sq2(u0) + sq2(u1) + (lo ? h0 : 0.f), e1 = sq2(w0) + sq2(w1) + (lo ? h1 : 0.f);
    float o0 = sq2(u3) + sq2(u4) + (lo ? 0.f : h0), o1 = sq2(w3) + sq2(w4) + (lo ? 0.f : h1);
    e0 += __shfl_xor_sync(~0u, e0, 1); e1 += __shfl_xor_sync(~0u, e1, 1); o0 += __shfl_xor_sync(~0u, o0, 1); o1 += __shfl_xor_sync(~0u, o1, 1);
    e0 += __shfl_xor_sync(~0u, e0, 2); e1 += __shfl_xor_sync(~0u, e1, 2); o0 += __shfl_xor_sync(~0u, o0, 2); o1 += __shfl_xor_sync(~0u, o1, 2);
    nrm[2 * PR] = fmaxf(e0, e1); nrm[2 * PR + 1] = fmaxf(o0, o1);
  }
}

__device__ __forceinline__ void hedgehog(const float (&p)[12], uint32_t (&f)[12], int t) {
#pragma unroll
  for (int hf = 0; hf < 2; hf++) {
    float v[6] = {p[2 * hf], p[2 * hf + 1], p[4 + 2 * hf], p[5 + 2 * hf], p[8 + 2 * hf], p[9 + 2 * hf]};
    float mx = fmaxf(fmaxf(fmaxf(v[0], v[1]), fmaxf(v[2], v[3])), fmaxf(v[4], v[5]));
    float mn = fminf(fminf(fminf(v[0], v[1]), fminf(v[2], v[3])), fminf(v[4], v[5]));
    mx = fmaxf(mx, __shfl_xor_sync(~0u, mx, 1)); mn = fminf(mn, __shfl_xor_sync(~0u, mn, 1));
    mx = fmaxf(mx, __shfl_xor_sync(~0u, mx, 2)); mn = fminf(mn, __shfl_xor_sync(~0u, mn, 2));
    const float bp = -mx * LOG2E, bn = mn * LOG2E;
    float ep[6], en[6];
#pragma unroll
    for (int i = 0; i < 6; i++) { ep[i] = ex2(fmaf(v[i], LOG2E, bp)); en[i] = ex2(fmaf(v[i], -LOG2E, bn)); }
    const float keep = (t < 2) ? 1.f : 0.f;
    float sp = (ep[0] + ep[1]) + (ep[2] + ep[3]) + keep * (ep[4] + ep[5]);
    float sn = (en[0] + en[1]) + (en[2] + en[3]) + keep * (en[4] + en[5]);
    sp += __shfl_xor_sync(~0u, sp, 1); sn += __shfl_xor_sync(~0u, sn, 1);
    sp += __shfl_xor_sync(~0u, sp, 2); sn += __shfl_xor_sync(~0u, sn, 2);
    const float rp = rcp(sp), rn = rcp(sn), rp2 = rp * keep, rn2 = rn * keep;
    f[0 + hf] = packbf(ep[0] * rp, ep[1] * rp);
    f[2 + hf] = packbf(ep[2] * rp, ep[3] * rp);
    f[4 + hf] = packbf(ep[4] * rp2, ep[5] * rp2);
    f[6 + hf] = packbf(en[0] * rn, en[1] * rn);
    f[8 + hf] = packbf(en[2] * rn, en[3] * rn);
    f[10 + hf] = packbf(en[4] * rn2, en[5] * rn2);
  }
}

__device__ __forceinline__ void issue_pq(float (&p0)[12], float (&p1)[12], uint32_t img, uint32_t wph) {
  const uint64_t ad = mkdesc(img, 128, 384, 0), a2 = mkdesc(img + 256, 0, 384, 0), wd = mkdesc(wph, 384, 128, 0);
  wg_fence();
  mma_n24_ss_tb(p0, ad, wd, 0);
  mma_n24_ss_tb(p0, a2, wd + 48, 1);
  mma_n24_ss_tb(p1, ad + 192, wd, 0);
  mma_n24_ss_tb(p1, a2 + 192, wd + 48, 1);
  wg_commit();
}
__device__ __forceinline__ void phi_q_store(const float (&p0)[12], const float (&p1)[12], uint4* dst, int t) {
  uint32_t f[12];
  hedgehog(p0, f, t);
#pragma unroll
  for (int ks = 0; ks < 3; ks++) dst[ks * 128] = make_uint4(f[4 * ks], f[4 * ks + 1], f[4 * ks + 2], f[4 * ks + 3]);
  hedgehog(p1, f, t);
#pragma unroll
  for (int ks = 0; ks < 3; ks++) dst[(3 + ks) * 128] = make_uint4(f[4 * ks], f[4 * ks + 1], f[4 * ks + 2], f[4 * ks + 3]);
}
template <int SEC, int PR>
__device__ __forceinline__ void frag_pair(const float (&a1)[96], const float (&a2)[24], uint32_t (&e)[6], uint32_t (&o)[6], int t) {
  auto pk = [](float2 v) { return packbf(v.x, v.y); };
  e[0] = pk(grp<SEC, 5 * PR, 0>(a1, a2)); e[1] = pk(grp<SEC, 5 * PR, 1>(a1, a2));
  e[2] = pk(grp<SEC, 5 * PR + 1, 0>(a1, a2)); e[3] = pk(grp<SEC, 5 * PR + 1, 1>(a1, a2));
  o[0] = pk(grp<SEC, 5 * PR + 3, 0>(a1, a2)); o[1] = pk(grp<SEC, 5 * PR + 3, 1>(a1, a2));
  o[2] = pk(grp<SEC, 5 * PR + 4, 0>(a1, a2)); o[3] = pk(grp<SEC, 5 * PR + 4, 1>(a1, a2));
  const uint32_t m0 = pk(grp<SEC, 5 * PR + 2, 0>(a1, a2)), m1 = pk(grp<SEC, 5 * PR + 2, 1>(a1, a2));
  e[4] = t < 2 ? m0 : 0u; e[5] = t < 2 ? m1 : 0u;
  o[4] = t < 2 ? 0u : m0; o[5] = t < 2 ? 0u : m1;
}

struct K1Maps { CUtensorMap x, a64_1, a16_1, a64_2, a16_2, b64_1, b16_1, b64_2, b16_2; };

__device__ __forceinline__ void k1_load(const K1Maps& m, int it, uint32_t d, uint32_t b, int mt, int hg) {
  const int k0 = (it % 20) * 32;
  const bool w0 = it < 20;
  mbar_expect(b, K1_STAGE);
  tma2(d, &m.x, k0, mt * 128, b);
  tma3(d + 8192, w0 ? &m.b64_2 : &m.a64_2, hg * 80, k0, 1, b);
  tma3(d + 8192 + 8192, w0 ? &m.a64_1 : &m.b64_1, hg * 80, k0, 0, b);
  tma3(d + 20480, w0 ? &m.b16_2 : &m.a16_2, hg * 80 + 64, k0, 1, b);
  tma3(d + 20480 + 2048, w0 ? &m.a16_1 : &m.b16_1, hg * 80 + 64, k0, 0, b);
}

__global__ void __launch_bounds__(512, 1)
k1_qkv(const __grid_constant__ K1Maps maps,
       const __nv_bfloat16* __restrict__ x, const __nv_bfloat16* __restrict__ wphi, const __nv_bfloat16* __restrict__ gate_w,
       const uint8_t* __restrict__ wa, const uint8_t* __restrict__ wb, const uint8_t* __restrict__ woa, const uint8_t* __restrict__ wob) {
  extern __shared__ __align__(1024) uint8_t smem[];
  const uint32_t sb = smem_u32(smem);
  const uint32_t full = sb + K1_BAR, empty = full + 8 * K1_NST;
  const int warp = __shfl_sync(~0u, threadIdx.x >> 5, 0), lane = threadIdx.x & 31, wg = warp >> 2;
  const int bid = blockIdx.x;
  const int mt = (bid & 3) + 4 * (bid >> 5), hg = (bid >> 2) & 7;
  PROF(threadIdx.x == 0, 0, 0);
  if (threadIdx.x == 384) {
    for (int i = 0; i < K1_NST; i++) { mbar_init(full + 8 * i, 1); mbar_init(empty + 8 * i, 2); }
    asm volatile("fence.mbarrier_init.release.cluster;" ::: "memory");
    for (int it = 0; it < K1_NST; it++) k1_load(maps, it, sb + it * K1_STAGE, full + 8 * it, mt, hg);
    pdl_launch();
  }
  __syncthreads();

  if (wg == 3) {
    reg_dec<40>();
    if (warp == 12) {
      if (lane == 0) {
        for (int it = K1_NST; it < 40; it++) {
          const int s = it % K1_NST;
          mbar_wait(empty + 8 * s, ((it / K1_NST) - 1) & 1);
          k1_load(maps, it, sb + s * K1_STAGE, full + 8 * s, mt, hg);
        }
      }
    } else {
      if (bid == 0 && warp == 14) g_KVFLAG[lane] = 0;
      mbar_wait(full, 0);
      if (warp == 13 && lane == 0) { prefetch_l2(wa + (size_t)bid * 19200, 19200); prefetch_l2(wb + (size_t)bid * 19200, 19200); }
      uint2 gw[5];
#pragma unroll
      for (int i = 0; i < 5; i++) gw[i] = *(const uint2*)(gate_w + i * 128 + lane * 4);
      for (int r = warp - 13; r < 16; r += 3) {
        const int row = mt * 128 + hg * 16 + r;
        float acc = 0.f;
#pragma unroll
        for (int i = 0; i < 5; i++) {
          const uint2 xv = *(const uint2*)(x + (size_t)row * DM + i * 128 + lane * 4);
          uint32_t p0, p1;
          asm("mul.rn.bf16x2 %0, %1, %2;" : "=r"(p0) : "r"(xv.x), "r"(gw[i].x));
          asm("mul.rn.bf16x2 %0, %1, %2;" : "=r"(p1) : "r"(xv.y), "r"(gw[i].y));
          acc += (bf_lo(p0) + bf_hi(p0)) + (bf_lo(p1) + bf_hi(p1));
        }
#pragma unroll
        for (int o = 16; o; o >>= 1) acc += __shfl_xor_sync(~0u, acc, o);
        if (lane == 0) {
          const float g = bf_round(__fdividef(1.f, 1.f + __expf(-bf_round(acc))));
          g_GATE[row] = make_float2(g, bf_round(1.f - g));
        }
      }
      for (int kg = bid; kg < 160; kg += 128) {
        const uint8_t* src = kg < 80 ? woa + (size_t)kg * 10240 : wob + (size_t)(kg - 80) * 10240;
        for (int e = (warp - 13) * 32 + lane; e < 640; e += 96) {
          const int nt = e / 160, r = e % 160;
          *(uint4*)(g_WOI + (size_t)nt * 409600 + kg * 2560 + r * 16) = __ldg((const uint4*)(src + (r & 7) * 1280 + (nt * 20 + (r >> 3)) * 16));
        }
      }
    }
  } else if (wg == 2) {
    reg_dec<112>();
    const int tid = threadIdx.x - 256, t = lane & 3;
    for (int e = tid; e < 4 * 768; e += 128) {
      const int i = e / 768, r = e % 768, kg = r / 192, nc = (r % 192) / 64, kr = (r % 64) / 8, ne = r % 8;
      const int slot = kg * 8 + kr, n = nc * 8 + ne;
      int d = -1;
      if (i & 1) { if (slot < 16) d = slot + 4; else if (slot >= 20 && slot < 24) d = slot - 20; }
      else if (slot < 20) d = slot;
      const int f = n < 20 ? n : n - 4;
      const unsigned short val = d >= 0 ? *(const unsigned short*)(wphi + ((size_t)(hg * 4 + i) * 20 + d) * 20 + f) : (unsigned short)0;
      *(unsigned short*)(smem + K1_WPH + e * 2) = val;
    }
    fence_async_smem();
    bar_sync(1, 384);
    const uint32_t stg = sb + K1_STG, wph = sb + K1_WPH;
    if (tid < 8) {
      bulk_s2g(g_QKVB + (size_t)((1 + (tid >> 2)) * NH + hg * 4 + (tid & 3)) * IMG_HEAD + (size_t)mt * 6144, stg + tid * 6144, 6144);
      asm volatile("cp.async.bulk.commit_group;" ::: "memory");
    }
    float pa0[12], pa1[12], pb0[12], pb1[12];
    issue_pq(pa0, pa1, stg + 8 * 6144, wph);
    wg_wait<0>();
    pin(pa0); pin(pa1);
#pragma unroll 1
    for (int i = 0; i < 4; i += 2) {
      uint4* dst = g_PHIQ + ((size_t)((hg * 4 + i) * 32 + mt * 2) * 3) * 128 + tid;
      issue_pq(pb0, pb1, stg + (9 + i) * 6144, wph + (i + 1) * 1536);
      phi_q_store(pa0, pa1, dst, t);
      wg_wait<0>();
      pin(pb0); pin(pb1);
      issue_pq(pa0, pa1, stg + (8 + ((i + 2) & 3)) * 6144, wph + ((i + 2) & 3) * 1536);
      phi_q_store(pb0, pb1, dst + 32 * 3 * 128, t);
      wg_wait<0>();
      pin(pa0); pin(pa1);
    }
    if (tid < 8) asm volatile("cp.async.bulk.wait_group 0;" ::: "memory");
    bar_arrive(2, 384);
    PROF(tid == 0, 0, 6);
  } else {
    reg_inc<176>();
    const int w4 = warp & 3, t = lane & 3;
    const uint32_t arow = wg * 4096 + (w4 * 16 + (lane & 15)) * 64, asw = (lane >> 1) & 3, ahi = lane >> 4;
    const int rg = wg * 8 + w4 * 2, mi = lane >> 3;
    const uint32_t stg = sb + K1_STG;
    const uint32_t sbase = stg + (rg + (mi & 1)) * 384 + (lane & 7) * 16;
    const uint32_t ad01 = sbase + (mi >> 1) * 128, ad2 = sbase + (mi >> 1) * 6144 + 256;
    float a1[96], a2[24];
    float nrm[4];
#pragma unroll 1
    for (int tile = 0; tile < 2; tile++) {
#pragma unroll 1
      for (int ks = 0; ks < 20; ks += 2) {
        uint32_t fa[2][4], fb[2][4];
#pragma unroll
        for (int u = 0; u < 2; u++) {
          const int it = tile * 20 + ks + u, s = it % K1_NST;
          mbar_wait(full + 8 * s, (it / K1_NST) & 1);
          PROF(threadIdx.x == 0 && it == 0, 0, 1);
          const uint32_t st = sb + s * K1_STAGE;
          uint32_t(&f)[2][4] = u ? fb : fa;
          ldsm4(f[0], st + arow + ((ahi ^ asw) << 4));
          ldsm4(f[1], st + arow + (((2 + ahi) ^ asw) << 4));
          const uint64_t b1 = mkdesc(st + 8192, 4096, 1024, 1);
          const uint64_t b2 = mkdesc(st + 20480, 1024, 256, 3);
          wg_fence();
#pragma unroll
          for (int kk = 0; kk < 2; kk++) {
            mma_n192_rs_tb(a1, f[kk][0], f[kk][1], f[kk][2], f[kk][3], b1 + kk * 128, ks | u | kk);
            mma_n48_rs_tb(a2, f[kk][0], f[kk][1], f[kk][2], f[kk][3], b2 + kk * 32, ks | u | kk);
          }
          wg_commit();
          wg_wait<1>();
          if ((ks | u) && (threadIdx.x & 127) == 0) mbar_arrive(empty + 8 * ((it - 1) % K1_NST));
        }
      }
      wg_wait<0>();
      pin(a1); pin(a2);
      PROF(threadIdx.x == 0, 0, 2 + 2 * tile);
      if ((threadIdx.x & 127) == 0) mbar_arrive(empty + 8 * ((tile * 20 + 19) % K1_NST));
      if (tile == 0) {
        const bool p0 = (POLY_MASK >> rg) & 1, p1 = (POLY_MASK >> (rg + 1)) & 1;
        const uint32_t kp = (t & 1) ? 0u : (BF_ONE | (BF_MAGIC << 16)), km = (t & 1) ? BF_MU_LO : (BF_ONE | (BF_MU_HI << 16));
        const uint32_t vp = (t & 1) ? 0u : (BF_ONE | 0x8000u), vm = (t & 1) ? 0u : BF_ONE;
        stage_pair<0, 0, true>(a1, a2, 1.f, 1.f, p0 ? kp : km, p1 ? kp : km, ad01, ad2, 6144, t, nrm);
        stage_pair<0, 1, true>(a1, a2, 1.f, 1.f, p0 ? kp : km, p1 ? kp : km, ad01, ad2, 6144, t, nrm);
        stage_pair<1, 0, false>(a1, a2, p0 ? -1.f : 1.f, p1 ? -1.f : 1.f, p0 ? vp : vm, p1 ? vp : vm, ad01, ad2, 6144, t, nrm);
        stage_pair<1, 1, false>(a1, a2, p0 ? -1.f : 1.f, p1 ? -1.f : 1.f, p0 ? vp : vm, p1 ? vp : vm, ad01, ad2, 6144, t, nrm);
        stage_pair<2, 0, false>(a1, a2, 1.f, 1.f, 0u, 0u, ad01, ad2, 6144, t, nrm);
        stage_pair<2, 1, false>(a1, a2, 1.f, 1.f, 0u, 0u, ad01, ad2, 6144, t, nrm);
        fence_async_smem();
        bar_arrive(1, 384);
#pragma unroll
        for (int i = 0; i < 4; i++) {
          const uint32_t m = __reduce_max_sync(~0u, __float_as_uint(nrm[i]));
          if (lane == i) g_KMAX[(hg * 4 + i) * 128 + mt * 8 + wg * 4 + w4] = __uint_as_float(m);
        }
        PROF(threadIdx.x == 0, 0, 3);
      }
    }
    bar_sync(2, 384);
    const uint32_t one = (t & 1) ? 0u : BF_ONE;
    stage_pair<2, 0, false>(a1, a2, QSCALE, QSCALE, 0u, 0u, ad01, ad2, 6144, t, nrm);
    stage_pair<2, 1, false>(a1, a2, QSCALE, QSCALE, 0u, 0u, ad01, ad2, 6144, t, nrm);
    fence_async_smem();
    bar_sync(3 + wg, 128);
    if (w4 == 0 && lane < 4) {
      bulk_s2g(g_QKVB + (size_t)(hg * 4 + lane) * IMG_HEAD + (size_t)(mt * 2 + wg) * 3072, stg + (8 + lane) * 6144 + wg * 3072, 3072);
      asm volatile("cp.async.bulk.commit_group;" ::: "memory");
    }
    stage_pair<1, 0, false>(a1, a2, 1.f, 1.f, one, one, ad01, ad2, 6144, t, nrm);
    stage_pair<1, 1, false>(a1, a2, 1.f, 1.f, one, one, ad01, ad2, 6144, t, nrm);
    uint32_t fk[4][6];
    frag_pair<0, 0>(a1, a2, fk[0], fk[1], t);
    frag_pair<0, 1>(a1, a2, fk[2], fk[3], t);
    float pk[4][12];
    wg_fence();
#pragma unroll
    for (int i = 0; i < 4; i++) {
      const uint64_t wd = mkdesc(sb + K1_WPH + i * 1536, 384, 128, 0);
      mma_n24_rs_tb(pk[i], fk[i][0], fk[i][1], fk[i][2], fk[i][3], wd, 0);
      mma_n24_rs_tb(pk[i], fk[i][4], fk[i][5], 0u, 0u, wd + 48, 1);
    }
    wg_commit();
    mbar_wait(empty + 8 * (38 % K1_NST), (38 / K1_NST) & 1);
    wg_wait<0>();
    const uint32_t pka = sb + (rg + ((lane >> 3) & 1)) * 768 + (lane >> 4) * 128 + (lane & 7) * 16;
#pragma unroll
    for (int i = 0; i < 4; i++) {
      pin(pk[i]);
      uint32_t f[12];
      hedgehog(pk[i], f, t);
#pragma unroll
      for (int ks = 0; ks < 3; ks++) stsm4(pka + i * 12288 + ks * 256, f[4 * ks], f[4 * ks + 1], f[4 * ks + 2], f[4 * ks + 3]);
    }
    fence_async_smem();
    bar_sync(5, 256);
    float kv[2][12];
    wg_fence();
#pragma unroll
    for (int j = 0; j < 2; j++) {
      const uint64_t ad = mkdesc(sb + (wg * 2 + j) * 12288, 768, 128, 0), vd = mkdesc(stg + (4 + wg * 2 + j) * 6144, 384, 128, 0);
#pragma unroll
      for (int ks = 0; ks < 8; ks++) mma_n24_ss_tatb(kv[j], ad + ks * 96, vd + ks * 48, ks);
    }
    wg_commit();
    wg_wait<0>();
    if (w4 < 3) {
#pragma unroll
      for (int j = 0; j < 2; j++) {
        pin(kv[j]);
        float4* dst = g_KVP + (size_t)((hg * 4 + wg * 2 + j) * 16 + mt) * 288 + w4 * 96 + lane;
        dst[0] = make_float4(kv[j][0], kv[j][1], kv[j][2], kv[j][3]);
        dst[32] = make_float4(kv[j][4], kv[j][5], kv[j][6], kv[j][7]);
        dst[64] = make_float4(kv[j][8], kv[j][9], kv[j][10], kv[j][11]);
      }
    }
    if (w4 == 0 && lane < 4) asm volatile("cp.async.bulk.wait_group 0;" ::: "memory");
    PROF(threadIdx.x == 0, 0, 5);
  }
}

constexpr int K2_K = 0, K2_V = IMG_HEAD, K2_Q = 2 * IMG_HEAD, K2_KV = K2_Q + 8 * 3072, K2_BAR = K2_KV + 2 * 2304, K2_SMEM = K2_BAR + 128;

__device__ __forceinline__ uint32_t exp2_bits(float y0, float y1, uint32_t cm, uint32_t neg1) {
  uint32_t w, m, r;
  asm("prmt.b32 %0, %1, %2, 0x6521;" : "=r"(w) : "r"(__float_as_uint(y0)), "r"(__float_as_uint(y1)));
  asm("lop3.b32 %0, %1, 0x007F007F, %2, 0xEA;" : "=r"(m) : "r"(w), "r"(cm));
  const uint32_t e = m * neg1 + w;
  asm("fma.rn.bf16x2 %0, %1, %2, %3;" : "=r"(r) : "r"(w), "r"(m), "r"(e));
  return r;
}
__device__ __forceinline__ void exp_tile(const float (&s)[64], uint32_t (&p)[32], uint32_t cm, uint32_t neg1) {
#pragma unroll
  for (int g = 0; g < 16; g++) {
    if ((POLY_MASK >> g) & 1) {
      p[2 * g] = exp2_bits(s[4 * g], s[4 * g + 1], cm, neg1);
      p[2 * g + 1] = exp2_bits(s[4 * g + 2], s[4 * g + 3], cm, neg1);
    } else {
      p[2 * g] = packbf(ex2(s[4 * g]), ex2(s[4 * g + 1]));
      p[2 * g + 1] = packbf(ex2(s[4 * g + 2]), ex2(s[4 * g + 3]));
    }
  }
}
__device__ __forceinline__ void issue_qk(float (&s)[64], uint64_t qd, uint64_t kd) {
  mma_n128_ss(s, qd, kd, 0);
  mma_n128_ss(s, (qd + 16) & ~(0x3FFFull << 16), (kd + 16) & ~(0x3FFFull << 16), 1);
}
__device__ __forceinline__ void issue_pv(float (&o)[12], const uint32_t (&p)[32], uint64_t vd, int acc) {
#pragma unroll
  for (int kk = 0; kk < 8; kk++) mma_n24_rs_tb(o, p[4 * kk], p[4 * kk + 1], p[4 * kk + 2], p[4 * kk + 3], vd + kk * 48, acc | kk);
}
__device__ __forceinline__ void attn_pair(float (&s0)[64], float (&s1)[64], uint32_t (&p0)[32], uint32_t (&p1)[32], float (&o)[12],
                                          uint64_t qd1, uint64_t kd1, uint64_t qd2, uint64_t kd2, uint64_t vd, int acc, uint32_t bar,
                                          uint32_t cm, uint32_t neg1) {
  wg_fence();
  issue_qk(s1, qd1, kd1);
  wg_commit();
  exp_tile(s0, p0, cm, neg1);
  wg_fence();
  issue_pv(o, p0, vd, acc);
  wg_commit();
  wg_wait<1>();
  pin(s1);
  mbar_wait_u(bar, 0);
  wg_fence();
  issue_qk(s0, qd2, kd2);
  wg_commit();
  exp_tile(s1, p1, cm, neg1);
  wg_fence();
  issue_pv(o, p1, vd + 384, 1);
  wg_commit();
}
__device__ __forceinline__ void store_o(const float (&o)[12], int odd, int lane, int m16, int colgrp, float eps, float s0, float s1) {
  const int src = (lane & ~3) | (odd ? 0 : 2);
  const float l0 = __shfl_sync(~0u, o[8], src) + eps, l1 = __shfl_sync(~0u, o[10], src) + eps;
  const float r0 = s0 * rcp(l0), r1 = s1 * rcp(l1);
  const int g0 = colgrp + (odd ? 3 : 0), g1 = g0 + 1, g2 = colgrp + 2;
  uint8_t* base = g_OAB + (size_t)(m16 >> 3) * (20 * 16384) + (m16 & 7) * 2048 + lane * 4;
  uint8_t* c0 = base + (g0 >> 3) * 16384 + (g0 & 7) * 128;
  uint8_t* c1 = base + (g1 >> 3) * 16384 + (g1 & 7) * 128;
  uint8_t* c2 = base + (g2 >> 3) * 16384 + (g2 & 7) * 128;
  *(uint32_t*)c0 = packbf(o[0] * r0, o[1] * r0); *(uint32_t*)(c0 + 1024) = packbf(o[2] * r1, o[3] * r1);
  *(uint32_t*)c1 = packbf(o[4] * r0, o[5] * r0); *(uint32_t*)(c1 + 1024) = packbf(o[6] * r1, o[7] * r1);
  if (((lane & 3) < 2) != (odd != 0)) { *(uint32_t*)c2 = packbf(o[8] * r0, o[9] * r0); *(uint32_t*)(c2 + 1024) = packbf(o[10] * r1, o[11] * r1); }
}

__device__ __forceinline__ void linear_readout(uint32_t kvs, int h, int mt0, int wg, int w4, int lane, int row_g, int colgrp) {
  const int tid = w4 * 32 + lane;
  uint4 f[4][3];
  float g[4][2];
#pragma unroll
  for (int p = 0; p < 4; p++) {
    const uint4* src = g_PHIQ + ((size_t)(h * 32 + mt0 + p) * 3) * 128 + tid;
    f[p][0] = ldg_cg4(src); f[p][1] = ldg_cg4(src + 128); f[p][2] = ldg_cg4(src + 256);
    g[p][0] = g_GATE[row_g + p * 64].x; g[p][1] = g_GATE[row_g + p * 64 + 8].x;
  }
#pragma unroll 1
  for (int n = 0; n < 20000000; n++) {
    uint32_t v;
    asm volatile("ld.acquire.gpu.global.u32 %0, [%1];" : "=r"(v) : "l"(g_KVFLAG + (h >> 3)) : "memory");
    if (__all_sync(~0u, v != 0)) break;
  }
  const uint8_t* kvg = g_KVB + h * 2304;
  const uint4 k0 = ldg_cg4(kvg + tid * 16), k1 = ldg_cg4(kvg + 2048 + (tid & 15) * 16);
  asm volatile("st.shared.v4.b32 [%0], {%1,%2,%3,%4};" ::"r"(kvs + tid * 16), "r"(k0.x), "r"(k0.y), "r"(k0.z), "r"(k0.w) : "memory");
  asm volatile("st.shared.v4.b32 [%0], {%1,%2,%3,%4};" ::"r"(kvs + 2048 + (tid & 15) * 16), "r"(k1.x), "r"(k1.y), "r"(k1.z), "r"(k1.w) : "memory");
  fence_async_smem();
  bar_sync(1 + wg, 128);
  const uint64_t kvd = mkdesc(kvs, 384, 128, 0);
  float oa[4][12];
#pragma unroll
  for (int p = 0; p < 4; p++)
#pragma unroll
    for (int ks = 0; ks < 3; ks++) asm volatile("" : "+r"(f[p][ks].x), "+r"(f[p][ks].y), "+r"(f[p][ks].z), "+r"(f[p][ks].w)::"memory");
  wg_fence();
#pragma unroll
  for (int p = 0; p < 4; p++)
#pragma unroll
    for (int ks = 0; ks < 3; ks++) mma_n24_rs_tb(oa[p], f[p][ks].x, f[p][ks].y, f[p][ks].z, f[p][ks].w, kvd + ks * 48, ks);
  wg_commit();
  wg_wait<0>();
#pragma unroll
  for (int p = 0; p < 4; p++) {
    pin(oa[p]);
    store_o(oa[p], h & 1, lane, (mt0 + p) * 4 + w4, colgrp, 1e-6f, g[p][0], g[p][1]);
  }
}

__global__ void __launch_bounds__(256, 1) k2_attn(uint32_t cm, uint32_t neg1) {
  extern __shared__ __align__(1024) uint8_t smem[];
  const uint32_t sb = smem_u32(smem);
  const int tid = threadIdx.x, lane = tid & 31;
  const int warp = __shfl_sync(~0u, tid >> 5, 0), wg = warp >> 2, w4 = warp & 3, t = lane & 3;
  PROF(tid == 0, 1, 0);
  if (blockIdx.x < 4) {
    pdl_wait();
    if (tid == 0) pdl_launch();
#pragma unroll 1
    for (int e0 = tid; e0 < 8 * 288; e0 += 256) {
      const int h = blockIdx.x * 8 + e0 / 288, e = e0 % 288;
      const float4* src = g_KVP + (size_t)h * 16 * 288 + e;
      uint4 v[16];
#pragma unroll
      for (int m = 0; m < 16; m++) v[m] = ldg_cg4(src + m * 288);
      float4 acc = make_float4(0.f, 0.f, 0.f, 0.f);
#pragma unroll
      for (int m = 0; m < 16; m++) {
        acc.x += __uint_as_float(v[m].x); acc.y += __uint_as_float(v[m].y); acc.z += __uint_as_float(v[m].z); acc.w += __uint_as_float(v[m].w);
      }
      uint8_t* dst = g_KVB + h * 2304 + (e / 96) * 768 + ((e % 96) >> 5) * 128 + (e & 31) * 4;
      *(uint32_t*)dst = packbf(acc.x, acc.y);
      *(uint32_t*)(dst + 384) = packbf(acc.z, acc.w);
    }
    __threadfence();
    __syncthreads();
    if (tid == 0) asm volatile("st.release.gpu.global.u32 [%0], %1;" ::"l"(g_KVFLAG + blockIdx.x), "r"(1u) : "memory");
    PROF(tid == 0, 1, 7);
    return;
  }
  const int cb = blockIdx.x - 4, h = cb >> 2, quarter = cb & 3, odd = h & 1;
  const uint32_t bar = sb + K2_BAR;
  const uint8_t* gq = g_QKVB + (size_t)h * IMG_HEAD;
  const uint8_t* gk = gq + (size_t)NH * IMG_HEAD;
  const uint8_t* gv = gk + (size_t)NH * IMG_HEAD;
  if (tid == 0) {
    for (int i = 0; i < 8; i++) mbar_init(bar + 8 * i, 1);
    asm volatile("fence.mbarrier_init.release.cluster;" ::: "memory");
  }
  pdl_wait();
  PROF(tid == 0, 1, 1);
  if (tid == 0) {
    pdl_launch();
    mbar_expect(bar, 24576);
    bulk_g2s(sb + K2_K, gk, 12288, bar);
    bulk_g2s(sb + K2_V, gv, 12288, bar);
  }
  const int mt0 = quarter * 8 + wg * 4;
  uint32_t q[4][6];
#pragma unroll
  for (int p = 0; p < 4; p++) {
    const uint8_t* src = gq + (size_t)((mt0 + p) * 8 + w4 * 2) * 384 + lane * 4;
#pragma unroll
    for (int c = 0; c < 3; c++) { q[p][2 * c] = ldg_cg(src + c * 128); q[p][2 * c + 1] = ldg_cg(src + 384 + c * 128); }
  }
  const uint4 km4 = ldg_cg4(g_KMAX + h * 128 + lane * 4);
  const float kmax = sqrt_ap(__uint_as_float(__reduce_max_sync(~0u, max(max(km4.x, km4.y), max(km4.z, km4.w))))) * 1.01f;
  if (warp == 0 && lane >= 1 && lane < 8) {
    mbar_expect(bar + 8 * lane, 24576);
    bulk_g2s(sb + K2_K + lane * 12288, gk + lane * 12288, 12288, bar + 8 * lane);
    bulk_g2s(sb + K2_V + lane * 12288, gv + lane * 12288, 12288, bar + 8 * lane);
  }
  const bool is_feat = (t < 2) != (odd != 0);
  float bnd[4][2];
  bool unsafe = false;
#pragma unroll
  for (int p = 0; p < 4; p++)
#pragma unroll
    for (int hf = 0; hf < 2; hf++) {
      float n2 = 0.f;
#pragma unroll
      for (int c = 0; c < 3; c++) { const uint32_t v = q[p][2 * c + hf]; n2 = fmaf(bf_lo(v), bf_lo(v), fmaf(bf_hi(v), bf_hi(v), n2)); }
      n2 += __shfl_xor_sync(~0u, n2, 1);
      n2 += __shfl_xor_sync(~0u, n2, 2);
      bnd[p][hf] = sqrt_ap(n2) * kmax * 1.01f;
      unsafe |= !(bnd[p][hf] <= FAST_BOUND);
    }
  const bool slow = __any_sync(~0u, __syncthreads_or(unsafe));
#pragma unroll
  for (int p = 0; p < 4; p++)
#pragma unroll
    for (int hf = 0; hf < 2; hf++) {
      const uint32_t dst = sb + K2_Q + (wg * 4 + p) * 3072 + (w4 * 2 + hf) * 384 + lane * 4;
      sts32(dst, q[p][hf]);
      sts32(dst + 128, q[p][2 + hf]);
      const uint32_t v = q[p][4 + hf];
      uint32_t c2 = packbf(bf_lo(v) * 0.5f, bf_hi(v) * 0.5f);
      if (!is_feat) c2 = slow ? 0u : ((t & 1) ? 0x3F00u : packbf(-0.5f * bnd[p][hf], 0.5f));
      sts32(dst + 256, c2);
    }
  fence_async_smem();
  bar_sync(1 + wg, 128);
  PROF(tid == 0, 1, 2);
  const int row_g = mt0 * 64 + w4 * 16 + (lane >> 2);
  const int colgrp = (h >> 1) * 5;
  const uint64_t kd0 = mkdesc(sb + K2_K, 128, 384, 0), vd0 = mkdesc(sb + K2_V, 384, 128, 0);
  const uint64_t qd0 = mkdesc(sb + K2_Q + wg * 4 * 3072, 128, 384, 0);
  float o[12], s0[64];
  mbar_wait_u(bar, 0);
  wg_fence();
  issue_qk(s0, qd0, kd0);
  wg_commit();
  wg_wait<0>();
  pin(s0);
#pragma unroll 1
  for (int pass = 0; pass < 4; pass++) {
    const uint64_t qd = qd0 + pass * 192;
    const float g0 = g_GATE[row_g + pass * 64].y, g1 = g_GATE[row_g + pass * 64 + 8].y;
    if (!slow) {
      float s1[64];
      uint32_t p0[32], p1[32];
      uint64_t kd = kd0, vd = vd0;
#pragma unroll 1
      for (int j = 0; j < 7; j++) {
        attn_pair(s0, s1, p0, p1, o, qd, kd + 384, qd, kd + 768, vd, j, bar + 8 * (j + 1), cm, neg1);
        wg_wait<1>();
        pin(s0);
        kd += 768; vd += 768;
      }
      attn_pair(s0, s1, p0, p1, o, qd, kd + 384, qd0 + ((pass + 1) & 3) * 192, kd0, vd, 1, bar, cm, neg1);
      wg_wait<0>();
      pin(s0); pin(o);
    } else {
      uint32_t p[32];
      float m0 = -INFINITY, m1 = -INFINITY;
#pragma unroll
      for (int i = 0; i < 12; i++) o[i] = 0.f;
#pragma unroll 1
      for (int j = 0; j < 16; j++) {
        mbar_wait_u(bar + 8 * (j >> 1), 0);
        wg_fence();
        issue_qk(s0, qd, kd0 + j * 384);
        wg_commit();
        wg_wait<0>();
        pin(s0);
        float n0 = m0, n1 = m1;
#pragma unroll
        for (int g = 0; g < 16; g++) { n0 = fmaxf(n0, fmaxf(s0[4 * g], s0[4 * g + 1])); n1 = fmaxf(n1, fmaxf(s0[4 * g + 2], s0[4 * g + 3])); }
        n0 = fmaxf(n0, __shfl_xor_sync(~0u, n0, 1)); n1 = fmaxf(n1, __shfl_xor_sync(~0u, n1, 1));
        n0 = fmaxf(n0, __shfl_xor_sync(~0u, n0, 2)); n1 = fmaxf(n1, __shfl_xor_sync(~0u, n1, 2));
        const float c0 = ex2(m0 - n0), c1 = ex2(m1 - n1);
        m0 = n0; m1 = n1;
#pragma unroll
        for (int i = 0; i < 3; i++) { o[4 * i] *= c0; o[4 * i + 1] *= c0; o[4 * i + 2] *= c1; o[4 * i + 3] *= c1; }
#pragma unroll
        for (int g = 0; g < 16; g++) {
          const uint32_t sg = ((POLY_MASK >> g) & 1) ? 0x80008000u : 0u;
          p[2 * g] = packbf(ex2(s0[4 * g] - m0), ex2(s0[4 * g + 1] - m0)) ^ sg;
          p[2 * g + 1] = packbf(ex2(s0[4 * g + 2] - m1), ex2(s0[4 * g + 3] - m1)) ^ sg;
        }
        wg_fence();
        issue_pv(o, p, vd0 + j * 384, 1);
        wg_commit();
        wg_wait<0>();
        pin(o);
      }
    }
    store_o(o, odd, lane, (mt0 + pass) * 4 + w4, 80 + colgrp, 0.f, g0, g1);
    PROF(tid == 0, 1, 3 + pass);
    if (pass == 1 + wg) linear_readout(sb + K2_KV + wg * 2304, h, mt0, wg, w4, lane, row_g, colgrp);
  }
  PROF(tid == 0, 1, 7);
}

constexpr int K3_STAGE = 36864, K3_NST = 5, K3_XCH = K3_NST * K3_STAGE, K3_BAR = K3_XCH + 40960, K3_SMEM = K3_BAR + 128;

__global__ void __cluster_dims__(2, 1, 1) __launch_bounds__(288, 1) k3_out(const __grid_constant__ CUtensorMap mout) {
  extern __shared__ __align__(1024) uint8_t smem[];
  const uint32_t sb = smem_u32(smem);
  const uint32_t full = sb + K3_BAR, empty = full + 8 * K3_NST;
  const int warp = __shfl_sync(~0u, threadIdx.x >> 5, 0), lane = threadIdx.x & 31, wg = warp >> 2, w4 = warp & 3;
  const int bid = blockIdx.x, half = bid & 1, nt = (bid >> 1) & 3, mt = bid >> 3;
  PROF(threadIdx.x == 0, 2, 0);
  const uint8_t* ga = g_OAB + (size_t)(mt * 20 + half * 10) * 16384;
  const uint8_t* gb = g_WOI + (size_t)nt * 409600 + half * 204800;
  if (threadIdx.x == 256) {
    for (int i = 0; i < K3_NST; i++) { mbar_init(full + 8 * i, 1); mbar_init(empty + 8 * i, 2); }
    asm volatile("fence.mbarrier_init.release.cluster;" ::: "memory");
    for (int i = 0; i < K3_NST; i++) {
      mbar_expect(full + 8 * i, K3_STAGE);
      bulk_g2s(sb + i * K3_STAGE + 16384, gb + i * 20480, 20480, full + 8 * i);
    }
  }
  __syncthreads();
  asm volatile("barrier.cluster.arrive.relaxed.aligned;" ::: "memory");
  if (warp == 8) {
    if (lane == 0) {
      pdl_wait();
      PROF(true, 2, 1);
      fence_async_all();
      for (int i = 0; i < K3_NST; i++) bulk_g2s(sb + i * K3_STAGE, ga + i * 16384, 16384, full + 8 * i);
      for (int it = K3_NST; it < 10; it++) {
        const int s = it - K3_NST;
        mbar_wait(empty + 8 * s, 0);
        mbar_expect(full + 8 * s, K3_STAGE);
        bulk_g2s(sb + s * K3_STAGE, ga + it * 16384, 16384, full + 8 * s);
        bulk_g2s(sb + s * K3_STAGE + 16384, gb + it * 20480, 20480, full + 8 * s);
      }
    }
    __syncwarp();
    asm volatile("barrier.cluster.wait.aligned;" ::: "memory");
    asm volatile("barrier.cluster.arrive.release.aligned;" ::: "memory");
    asm volatile("barrier.cluster.wait.acquire.aligned;" ::: "memory");
  } else {
    float acc[80];
#pragma unroll 1
    for (int it = 0; it < 10; it++) {
      const int s = it % K3_NST;
      mbar_wait_u(full + 8 * s, it / K3_NST);
      PROF(threadIdx.x == 0 && it == 0, 2, 2);
      const uint32_t st = sb + s * K3_STAGE;
      const uint64_t ad = mkdesc(st + wg * 8192, 128, 1024, 0), bd = mkdesc(st + 16384, 2560, 128, 0);
      wg_fence();
#pragma unroll
      for (int kk = 0; kk < 4; kk++) mma_n160_ss_tb(acc, ad + kk * 16, bd + kk * 320, it | kk);
      wg_commit();
      wg_wait<1>();
      if (it > 0 && (threadIdx.x & 127) == 0) mbar_arrive(empty + 8 * ((it - 1) % K3_NST));
    }
    wg_wait<0>();
    pin(acc);
    PROF(threadIdx.x == 0, 2, 3);
    asm volatile("barrier.cluster.wait.aligned;" ::: "memory");
    uint32_t remote;
    asm volatile("mapa.shared::cluster.u32 %0, %1, %2;" : "=r"(remote) : "r"(sb + K3_XCH + threadIdx.x * 16), "r"(half ^ 1));
#pragma unroll
    for (int j = 0; j < 10; j++) {
      const float v0 = half ? acc[4 * j] : acc[40 + 4 * j], v1 = half ? acc[4 * j + 1] : acc[41 + 4 * j];
      const float v2 = half ? acc[4 * j + 2] : acc[42 + 4 * j], v3 = half ? acc[4 * j + 3] : acc[43 + 4 * j];
      asm volatile("st.shared::cluster.v4.f32 [%0], {%1,%2,%3,%4};" ::"r"(remote + j * 4096), "f"(v0), "f"(v1), "f"(v2), "f"(v3) : "memory");
    }
    asm volatile("barrier.cluster.arrive.release.aligned;" ::: "memory");
    asm volatile("barrier.cluster.wait.acquire.aligned;" ::: "memory");
    bar_sync(3, 256);
    const uint32_t ob = sb + wg * 10240;
    const uint32_t oa = ob + (w4 * 16 + (lane & 15)) * 160 + (lane >> 4) * 16;
    uint32_t pk[20];
#pragma unroll
    for (int j = 0; j < 10; j++) {
      const float4 r = *(const float4*)(smem + K3_XCH + j * 4096 + threadIdx.x * 16);
      const float v0 = half ? acc[40 + 4 * j] : acc[4 * j], v1 = half ? acc[41 + 4 * j] : acc[4 * j + 1];
      const float v2 = half ? acc[42 + 4 * j] : acc[4 * j + 2], v3 = half ? acc[43 + 4 * j] : acc[4 * j + 3];
      pk[2 * j] = packbf(v0 + r.x, v1 + r.y);
      pk[2 * j + 1] = packbf(v2 + r.z, v3 + r.w);
    }
#pragma unroll
    for (int j = 0; j < 10; j += 2) stsm4(oa + j * 16, pk[2 * j], pk[2 * j + 1], pk[2 * j + 2], pk[2 * j + 3]);
    fence_async_smem();
    bar_sync(1 + wg, 128);
    if ((threadIdx.x & 127) == 0) {
      asm volatile("cp.async.bulk.tensor.2d.global.shared::cta.bulk_group [%0, {%2,%3}], [%1];" ::"l"(&mout), "r"(ob), "r"(nt * 160 + half * 80),
                   "r"(mt * 128 + wg * 64) : "memory");
      asm volatile("cp.async.bulk.commit_group;" ::: "memory");
      asm volatile("cp.async.bulk.wait_group 0;" ::: "memory");
    }
    PROF(threadIdx.x == 0, 2, 4);
  }
}

typedef CUresult (*EncodeFn)(CUtensorMap*, CUtensorMapDataType, cuuint32_t, void*, const cuuint64_t*, const cuuint64_t*, const cuuint32_t*,
                             const cuuint32_t*, CUtensorMapInterleave, CUtensorMapSwizzle, CUtensorMapL2promotion, CUtensorMapFloatOOBfill);

void encode(EncodeFn fn, CUtensorMap* m, const void* p, int rank, const cuuint64_t* dims, const cuuint64_t* strides, const cuuint32_t* box,
            CUtensorMapSwizzle sw) {
  const cuuint32_t es[3] = {1, 1, 1};
  fn(m, CU_TENSOR_MAP_DATA_TYPE_BFLOAT16, rank, const_cast<void*>(p), dims, strides, box, es, CU_TENSOR_MAP_INTERLEAVE_NONE, sw,
     CU_TENSOR_MAP_L2_PROMOTION_L2_128B, CU_TENSOR_MAP_FLOAT_OOB_FILL_NONE);
}

}

extern "C" void kernel_launch(void* const* d_in, const int* in_sizes, int n_in, void* d_out, int out_size) {
  (void)in_sizes; (void)n_in; (void)out_size;
  const __nv_bfloat16* x = (const __nv_bfloat16*)d_in[0];
  const void* wa = d_in[1];
  const __nv_bfloat16* wphi = (const __nv_bfloat16*)d_in[2];
  const void* woa = d_in[3];
  const void* wb = d_in[5];
  const void* wob = d_in[6];
  const __nv_bfloat16* gate_w = (const __nv_bfloat16*)d_in[7];

  static EncodeFn enc = nullptr;
  if (!enc) {
    void* fn = nullptr;
    cudaDriverEntryPointQueryResult qr;
    cudaGetDriverEntryPoint("cuTensorMapEncodeTiled", &fn, cudaEnableDefault, &qr);
    enc = (EncodeFn)fn;
    cudaFuncSetAttribute(k1_qkv, cudaFuncAttributeMaxDynamicSharedMemorySize, K1_SMEM);
    cudaFuncSetAttribute(k2_attn, cudaFuncAttributeMaxDynamicSharedMemorySize, K2_SMEM);
    cudaFuncSetAttribute(k3_out, cudaFuncAttributeMaxDynamicSharedMemorySize, K3_SMEM);
  }
  K1Maps maps;
  CUtensorMap mout;
  {
    const cuuint64_t dx[2] = {640, 2048}, sx[1] = {1280};
    const cuuint32_t bx[2] = {32, 128}, bo[2] = {80, 64};
    encode(enc, &maps.x, x, 2, dx, sx, bx, CU_TENSOR_MAP_SWIZZLE_64B);
    encode(enc, &mout, d_out, 2, dx, sx, bo, CU_TENSOR_MAP_SWIZZLE_NONE);
    const cuuint64_t dw[3] = {640, 640, 3}, sw[2] = {3840, 1280};
    const cuuint32_t b64_1[3] = {64, 32, 1}, b16_1[3] = {16, 32, 1}, b64_2[3] = {64, 32, 2}, b16_2[3] = {16, 32, 2};
    encode(enc, &maps.a64_1, wa, 3, dw, sw, b64_1, CU_TENSOR_MAP_SWIZZLE_128B);
    encode(enc, &maps.a16_1, wa, 3, dw, sw, b16_1, CU_TENSOR_MAP_SWIZZLE_32B);
    encode(enc, &maps.a64_2, wa, 3, dw, sw, b64_2, CU_TENSOR_MAP_SWIZZLE_128B);
    encode(enc, &maps.a16_2, wa, 3, dw, sw, b16_2, CU_TENSOR_MAP_SWIZZLE_32B);
    encode(enc, &maps.b64_1, wb, 3, dw, sw, b64_1, CU_TENSOR_MAP_SWIZZLE_128B);
    encode(enc, &maps.b16_1, wb, 3, dw, sw, b16_1, CU_TENSOR_MAP_SWIZZLE_32B);
    encode(enc, &maps.b64_2, wb, 3, dw, sw, b64_2, CU_TENSOR_MAP_SWIZZLE_128B);
    encode(enc, &maps.b16_2, wb, 3, dw, sw, b16_2, CU_TENSOR_MAP_SWIZZLE_32B);
  }
  cudaStream_t st = cudaStreamPerThread;
  cudaLaunchAttribute pdl[1];
  pdl[0].id = cudaLaunchAttributeProgrammaticStreamSerialization;
  pdl[0].val.programmaticStreamSerializationAllowed = 1;
  cudaLaunchConfig_t c = {};
  c.stream = st;
  c.gridDim = dim3(128); c.blockDim = dim3(512); c.dynamicSmemBytes = K1_SMEM; c.attrs = nullptr; c.numAttrs = 0;
  cudaLaunchKernelEx(&c, k1_qkv, maps, x, wphi, gate_w, (const uint8_t*)wa, (const uint8_t*)wb,
                     (const uint8_t*)woa, (const uint8_t*)wob);
  c.gridDim = dim3(132); c.blockDim = dim3(256); c.dynamicSmemBytes = K2_SMEM; c.attrs = pdl; c.numAttrs = 1;
  cudaLaunchKernelEx(&c, k2_attn, 0x1F801F80u, 0xFFFFFFFFu);
  c.gridDim = dim3(128); c.blockDim = dim3(288); c.dynamicSmemBytes = K3_SMEM;
  cudaLaunchKernelEx(&c, k3_out, mout);
}
```

```cpp
#include <cuda_runtime.h>
#include <cuda_bf16.h>
#include <cuda.h>
#include <stdint.h>

#define NOPHIQ 0
#define NOKV 0
namespace {

constexpr int SEQ = 2048, DM = 640, NH = 32;
constexpr int IMG_HEAD = SEQ * 48;
#define POLY_MASK 0x76DDu
constexpr float LOG2E = 1.4426950408889634f;
constexpr float QSCALE = 0.22360679774997896f * 1.4426950408889634f;
constexpr uint32_t BF_ONE = 0x3F80u;
constexpr uint32_t BF_MAGIC = 0x43E0u;
constexpr uint32_t BF_MU_HI = 0x4025u;
constexpr uint32_t BF_MU_LO = 0x3B8Bu;
constexpr float FAST_BOUND = 40.0f;

__device__ __align__(1024) uint8_t g_QKVB[3 * NH * IMG_HEAD];
__device__ __align__(1024) uint4 g_PHIQ[NH * 32 * 3 * 128];
__device__ __align__(1024) float4 g_KVP[NH * 16 * 288];
__device__ __align__(1024) uint8_t g_KVB[NH * 2304];
__device__ __align__(128) uint32_t g_KVFLAG[32];
__device__ __align__(1024) float g_KMAX[NH * 128];
__device__ __align__(1024) float2 g_GATE[SEQ];
__device__ __align__(1024) uint8_t g_OAB[16 * 20 * 16384];
__device__ __align__(1024) uint8_t g_WOI[8 * 20 * 10240];

#define PROF(cond, k, slot)
__device__ __forceinline__ uint32_t smem_u32(const void* p) { return (uint32_t)__cvta_generic_to_shared(p); }
__device__ __forceinline__ void mbar_init(uint32_t a, uint32_t c) { asm volatile("mbarrier.init.shared::cta.b64 [%0], %1;" ::"r"(a), "r"(c) : "memory"); }
__device__ __forceinline__ void mbar_expect(uint32_t a, uint32_t b) { asm volatile("mbarrier.arrive.expect_tx.shared::cta.b64 _, [%0], %1;" ::"r"(a), "r"(b) : "memory"); }
__device__ __forceinline__ void mbar_arrive(uint32_t a) { asm volatile("mbarrier.arrive.shared::cta.b64 _, [%0];" ::"r"(a) : "memory"); }
__device__ __forceinline__ void mbar_wait(uint32_t a, uint32_t ph) {
  asm volatile(
      "{\n.reg .pred p;\n.reg .u32 n;\nmov.u32 n, 0;\n"
      "W_%=:\nmbarrier.try_wait.parity.shared::cta.b64 p, [%0], %1;\n@p bra D_%=;\n"
      "add.u32 n, n, 1;\nsetp.lt.u32 p, n, 4000000;\n@p bra W_%=;\ntrap;\nD_%=:\n}\n" ::"r"(a), "r"(ph) : "memory");
}
__device__ __forceinline__ void mbar_wait_u(uint32_t a, uint32_t ph) {
#pragma unroll 1
  for (int n = 0;; n++) {
    uint32_t ok;
    asm volatile("{\n.reg .pred p;\nmbarrier.try_wait.parity.shared::cta.b64 p, [%1], %2;\nselp.u32 %0, 1, 0, p;\n}\n" : "=r"(ok) : "r"(a), "r"(ph) : "memory");
    if (__all_sync(~0u, ok)) break;
    if (n > 4000000) __trap();
  }
}
__device__ __forceinline__ void tma2(uint32_t dst, const CUtensorMap* m, int c0, int c1, uint32_t bar) {
  asm volatile("cp.async.bulk.tensor.2d.shared::cluster.global.mbarrier::complete_tx::bytes [%0], [%1, {%3,%4}], [%2];" ::"r"(dst), "l"(m), "r"(bar), "r"(c0), "r"(c1) : "memory");
}
__device__ __forceinline__ void tma3(uint32_t dst, const CUtensorMap* m, int c0, int c1, int c2, uint32_t bar) {
  asm volatile("cp.async.bulk.tensor.3d.shared::cluster.global.mbarrier::complete_tx::bytes [%0], [%1, {%3,%4,%5}], [%2];" ::"r"(dst), "l"(m), "r"(bar), "r"(c0), "r"(c1), "r"(c2) : "memory");
}
__device__ __forceinline__ void bulk_g2s(uint32_t dst, const void* src, uint32_t bytes, uint32_t bar) {
  asm volatile("cp.async.bulk.shared::cluster.global.mbarrier::complete_tx::bytes [%0], [%1], %2, [%3];" ::"r"(dst), "l"(src), "r"(bytes), "r"(bar) : "memory");
}
__device__ __forceinline__ void prefetch_l2(const void* src, uint32_t bytes) { asm volatile("cp.async.bulk.prefetch.L2.global [%0], %1;" ::"l"(src), "r"(bytes) : "memory"); }
__device__ __forceinline__ void fence_async_smem() { asm volatile("fence.proxy.async.shared::cta;" ::: "memory"); }
__device__ __forceinline__ void fence_async_all() { asm volatile("fence.proxy.async;" ::: "memory"); }
__device__ __forceinline__ void bar_sync(int id, int n) { asm volatile("bar.sync %0, %1;" ::"r"(id), "r"(n) : "memory"); }
__device__ __forceinline__ void bar_arrive(int id, int n) { asm volatile("bar.arrive %0, %1;" ::"r"(id), "r"(n) : "memory"); }
__device__ __forceinline__ void pdl_wait() { asm volatile("griddepcontrol.wait;" ::: "memory"); }
__device__ __forceinline__ void pdl_launch() { asm volatile("griddepcontrol.launch_dependents;" ::: "memory"); }
__device__ __forceinline__ void wg_fence() { asm volatile("wgmma.fence.sync.aligned;" ::: "memory"); }
__device__ __forceinline__ void wg_commit() { asm volatile("wgmma.commit_group.sync.aligned;" ::: "memory"); }
template <int N> __device__ __forceinline__ void wg_wait() { asm volatile("wgmma.wait_group.sync.aligned %0;" ::"n"(N) : "memory"); }
template <int N> __device__ __forceinline__ void reg_inc() { asm volatile("setmaxnreg.inc.sync.aligned.u32 %0;" ::"n"(N)); }
template <int N> __device__ __forceinline__ void reg_dec() { asm volatile("setmaxnreg.dec.sync.aligned.u32 %0;" ::"n"(N)); }
template <int N> __device__ __forceinline__ void pin(float (&r)[N]) {
#pragma unroll
  for (int i = 0; i < N; i++) asm volatile("" : "+f"(r[i])::"memory");
}
template <int N> __device__ __forceinline__ void pin(uint32_t (&r)[N]) {
#pragma unroll
  for (int i = 0; i < N; i++) asm volatile("" : "+r"(r[i])::"memory");
}
__device__ __forceinline__ uint64_t mkdesc(uint32_t addr, uint32_t lbo, uint32_t sbo, uint32_t swz) {
  return (uint64_t)((addr & 0x3FFFF) >> 4) | ((uint64_t)(lbo >> 4) << 16) | ((uint64_t)(sbo >> 4) << 32) | ((uint64_t)swz << 62);
}
__device__ __forceinline__ float ex2(float x) { float y; asm("ex2.approx.ftz.f32 %0, %1;" : "=f"(y) : "f"(x)); return y; }
__device__ __forceinline__ float rcp(float x) { float y; asm("rcp.approx.ftz.f32 %0, %1;" : "=f"(y) : "f"(x)); return y; }
__device__ __forceinline__ float sqrt_ap(float x) { float y; asm("sqrt.approx.f32 %0, %1;" : "=f"(y) : "f"(x)); return y; }
__device__ __forceinline__ uint32_t packbf(float lo, float hi) { uint32_t d; asm("cvt.rn.bf16x2.f32 %0, %1, %2;" : "=r"(d) : "f"(hi), "f"(lo)); return d; }
__device__ __forceinline__ float bf_lo(uint32_t v) { return __uint_as_float(v << 16); }
__device__ __forceinline__ float bf_hi(uint32_t v) { return __uint_as_float(v & 0xFFFF0000u); }
__device__ __forceinline__ float bf_round(float x) { return bf_lo(packbf(x, 0.f)); }
__device__ __forceinline__ uint32_t ldg_cg(const void* p) { uint32_t v; asm volatile("ld.global.cg.b32 %0, [%1];" : "=r"(v) : "l"(p) : "memory"); return v; }
__device__ __forceinline__ uint4 ldg_cg4(const void* p) { uint4 v; asm volatile("ld.global.cg.v4.b32 {%0,%1,%2,%3}, [%4];" : "=r"(v.x), "=r"(v.y), "=r"(v.z), "=r"(v.w) : "l"(p) : "memory"); return v; }
__device__ __forceinline__ void sts32(uint32_t a, uint32_t v) { asm volatile("st.shared.b32 [%0], %1;" ::"r"(a), "r"(v) : "memory"); }
__device__ __forceinline__ void stsm4(uint32_t a, uint32_t r0, uint32_t r1, uint32_t r2, uint32_t r3) {
  asm volatile("stmatrix.sync.aligned.m8n8.x4.shared.b16 [%0], {%1,%2,%3,%4};" ::"r"(a), "r"(r0), "r"(r1), "r"(r2), "r"(r3) : "memory");
}

__device__ __forceinline__ void ldsm4(uint32_t (&r)[4], uint32_t a) {
  asm volatile("ldmatrix.sync.aligned.m8n8.x4.shared.b16 {%0,%1,%2,%3}, [%4];" : "=r"(r[0]), "=r"(r[1]), "=r"(r[2]), "=r"(r[3]) : "r"(a) : "memory");
}
__device__ __forceinline__ void bulk_s2g(void* dst, uint32_t src, uint32_t bytes) {
  asm volatile("cp.async.bulk.global.shared::cta.bulk_group [%0], [%1], %2;" ::"l"(dst), "r"(src), "r"(bytes) : "memory");
}

__device__ __forceinline__ void mma_n24_ss_tb(float (&d)[12], uint64_t adesc, uint64_t bdesc, int acc) {
  asm volatile("{\n.reg .pred p;\nsetp.ne.b32 p, %14, 0;\n"
      "wgmma.mma_async.sync.aligned.m64n24k16.f32.bf16.bf16 "
      "{%0,%1,%2,%3,%4,%5,%6,%7,%8,%9,%10,%11}, "
      "%12, %13, p, 1, 1, 0, 1;\n}\n"
      : "+f"(d[0]), "+f"(d[1]), "+f"(d[2]), "+f"(d[3]), "+f"(d[4]), "+f"(d[5]), "+f"(d[6]), "+f"(d[7]),
        "+f"(d[8]), "+f"(d[9]), "+f"(d[10]), "+f"(d[11])
      : "l"(adesc), "l"(bdesc), "r"(acc));
}
__device__ __forceinline__ void mma_n192_rs_tb(float (&d)[96], uint32_t a0, uint32_t a1, uint32_t a2, uint32_t a3, uint64_t bdesc, int acc) {
  asm volatile("{\n.reg .pred p;\nsetp.ne.b32 p, %101, 0;\n"
      "wgmma.mma_async.sync.aligned.m64n192k16.f32.bf16.bf16 "
      "{%0,%1,%2,%3,%4,%5,%6,%7,%8,%9,%10,%11,%12,%13,%14,%15,"
      "%16,%17,%18,%19,%20,%21,%22,%23,%24,%25,%26,%27,%28,%29,%30,%31,"
      "%32,%33,%34,%35,%36,%37,%38,%39,%40,%41,%42,%43,%44,%45,%46,%47,"
      "%48,%49,%50,%51,%52,%53,%54,%55,%56,%57,%58,%59,%60,%61,%62,%63,"
      "%64,%65,%66,%67,%68,%69,%70,%71,%72,%73,%74,%75,%76,%77,%78,%79,"
      "%80,%81,%82,%83,%84,%85,%86,%87,%88,%89,%90,%91,%92,%93,%94,%95}, "
      "{%96,%97,%98,%99}, %100, p, 1, 1, 1;\n}\n"
      : "+f"(d[0]), "+f"(d[1]), "+f"(d[2]), "+f"(d[3]), "+f"(d[4]), "+f"(d[5]), "+f"(d[6]), "+f"(d[7]),
        "+f"(d[8]), "+f"(d[9]), "+f"(d[10]), "+f"(d[11]), "+f"(d[12]), "+f"(d[13]), "+f"(d[14]), "+f"(d[15]),
        "+f"(d[16]), "+f"(d[17]), "+f"(d[18]), "+f"(d[19]), "+f"(d[20]), "+f"(d[21]), "+f"(d[22]), "+f"(d[23]),
        "+f"(d[24]), "+f"(d[25]), "+f"(d[26]), "+f"(d[27]), "+f"(d[28]), "+f"(d[29]), "+f"(d[30]), "+f"(d[31]),
        "+f"(d[32]), "+f"(d[33]), "+f"(d[34]), "+f"(d[35]), "+f"(d[36]), "+f"(d[37]), "+f"(d[38]), "+f"(d[39]),
        "+f"(d[40]), "+f"(d[41]), "+f"(d[42]), "+f"(d[43]), "+f"(d[44]), "+f"(d[45]), "+f"(d[46]), "+f"(d[47]),
        "+f"(d[48]), "+f"(d[49]), "+f"(d[50]), "+f"(d[51]), "+f"(d[52]), "+f"(d[53]), "+f"(d[54]), "+f"(d[55]),
        "+f"(d[56]), "+f"(d[57]), "+f"(d[58]), "+f"(d[59]), "+f"(d[60]), "+f"(d[61]), "+f"(d[62]), "+f"(d[63]),
        "+f"(d[64]), "+f"(d[65]), "+f"(d[66]), "+f"(d[67]), "+f"(d[68]), "+f"(d[69]), "+f"(d[70]), "+f"(d[71]),
        "+f"(d[72]), "+f"(d[73]), "+f"(d[74]), "+f"(d[75]), "+f"(d[76]), "+f"(d[77]), "+f"(d[78]), "+f"(d[79]),
        "+f"(d[80]), "+f"(d[81]), "+f"(d[82]), "+f"(d[83]), "+f"(d[84]), "+f"(d[85]), "+f"(d[86]), "+f"(d[87]),
        "+f"(d[88]), "+f"(d[89]), "+f"(d[90]), "+f"(d[91]), "+f"(d[92]), "+f"(d[93]), "+f"(d[94]), "+f"(d[95])
      : "r"(a0), "r"(a1), "r"(a2), "r"(a3), "l"(bdesc), "r"(acc));
}
__device__ __forceinline__ void mma_n48_rs_tb(float (&d)[24], uint32_t a0, uint32_t a1, uint32_t a2, uint32_t a3, uint64_t bdesc, int acc) {
  asm volatile("{\n.reg .pred p;\nsetp.ne.b32 p, %29, 0;\n"
      "wgmma.mma_async.sync.aligned.m64n48k16.f32.bf16.bf16 "
      "{%0,%1,%2,%3,%4,%5,%6,%7,%8,%9,%10,%11,%12,%13,%14,%15,"
      "%16,%17,%18,%19,%20,%21,%22,%23}, "
      "{%24,%25,%26,%27}, %28, p, 1, 1, 1;\n}\n"
      : "+f"(d[0]), "+f"(d[1]), "+f"(d[2]), "+f"(d[3]), "+f"(d[4]), "+f"(d[5]), "+f"(d[6]), "+f"(d[7]),
        "+f"(d[8]), "+f"(d[9]), "+f"(d[10]), "+f"(d[11]), "+f"(d[12]), "+f"(d[13]), "+f"(d[14]), "+f"(d[15]),
        "+f"(d[16]), "+f"(d[17]), "+f"(d[18]), "+f"(d[19]), "+f"(d[20]), "+f"(d[21]), "+f"(d[22]), "+f"(d[23])
      : "r"(a0), "r"(a1), "r"(a2), "r"(a3), "l"(bdesc), "r"(acc));
}
__device__ __forceinline__ void mma_n128_ss(float (&d)[64], uint64_t adesc, uint64_t bdesc, int acc) {
  asm volatile("{\n.reg .pred p;\nsetp.ne.b32 p, %66, 0;\n"
      "wgmma.mma_async.sync.aligned.m64n128k16.f32.bf16.bf16 "
      "{%0,%1,%2,%3,%4,%5,%6,%7,%8,%9,%10,%11,%12,%13,%14,%15,"
      "%16,%17,%18,%19,%20,%21,%22,%23,%24,%25,%26,%27,%28,%29,%30,%31,"
      "%32,%33,%34,%35,%36,%37,%38,%39,%40,%41,%42,%43,%44,%45,%46,%47,"
      "%48,%49,%50,%51,%52,%53,%54,%55,%56,%57,%58,%59,%60,%61,%62,%63}, "
      "%64, %65, p, 1, 1, 0, 0;\n}\n"
      : "+f"(d[0]), "+f"(d[1]), "+f"(d[2]), "+f"(d[3]), "+f"(d[4]), "+f"(d[5]), "+f"(d[6]), "+f"(d[7]),
        "+f"(d[8]), "+f"(d[9]), "+f"(d[10]), "+f"(d[11]), "+f"(d[12]), "+f"(d[13]), "+f"(d[14]), "+f"(d[15]),
        "+f"(d[16]), "+f"(d[17]), "+f"(d[18]), "+f"(d[19]), "+f"(d[20]), "+f"(d[21]), "+f"(d[22]), "+f"(d[23]),
        "+f"(d[24]), "+f"(d[25]), "+f"(d[26]), "+f"(d[27]), "+f"(d[28]), "+f"(d[29]), "+f"(d[30]), "+f"(d[31]),
        "+f"(d[32]), "+f"(d[33]), "+f"(d[34]), "+f"(d[35]), "+f"(d[36]), "+f"(d[37]), "+f"(d[38]), "+f"(d[39]),
        "+f"(d[40]), "+f"(d[41]), "+f"(d[42]), "+f"(d[43]), "+f"(d[44]), "+f"(d[45]), "+f"(d[46]), "+f"(d[47]),
        "+f"(d[48]), "+f"(d[49]), "+f"(d[50]), "+f"(d[51]), "+f"(d[52]), "+f"(d[53]), "+f"(d[54]), "+f"(d[55]),
        "+f"(d[56]), "+f"(d[57]), "+f"(d[58]), "+f"(d[59]), "+f"(d[60]), "+f"(d[61]), "+f"(d[62]), "+f"(d[63])
      : "l"(adesc), "l"(bdesc), "r"(acc));
}
__device__ __forceinline__ void mma_n160_ss_tb(float (&d)[80], uint64_t adesc, uint64_t bdesc, int acc) {
  asm volatile("{\n.reg .pred p;\nsetp.ne.b32 p, %82, 0;\n"
      "wgmma.mma_async.sync.aligned.m64n160k16.f32.bf16.bf16 "
      "{%0,%1,%2,%3,%4,%5,%6,%7,%8,%9,%10,%11,%12,%13,%14,%15,"
      "%16,%17,%18,%19,%20,%21,%22,%23,%24,%25,%26,%27,%28,%29,%30,%31,"
      "%32,%33,%34,%35,%36,%37,%38,%39,%40,%41,%42,%43,%44,%45,%46,%47,"
      "%48,%49,%50,%51,%52,%53,%54,%55,%56,%57,%58,%59,%60,%61,%62,%63,"
      "%64,%65,%66,%67,%68,%69,%70,%71,%72,%73,%74,%75,%76,%77,%78,%79}, "
      "%80, %81, p, 1, 1, 0, 1;\n}\n"
      : "+f"(d[0]), "+f"(d[1]), "+f"(d[2]), "+f"(d[3]), "+f"(d[4]), "+f"(d[5]), "+f"(d[6]), "+f"(d[7]),
        "+f"(d[8]), "+f"(d[9]), "+f"(d[10]), "+f"(d[11]), "+f"(d[12]), "+f"(d[13]), "+f"(d[14]), "+f"(d[15]),
        "+f"(d[16]), "+f"(d[17]), "+f"(d[18]), "+f"(d[19]), "+f"(d[20]), "+f"(d[21]), "+f"(d[22]), "+f"(d[23]),
        "+f"(d[24]), "+f"(d[25]), "+f"(d[26]), "+f"(d[27]), "+f"(d[28]), "+f"(d[29]), "+f"(d[30]), "+f"(d[31]),
        "+f"(d[32]), "+f"(d[33]), "+f"(d[34]), "+f"(d[35]), "+f"(d[36]), "+f"(d[37]), "+f"(d[38]), "+f"(d[39]),
        "+f"(d[40]), "+f"(d[41]), "+f"(d[42]), "+f"(d[43]), "+f"(d[44]), "+f"(d[45]), "+f"(d[46]), "+f"(d[47]),
        "+f"(d[48]), "+f"(d[49]), "+f"(d[50]), "+f"(d[51]), "+f"(d[52]), "+f"(d[53]), "+f"(d[54]), "+f"(d[55]),
        "+f"(d[56]), "+f"(d[57]), "+f"(d[58]), "+f"(d[59]), "+f"(d[60]), "+f"(d[61]), "+f"(d[62]), "+f"(d[63]),
        "+f"(d[64]), "+f"(d[65]), "+f"(d[66]), "+f"(d[67]), "+f"(d[68]), "+f"(d[69]), "+f"(d[70]), "+f"(d[71]),
        "+f"(d[72]), "+f"(d[73]), "+f"(d[74]), "+f"(d[75]), "+f"(d[76]), "+f"(d[77]), "+f"(d[78]), "+f"(d[79])
      : "l"(adesc), "l"(bdesc), "r"(acc));
}
__device__ __forceinline__ void mma_n24_rs_tb(float (&d)[12], uint32_t a0, uint32_t a1, uint32_t a2, uint32_t a3, uint64_t bdesc, int acc) {
  asm volatile("{\n.reg .pred p;\nsetp.ne.b32 p, %17, 0;\n"
      "wgmma.mma_async.sync.aligned.m64n24k16.f32.bf16.bf16 "
      "{%0,%1,%2,%3,%4,%5,%6,%7,%8,%9,%10,%11}, "
      "{%12,%13,%14,%15}, %16, p, 1, 1, 1;\n}\n"
      : "+f"(d[0]), "+f"(d[1]), "+f"(d[2]), "+f"(d[3]), "+f"(d[4]), "+f"(d[5]), "+f"(d[6]), "+f"(d[7]),
        "+f"(d[8]), "+f"(d[9]), "+f"(d[10]), "+f"(d[11])
      : "r"(a0), "r"(a1), "r"(a2), "r"(a3), "l"(bdesc), "r"(acc));
}
__device__ __forceinline__ void mma_n24_ss_tatb(float (&d)[12], uint64_t adesc, uint64_t bdesc, int acc) {
  asm volatile("{\n.reg .pred p;\nsetp.ne.b32 p, %14, 0;\n"
      "wgmma.mma_async.sync.aligned.m64n24k16.f32.bf16.bf16 "
      "{%0,%1,%2,%3,%4,%5,%6,%7,%8,%9,%10,%11}, "
      "%12, %13, p, 1, 1, 1, 1;\n}\n"
      : "+f"(d[0]), "+f"(d[1]), "+f"(d[2]), "+f"(d[3]), "+f"(d[4]), "+f"(d[5]), "+f"(d[6]), "+f"(d[7]),
        "+f"(d[8]), "+f"(d[9]), "+f"(d[10]), "+f"(d[11])
      : "l"(adesc), "l"(bdesc), "r"(acc));
}

constexpr int K1_STAGE = 23552;
constexpr int K1_NST = 6;
constexpr int K1_STG = K1_NST * K1_STAGE;
constexpr int K1_WPH = K1_STG + 73728;
constexpr int K1_BAR = K1_WPH + 6144;
constexpr int K1_SMEM = K1_BAR + 128;

template <int SEC, int J, int HF>
__device__ __forceinline__ float2 grp(const float (&a1)[96], const float (&a2)[24]) {
  if constexpr (J < 8) return make_float2(a1[(8 * SEC + J) * 4 + 2 * HF], a1[(8 * SEC + J) * 4 + 2 * HF + 1]);
  else return make_float2(a2[(2 * SEC + J - 8) * 4 + 2 * HF], a2[(2 * SEC + J - 8) * 4 + 2 * HF + 1]);
}
__device__ __forceinline__ float sq2(float2 v) { return fmaf(v.x, v.x, v.y * v.y); }

template <int SEC, int PR, bool NORM>
__device__ __forceinline__ void stage_pair(const float (&a1)[96], const float (&a2)[24], float sc0, float sc1, uint32_t ext0, uint32_t ext1,
                                           uint32_t ad01, uint32_t ad2, int hs, int t, float (&nrm)[4]) {
  const float2 u0 = grp<SEC, 5 * PR, 0>(a1, a2), u1 = grp<SEC, 5 * PR + 1, 0>(a1, a2), u2 = grp<SEC, 5 * PR + 2, 0>(a1, a2),
               u3 = grp<SEC, 5 * PR + 3, 0>(a1, a2), u4 = grp<SEC, 5 * PR + 4, 0>(a1, a2);
  const float2 w0 = grp<SEC, 5 * PR, 1>(a1, a2), w1 = grp<SEC, 5 * PR + 1, 1>(a1, a2), w2 = grp<SEC, 5 * PR + 2, 1>(a1, a2),
               w3 = grp<SEC, 5 * PR + 3, 1>(a1, a2), w4 = grp<SEC, 5 * PR + 4, 1>(a1, a2);
  const uint32_t off = (SEC * 4 + 2 * PR) * hs;
  stsm4(ad01 + off, packbf(u0.x * sc0, u0.y * sc0), packbf(w0.x * sc1, w0.y * sc1), packbf(u1.x * sc0, u1.y * sc0), packbf(w1.x * sc1, w1.y * sc1));
  stsm4(ad01 + off + hs, packbf(u3.x * sc0, u3.y * sc0), packbf(w3.x * sc1, w3.y * sc1), packbf(u4.x * sc0, u4.y * sc0), packbf(w4.x * sc1, w4.y * sc1));
  const uint32_t m0 = packbf(u2.x * sc0, u2.y * sc0), m1 = packbf(w2.x * sc1, w2.y * sc1);
  const bool lo = t < 2;
  stsm4(ad2 + off, lo ? m0 : ext0, lo ? m1 : ext1, lo ? ext0 : m0, lo ? ext1 : m1);
  if (NORM) {
    const float h0 = sq2(u2), h1 = sq2(w2);
    float e0 = sq2(u0) + sq2(u1) + (lo ? h0 : 0.f), e1 = sq2(w0) + sq2(w1) + (lo ? h1 : 0.f);
    float o0 = sq2(u3) + sq2(u4) + (lo ? 0.f : h0), o1 = sq2(w3) + sq2(w4) + (lo ? 0.f : h1);
    e0 += __shfl_xor_sync(~0u, e0, 1); e1 += __shfl_xor_sync(~0u, e1, 1); o0 += __shfl_xor_sync(~0u, o0, 1); o1 += __shfl_xor_sync(~0u, o1, 1);
    e0 += __shfl_xor_sync(~0u, e0, 2); e1 += __shfl_xor_sync(~0u, e1, 2); o0 += __shfl_xor_sync(~0u, o0, 2); o1 += __shfl_xor_sync(~0u, o1, 2);
    nrm[2 * PR] = fmaxf(e0, e1); nrm[2 * PR + 1] = fmaxf(o0, o1);
  }
}

__device__ __forceinline__ void hedgehog(const float (&p)[12], uint32_t (&f)[12], int t) {
#pragma unroll
  for (int hf = 0; hf < 2; hf++) {
    float v[6] = {p[2 * hf], p[2 * hf + 1], p[4 + 2 * hf], p[5 + 2 * hf], p[8 + 2 * hf], p[9 + 2 * hf]};
    float mx = fmaxf(fmaxf(fmaxf(v[0], v[1]), fmaxf(v[2], v[3])), fmaxf(v[4], v[5]));
    float mn = fminf(fminf(fminf(v[0], v[1]), fminf(v[2], v[3])), fminf(v[4], v[5]));
    mx = fmaxf(mx, __shfl_xor_sync(~0u, mx, 1)); mn = fminf(mn, __shfl_xor_sync(~0u, mn, 1));
    mx = fmaxf(mx, __shfl_xor_sync(~0u, mx, 2)); mn = fminf(mn, __shfl_xor_sync(~0u, mn, 2));
    const float bp = -mx * LOG2E, bn = mn * LOG2E;
    float ep[6], en[6];
#pragma unroll
    for (int i = 0; i < 6; i++) { ep[i] = ex2(fmaf(v[i], LOG2E, bp)); en[i] = ex2(fmaf(v[i], -LOG2E, bn)); }
    const float keep = (t < 2) ? 1.f : 0.f;
    float sp = (ep[0] + ep[1]) + (ep[2] + ep[3]) + keep * (ep[4] + ep[5]);
    float sn = (en[0] + en[1]) + (en[2] + en[3]) + keep * (en[4] + en[5]);
    sp += __shfl_xor_sync(~0u, sp, 1); sn += __shfl_xor_sync(~0u, sn, 1);
    sp += __shfl_xor_sync(~0u, sp, 2); sn += __shfl_xor_sync(~0u, sn, 2);
    const float rp = rcp(sp), rn = rcp(sn), rp2 = rp * keep, rn2 = rn * keep;
    f[0 + hf] = packbf(ep[0] * rp, ep[1] * rp);
    f[2 + hf] = packbf(ep[2] * rp, ep[3] * rp);
    f[4 + hf] = packbf(ep[4] * rp2, ep[5] * rp2);
    f[6 + hf] = packbf(en[0] * rn, en[1] * rn);
    f[8 + hf] = packbf(en[2] * rn, en[3] * rn);
    f[10 + hf] = packbf(en[4] * rn2, en[5] * rn2);
  }
}

__device__ __forceinline__ void issue_pq(float (&p0)[12], float (&p1)[12], uint32_t img, uint32_t wph) {
  const uint64_t ad = mkdesc(img, 128, 384, 0), a2 = mkdesc(img + 256, 0, 384, 0), wd = mkdesc(wph, 384, 128, 0);
  wg_fence();
  mma_n24_ss_tb(p0, ad, wd, 0);
  mma_n24_ss_tb(p0, a2, wd + 48, 1);
  mma_n24_ss_tb(p1, ad + 192, wd, 0);
  mma_n24_ss_tb(p1, a2 + 192, wd + 48, 1);
  wg_commit();
}
__device__ __forceinline__ void phi_q_store(const float (&p0)[12], const float (&p1)[12], uint4* dst, int t) {
  uint32_t f[12];
  hedgehog(p0, f, t);
#pragma unroll
  for (int ks = 0; ks < 3; ks++) if (!NOPHIQ || f[0] == 0x12345) dst[ks * 128] = make_uint4(f[4 * ks], f[4 * ks + 1], f[4 * ks + 2], f[4 * ks + 3]);
  hedgehog(p1, f, t);
#pragma unroll
  for (int ks = 0; ks < 3; ks++) if (!NOPHIQ || f[0] == 0x12345) dst[(3 + ks) * 128] = make_uint4(f[4 * ks], f[4 * ks + 1], f[4 * ks + 2], f[4 * ks + 3]);
}
template <int SEC, int PR>
__device__ __forceinline__ void frag_pair(const float (&a1)[96], const float (&a2)[24], uint32_t (&e)[6], uint32_t (&o)[6], int t) {
  auto pk = [](float2 v) { return packbf(v.x, v.y); };
  e[0] = pk(grp<SEC, 5 * PR, 0>(a1, a2)); e[1] = pk(grp<SEC, 5 * PR, 1>(a1, a2));
  e[2] = pk(grp<SEC, 5 * PR + 1, 0>(a1, a2)); e[3] = pk(grp<SEC, 5 * PR + 1, 1>(a1, a2));
  o[0] = pk(grp<SEC, 5 * PR + 3, 0>(a1, a2)); o[1] = pk(grp<SEC, 5 * PR + 3, 1>(a1, a2));
  o[2] = pk(grp<SEC, 5 * PR + 4, 0>(a1, a2)); o[3] = pk(grp<SEC, 5 * PR + 4, 1>(a1, a2));
  const uint32_t m0 = pk(grp<SEC, 5 * PR + 2, 0>(a1, a2)), m1 = pk(grp<SEC, 5 * PR + 2, 1>(a1, a2));
  e[4] = t < 2 ? m0 : 0u; e[5] = t < 2 ? m1 : 0u;
  o[4] = t < 2 ? 0u : m0; o[5] = t < 2 ? 0u : m1;
}

struct K1Maps { CUtensorMap x, a64_1, a16_1, a64_2, a16_2, b64_1, b16_1, b64_2, b16_2; };

__device__ __forceinline__ void k1_load(const K1Maps& m, int it, uint32_t d, uint32_t b, int mt, int hg) {
  const int k0 = (it % 20) * 32;
  const bool w0 = it < 20;
  mbar_expect(b, K1_STAGE);
  tma2(d, &m.x, k0, mt * 128, b);
  tma3(d + 8192, w0 ? &m.b64_2 : &m.a64_2, hg * 80, k0, 1, b);
  tma3(d + 8192 + 8192, w0 ? &m.a64_1 : &m.b64_1, hg * 80, k0, 0, b);
  tma3(d + 20480, w0 ? &m.b16_2 : &m.a16_2, hg * 80 + 64, k0, 1, b);
  tma3(d + 20480 + 2048, w0 ? &m.a16_1 : &m.b16_1, hg * 80 + 64, k0, 0, b);
}

__global__ void __launch_bounds__(512, 1)
k1_qkv(const __grid_constant__ K1Maps maps,
       const __nv_bfloat16* __restrict__ x, const __nv_bfloat16* __restrict__ wphi, const __nv_bfloat16* __restrict__ gate_w,
       const uint8_t* __restrict__ wa, const uint8_t* __restrict__ wb, const uint8_t* __restrict__ woa, const uint8_t* __restrict__ wob) {
  extern __shared__ __align__(1024) uint8_t smem[];
  const uint32_t sb = smem_u32(smem);
  const uint32_t full = sb + K1_BAR, empty = full + 8 * K1_NST;
  const int warp = __shfl_sync(~0u, threadIdx.x >> 5, 0), lane = threadIdx.x & 31, wg = warp >> 2;
  const int bid = blockIdx.x;
#define K1MAP 3
  const int mt = K1MAP == 3 ? (bid & 3) + 4 * (bid >> 5) : K1MAP == 2 ? (bid & 1) + 2 * (bid >> 4) : K1MAP == 1 ? bid >> 3 : bid & 15;
  const int hg = K1MAP == 3 ? (bid >> 2) & 7 : K1MAP == 2 ? (bid >> 1) & 7 : K1MAP == 1 ? bid & 7 : bid >> 4;
  PROF(threadIdx.x == 0, 0, 0);
  if (threadIdx.x == 384) {
    for (int i = 0; i < K1_NST; i++) { mbar_init(full + 8 * i, 1); mbar_init(empty + 8 * i, 2); }
    asm volatile("fence.mbarrier_init.release.cluster;" ::: "memory");
    for (int it = 0; it < K1_NST; it++) k1_load(maps, it, sb + it * K1_STAGE, full + 8 * it, mt, hg);
    pdl_launch();
  }
  __syncthreads();

  if (wg == 3) {
    reg_dec<40>();
    if (warp == 12) {
      if (lane == 0) {
        for (int it = K1_NST; it < 40; it++) {
          const int s = it % K1_NST;
          mbar_wait(empty + 8 * s, ((it / K1_NST) - 1) & 1);
          k1_load(maps, it, sb + s * K1_STAGE, full + 8 * s, mt, hg);
        }
      }
    } else {
      if (bid == 0 && warp == 14) g_KVFLAG[lane] = 0;
      mbar_wait(full, 0);
      if (warp == 13 && lane == 0) { prefetch_l2(wa + (size_t)bid * 19200, 19200); prefetch_l2(wb + (size_t)bid * 19200, 19200); }
      uint2 gw[5];
#pragma unroll
      for (int i = 0; i < 5; i++) gw[i] = *(const uint2*)(gate_w + i * 128 + lane * 4);
      for (int r = warp - 13; r < 16; r += 3) {
        const int row = mt * 128 + hg * 16 + r;
        float acc = 0.f;
#pragma unroll
        for (int i = 0; i < 5; i++) {
          const uint2 xv = *(const uint2*)(x + (size_t)row * DM + i * 128 + lane * 4);
          uint32_t p0, p1;
          asm("mul.rn.bf16x2 %0, %1, %2;" : "=r"(p0) : "r"(xv.x), "r"(gw[i].x));
          asm("mul.rn.bf16x2 %0, %1, %2;" : "=r"(p1) : "r"(xv.y), "r"(gw[i].y));
          acc += (bf_lo(p0) + bf_hi(p0)) + (bf_lo(p1) + bf_hi(p1));
        }
#pragma unroll
        for (int o = 16; o; o >>= 1) acc += __shfl_xor_sync(~0u, acc, o);
        if (lane == 0) {
          const float g = bf_round(__fdividef(1.f, 1.f + __expf(-bf_round(acc))));
          g_GATE[row] = make_float2(g, bf_round(1.f - g));
        }
      }
      for (int kg = bid; kg < 160; kg += 128) {
        const uint8_t* src = kg < 80 ? woa + (size_t)kg * 10240 : wob + (size_t)(kg - 80) * 10240;
        for (int e = (warp - 13) * 32 + lane; e < 640; e += 96) {
          const int nt = e / 160, r = e % 160;
          *(uint4*)(g_WOI + (size_t)nt * 409600 + kg * 2560 + r * 16) = __ldg((const uint4*)(src + (r & 7) * 1280 + (nt * 20 + (r >> 3)) * 16));
        }
      }
    }
  } else if (wg == 2) {
    reg_dec<112>();
    const int tid = threadIdx.x - 256, t = lane & 3;
    for (int e = tid; e < 4 * 768; e += 128) {
      const int i = e / 768, r = e % 768, kg = r / 192, nc = (r % 192) / 64, kr = (r % 64) / 8, ne = r % 8;
      const int slot = kg * 8 + kr, n = nc * 8 + ne;
      int d = -1;
      if (i & 1) { if (slot < 16) d = slot + 4; else if (slot >= 20 && slot < 24) d = slot - 20; }
      else if (slot < 20) d = slot;
      const int f = n < 20 ? n : n - 4;
      const unsigned short val = d >= 0 ? *(const unsigned short*)(wphi + ((size_t)(hg * 4 + i) * 20 + d) * 20 + f) : (unsigned short)0;
      *(unsigned short*)(smem + K1_WPH + e * 2) = val;
    }
    fence_async_smem();
    bar_sync(1, 384);
    const uint32_t stg = sb + K1_STG, wph = sb + K1_WPH;
    if (tid < 8 && !NOKV) {
      bulk_s2g(g_QKVB + (size_t)((1 + (tid >> 2)) * NH + hg * 4 + (tid & 3)) * IMG_HEAD + (size_t)mt * 6144, stg + tid * 6144, 6144);
      asm volatile("cp.async.bulk.commit_group;" ::: "memory");
    }
    float pa0[12], pa1[12], pb0[12], pb1[12];
    issue_pq(pa0, pa1, stg + 8 * 6144, wph);
    wg_wait<0>();
    pin(pa0); pin(pa1);
#pragma unroll 1
    for (int i = 0; i < 4; i += 2) {
      uint4* dst = g_PHIQ + ((size_t)((hg * 4 + i) * 32 + mt * 2) * 3) * 128 + tid;
      issue_pq(pb0, pb1, stg + (9 + i) * 6144, wph + (i + 1) * 1536);
      phi_q_store(pa0, pa1, dst, t);
      wg_wait<0>();
      pin(pb0); pin(pb1);
      issue_pq(pa0, pa1, stg + (8 + ((i + 2) & 3)) * 6144, wph + ((i + 2) & 3) * 1536);
      phi_q_store(pb0, pb1, dst + 32 * 3 * 128, t);
      wg_wait<0>();
      pin(pa0); pin(pa1);
    }
    if (tid < 8) asm volatile("cp.async.bulk.wait_group 0;" ::: "memory");
    bar_arrive(2, 384);
    PROF(tid == 0, 0, 6);
  } else {
    reg_inc<176>();
    const int w4 = warp & 3, t = lane & 3;
    const uint32_t arow = wg * 4096 + (w4 * 16 + (lane & 15)) * 64, asw = (lane >> 1) & 3, ahi = lane >> 4;
    const int rg = wg * 8 + w4 * 2, mi = lane >> 3;
    const uint32_t stg = sb + K1_STG;
    const uint32_t sbase = stg + (rg + (mi & 1)) * 384 + (lane & 7) * 16;
    const uint32_t ad01 = sbase + (mi >> 1) * 128, ad2 = sbase + (mi >> 1) * 6144 + 256;
    float a1[96], a2[24];
    float nrm[4];
#pragma unroll 1
    for (int tile = 0; tile < 2; tile++) {
#pragma unroll 1
      for (int ks = 0; ks < 20; ks += 2) {
        uint32_t fa[2][4], fb[2][4];
#pragma unroll
        for (int u = 0; u < 2; u++) {
          const int it = tile * 20 + ks + u, s = it % K1_NST;
          mbar_wait(full + 8 * s, (it / K1_NST) & 1);
          PROF(threadIdx.x == 0 && it == 0, 0, 1);
          const uint32_t st = sb + s * K1_STAGE;
          uint32_t(&f)[2][4] = u ? fb : fa;
          ldsm4(f[0], st + arow + ((ahi ^ asw) << 4));
          ldsm4(f[1], st + arow + (((2 + ahi) ^ asw) << 4));
          const uint64_t b1 = mkdesc(st + 8192, 4096, 1024, 1);
          const uint64_t b2 = mkdesc(st + 20480, 1024, 256, 3);
          wg_fence();
#pragma unroll
          for (int kk = 0; kk < 2; kk++) {
            mma_n192_rs_tb(a1, f[kk][0], f[kk][1], f[kk][2], f[kk][3], b1 + kk * 128, ks | u | kk);
            mma_n48_rs_tb(a2, f[kk][0], f[kk][1], f[kk][2], f[kk][3], b2 + kk * 32, ks | u | kk);
          }
          wg_commit();
          wg_wait<1>();
          if ((ks | u) && (threadIdx.x & 127) == 0) mbar_arrive(empty + 8 * ((it - 1) % K1_NST));
        }
      }
      wg_wait<0>();
      pin(a1); pin(a2);
      PROF(threadIdx.x == 0, 0, 2 + 2 * tile);
      if ((threadIdx.x & 127) == 0) mbar_arrive(empty + 8 * ((tile * 20 + 19) % K1_NST));
      if (tile == 0) {
        const bool p0 = (POLY_MASK >> rg) & 1, p1 = (POLY_MASK >> (rg + 1)) & 1;
        const uint32_t kp = (t & 1) ? 0u : (BF_ONE | (BF_MAGIC << 16)), km = (t & 1) ? BF_MU_LO : (BF_ONE | (BF_MU_HI << 16));
        const uint32_t vp = (t & 1) ? 0u : (BF_ONE | 0x8000u), vm = (t & 1) ? 0u : BF_ONE;
        stage_pair<0, 0, true>(a1, a2, 1.f, 1.f, p0 ? kp : km, p1 ? kp : km, ad01, ad2, 6144, t, nrm);
        stage_pair<0, 1, true>(a1, a2, 1.f, 1.f, p0 ? kp : km, p1 ? kp : km, ad01, ad2, 6144, t, nrm);
        stage_pair<1, 0, false>(a1, a2, p0 ? -1.f : 1.f, p1 ? -1.f : 1.f, p0 ? vp : vm, p1 ? vp : vm, ad01, ad2, 6144, t, nrm);
        stage_pair<1, 1, false>(a1, a2, p0 ? -1.f : 1.f, p1 ? -1.f : 1.f, p0 ? vp : vm, p1 ? vp : vm, ad01, ad2, 6144, t, nrm);
        stage_pair<2, 0, false>(a1, a2, 1.f, 1.f, 0u, 0u, ad01, ad2, 6144, t, nrm);
        stage_pair<2, 1, false>(a1, a2, 1.f, 1.f, 0u, 0u, ad01, ad2, 6144, t, nrm);
        fence_async_smem();
        bar_arrive(1, 384);
#pragma unroll
        for (int i = 0; i < 4; i++) {
          const uint32_t m = __reduce_max_sync(~0u, __float_as_uint(nrm[i]));
          if (lane == i) g_KMAX[(hg * 4 + i) * 128 + mt * 8 + wg * 4 + w4] = __uint_as_float(m);
        }
        PROF(threadIdx.x == 0, 0, 3);
      }
    }
    bar_sync(2, 384);
    const uint32_t one = (t & 1) ? 0u : BF_ONE;
    stage_pair<2, 0, false>(a1, a2, QSCALE, QSCALE, 0u, 0u, ad01, ad2, 6144, t, nrm);
    stage_pair<2, 1, false>(a1, a2, QSCALE, QSCALE, 0u, 0u, ad01, ad2, 6144, t, nrm);
    fence_async_smem();
    bar_sync(3 + wg, 128);
    if (w4 == 0 && lane < 4) {
      bulk_s2g(g_QKVB + (size_t)(hg * 4 + lane) * IMG_HEAD + (size_t)(mt * 2 + wg) * 3072, stg + (8 + lane) * 6144 + wg * 3072, 3072);
      asm volatile("cp.async.bulk.commit_group;" ::: "memory");
    }
    stage_pair<1, 0, false>(a1, a2, 1.f, 1.f, one, one, ad01, ad2, 6144, t, nrm);
    stage_pair<1, 1, false>(a1, a2, 1.f, 1.f, one, one, ad01, ad2, 6144, t, nrm);
    uint32_t fk[4][6];
    frag_pair<0, 0>(a1, a2, fk[0], fk[1], t);
    frag_pair<0, 1>(a1, a2, fk[2], fk[3], t);
    float pk[4][12];
    wg_fence();
#pragma unroll
    for (int i = 0; i < 4; i++) {
      const uint64_t wd = mkdesc(sb + K1_WPH + i * 1536, 384, 128, 0);
      mma_n24_rs_tb(pk[i], fk[i][0], fk[i][1], fk[i][2], fk[i][3], wd, 0);
      mma_n24_rs_tb(pk[i], fk[i][4], fk[i][5], 0u, 0u, wd + 48, 1);
    }
    wg_commit();
    PROF(threadIdx.x == 0, 0, 7);
    mbar_wait(empty + 8 * (38 % K1_NST), (38 / K1_NST) & 1);
    wg_wait<0>();
    const uint32_t pka = sb + (rg + ((lane >> 3) & 1)) * 768 + (lane >> 4) * 128 + (lane & 7) * 16;
#pragma unroll
    for (int i = 0; i < 4; i++) {
      pin(pk[i]);
      uint32_t f[12];
      hedgehog(pk[i], f, t);
#pragma unroll
      for (int ks = 0; ks < 3; ks++) stsm4(pka + i * 12288 + ks * 256, f[4 * ks], f[4 * ks + 1], f[4 * ks + 2], f[4 * ks + 3]);
    }
    fence_async_smem();
    bar_sync(5, 256);
    float kv[2][12];
    wg_fence();
#pragma unroll
    for (int j = 0; j < 2; j++) {
      const uint64_t ad = mkdesc(sb + (wg * 2 + j) * 12288, 768, 128, 0), vd = mkdesc(stg + (4 + wg * 2 + j) * 6144, 384, 128, 0);
#pragma unroll
      for (int ks = 0; ks < 8; ks++) mma_n24_ss_tatb(kv[j], ad + ks * 96, vd + ks * 48, ks);
    }
    wg_commit();
    wg_wait<0>();
    if (w4 < 3) {
#pragma unroll
      for (int j = 0; j < 2; j++) {
        pin(kv[j]);
        float4* dst = g_KVP + (size_t)((hg * 4 + wg * 2 + j) * 16 + mt) * 288 + w4 * 96 + lane;
        dst[0] = make_float4(kv[j][0], kv[j][1], kv[j][2], kv[j][3]);
        dst[32] = make_float4(kv[j][4], kv[j][5], kv[j][6], kv[j][7]);
        dst[64] = make_float4(kv[j][8], kv[j][9], kv[j][10], kv[j][11]);
      }
    }
    if (w4 == 0 && lane < 4) asm volatile("cp.async.bulk.wait_group 0;" ::: "memory");
    PROF(threadIdx.x == 0, 0, 5);
  }
}

constexpr int K2_K = 0, K2_V = IMG_HEAD, K2_Q = 2 * IMG_HEAD, K2_KV = K2_Q + 8 * 3072, K2_BAR = K2_KV + 2 * 2304, K2_SMEM = K2_BAR + 128;

__device__ __forceinline__ uint32_t exp2_bits(float y0, float y1, uint32_t cm, uint32_t neg1) {
  uint32_t w, m, r;
  asm("prmt.b32 %0, %1, %2, 0x6521;" : "=r"(w) : "r"(__float_as_uint(y0)), "r"(__float_as_uint(y1)));
  asm("lop3.b32 %0, %1, 0x007F007F, %2, 0xEA;" : "=r"(m) : "r"(w), "r"(cm));
  const uint32_t e = m * neg1 + w;
  asm("fma.rn.bf16x2 %0, %1, %2, %3;" : "=r"(r) : "r"(w), "r"(m), "r"(e));
  return r;
}
__device__ __forceinline__ void exp_tile(const float (&s)[64], uint32_t (&p)[32], uint32_t cm, uint32_t neg1) {
#pragma unroll
  for (int g = 0; g < 16; g++) {
    if ((POLY_MASK >> g) & 1) {
      p[2 * g] = exp2_bits(s[4 * g], s[4 * g + 1], cm, neg1);
      p[2 * g + 1] = exp2_bits(s[4 * g + 2], s[4 * g + 3], cm, neg1);
    } else {
      p[2 * g] = packbf(ex2(s[4 * g]), ex2(s[4 * g + 1]));
      p[2 * g + 1] = packbf(ex2(s[4 * g + 2]), ex2(s[4 * g + 3]));
    }
  }
}
__device__ __forceinline__ void issue_qk(float (&s)[64], uint64_t qd, uint64_t kd) {
  mma_n128_ss(s, qd, kd, 0);
  mma_n128_ss(s, (qd + 16) & ~(0x3FFFull << 16), (kd + 16) & ~(0x3FFFull << 16), 1);
}
__device__ __forceinline__ void issue_pv(float (&o)[12], const uint32_t (&p)[32], uint64_t vd, int acc) {
#pragma unroll
  for (int kk = 0; kk < 8; kk++) mma_n24_rs_tb(o, p[4 * kk], p[4 * kk + 1], p[4 * kk + 2], p[4 * kk + 3], vd + kk * 48, acc | kk);
}
__device__ __forceinline__ void attn_pair(float (&s0)[64], float (&s1)[64], uint32_t (&p0)[32], uint32_t (&p1)[32], float (&o)[12],
                                          uint64_t qd1, uint64_t kd1, uint64_t qd2, uint64_t kd2, uint64_t vd, int acc, uint32_t bar,
                                          uint32_t cm, uint32_t neg1) {
  wg_fence();
  issue_qk(s1, qd1, kd1);
  wg_commit();
  exp_tile(s0, p0, cm, neg1);
  wg_fence();
  issue_pv(o, p0, vd, acc);
  wg_commit();
  wg_wait<1>();
  pin(s1);
  mbar_wait_u(bar, 0);
  wg_fence();
  issue_qk(s0, qd2, kd2);
  wg_commit();
  exp_tile(s1, p1, cm, neg1);
  wg_fence();
  issue_pv(o, p1, vd + 384, 1);
  wg_commit();
}
__device__ __forceinline__ void store_o(const float (&o)[12], int odd, int lane, int m16, int colgrp, float eps, float s0, float s1) {
  const int src = (lane & ~3) | (odd ? 0 : 2);
  const float l0 = __shfl_sync(~0u, o[8], src) + eps, l1 = __shfl_sync(~0u, o[10], src) + eps;
  const float r0 = s0 * rcp(l0), r1 = s1 * rcp(l1);
  const int g0 = colgrp + (odd ? 3 : 0), g1 = g0 + 1, g2 = colgrp + 2;
  uint8_t* base = g_OAB + (size_t)(m16 >> 3) * (20 * 16384) + (m16 & 7) * 2048 + lane * 4;
  uint8_t* c0 = base + (g0 >> 3) * 16384 + (g0 & 7) * 128;
  uint8_t* c1 = base + (g1 >> 3) * 16384 + (g1 & 7) * 128;
  uint8_t* c2 = base + (g2 >> 3) * 16384 + (g2 & 7) * 128;
  *(uint32_t*)c0 = packbf(o[0] * r0, o[1] * r0); *(uint32_t*)(c0 + 1024) = packbf(o[2] * r1, o[3] * r1);
  *(uint32_t*)c1 = packbf(o[4] * r0, o[5] * r0); *(uint32_t*)(c1 + 1024) = packbf(o[6] * r1, o[7] * r1);
  if (((lane & 3) < 2) != (odd != 0)) { *(uint32_t*)c2 = packbf(o[8] * r0, o[9] * r0); *(uint32_t*)(c2 + 1024) = packbf(o[10] * r1, o[11] * r1); }
}

__device__ __forceinline__ void linear_readout(uint32_t kvs, int h, int mt0, int wg, int w4, int lane, int row_g, int colgrp) {
  const int tid = w4 * 32 + lane;
  uint4 f[4][3];
  float g[4][2];
#pragma unroll
  for (int p = 0; p < 4; p++) {
    const uint4* src = g_PHIQ + ((size_t)(h * 32 + mt0 + p) * 3) * 128 + tid;
    f[p][0] = ldg_cg4(src); f[p][1] = ldg_cg4(src + 128); f[p][2] = ldg_cg4(src + 256);
    g[p][0] = g_GATE[row_g + p * 64].x; g[p][1] = g_GATE[row_g + p * 64 + 8].x;
  }
#pragma unroll 1
  for (int n = 0; n < 20000000; n++) {
    uint32_t v;
    asm volatile("ld.acquire.gpu.global.u32 %0, [%1];" : "=r"(v) : "l"(g_KVFLAG + (h >> 3)) : "memory");
    if (__all_sync(~0u, v != 0)) break;
  }
  const uint8_t* kvg = g_KVB + h * 2304;
  const uint4 k0 = ldg_cg4(kvg + tid * 16), k1 = ldg_cg4(kvg + 2048 + (tid & 15) * 16);
  asm volatile("st.shared.v4.b32 [%0], {%1,%2,%3,%4};" ::"r"(kvs + tid * 16), "r"(k0.x), "r"(k0.y), "r"(k0.z), "r"(k0.w) : "memory");
  asm volatile("st.shared.v4.b32 [%0], {%1,%2,%3,%4};" ::"r"(kvs + 2048 + (tid & 15) * 16), "r"(k1.x), "r"(k1.y), "r"(k1.z), "r"(k1.w) : "memory");
  fence_async_smem();
  bar_sync(1 + wg, 128);
  const uint64_t kvd = mkdesc(kvs, 384, 128, 0);
  float oa[4][12];
#pragma unroll
  for (int p = 0; p < 4; p++)
#pragma unroll
    for (int ks = 0; ks < 3; ks++) asm volatile("" : "+r"(f[p][ks].x), "+r"(f[p][ks].y), "+r"(f[p][ks].z), "+r"(f[p][ks].w)::"memory");
  wg_fence();
#pragma unroll
  for (int p = 0; p < 4; p++)
#pragma unroll
    for (int ks = 0; ks < 3; ks++) mma_n24_rs_tb(oa[p], f[p][ks].x, f[p][ks].y, f[p][ks].z, f[p][ks].w, kvd + ks * 48, ks);
  wg_commit();
  wg_wait<0>();
#pragma unroll
  for (int p = 0; p < 4; p++) {
    pin(oa[p]);
    store_o(oa[p], h & 1, lane, (mt0 + p) * 4 + w4, colgrp, 1e-6f, g[p][0], g[p][1]);
  }
}

__global__ void __launch_bounds__(256, 1) k2_attn(uint32_t cm, uint32_t neg1) {
  extern __shared__ __align__(1024) uint8_t smem[];
  const uint32_t sb = smem_u32(smem);
  const int tid = threadIdx.x, lane = tid & 31;
  const int warp = __shfl_sync(~0u, tid >> 5, 0), wg = warp >> 2, w4 = warp & 3, t = lane & 3;
  PROF(tid == 0, 1, 0);
  if (blockIdx.x < 4) {
    pdl_wait();
    if (tid == 0) pdl_launch();
#pragma unroll 1
    for (int e0 = tid; e0 < 8 * 288; e0 += 256) {
      const int h = blockIdx.x * 8 + e0 / 288, e = e0 % 288;
      const float4* src = g_KVP + (size_t)h * 16 * 288 + e;
      uint4 v[16];
#pragma unroll
      for (int m = 0; m < 16; m++) v[m] = ldg_cg4(src + m * 288);
      float4 acc = make_float4(0.f, 0.f, 0.f, 0.f);
#pragma unroll
      for (int m = 0; m < 16; m++) {
        acc.x += __uint_as_float(v[m].x); acc.y += __uint_as_float(v[m].y); acc.z += __uint_as_float(v[m].z); acc.w += __uint_as_float(v[m].w);
      }
      uint8_t* dst = g_KVB + h * 2304 + (e / 96) * 768 + ((e % 96) >> 5) * 128 + (e & 31) * 4;
      *(uint32_t*)dst = packbf(acc.x, acc.y);
      *(uint32_t*)(dst + 384) = packbf(acc.z, acc.w);
    }
    __threadfence();
    __syncthreads();
    if (tid == 0) asm volatile("st.release.gpu.global.u32 [%0], %1;" ::"l"(g_KVFLAG + blockIdx.x), "r"(1u) : "memory");
    PROF(tid == 0, 1, 7);
    return;
  }
  const int cb = blockIdx.x - 4, h = cb >> 2, quarter = cb & 3, odd = h & 1;
  const uint32_t bar = sb + K2_BAR;
  const uint8_t* gq = g_QKVB + (size_t)h * IMG_HEAD;
  const uint8_t* gk = gq + (size_t)NH * IMG_HEAD;
  const uint8_t* gv = gk + (size_t)NH * IMG_HEAD;
  if (tid == 0) {
    for (int i = 0; i < 8; i++) mbar_init(bar + 8 * i, 1);
    asm volatile("fence.mbarrier_init.release.cluster;" ::: "memory");
  }
  pdl_wait();
  PROF(tid == 0, 1, 1);
  if (tid == 0) {
    pdl_launch();
    mbar_expect(bar, 24576);
    bulk_g2s(sb + K2_K, gk, 12288, bar);
    bulk_g2s(sb + K2_V, gv, 12288, bar);
  }
  const int mt0 = quarter * 8 + wg * 4;
  uint32_t q[4][6];
#pragma unroll
  for (int p = 0; p < 4; p++) {
    const uint8_t* src = gq + (size_t)((mt0 + p) * 8 + w4 * 2) * 384 + lane * 4;
#pragma unroll
    for (int c = 0; c < 3; c++) { q[p][2 * c] = ldg_cg(src + c * 128); q[p][2 * c + 1] = ldg_cg(src + 384 + c * 128); }
  }
  const uint4 km4 = ldg_cg4(g_KMAX + h * 128 + lane * 4);
  const float kmax = sqrt_ap(__uint_as_float(__reduce_max_sync(~0u, max(max(km4.x, km4.y), max(km4.z, km4.w))))) * 1.01f;
  if (warp == 0 && lane >= 1 && lane < 8) {
    mbar_expect(bar + 8 * lane, 24576);
    bulk_g2s(sb + K2_K + lane * 12288, gk + lane * 12288, 12288, bar + 8 * lane);
    bulk_g2s(sb + K2_V + lane * 12288, gv + lane * 12288, 12288, bar + 8 * lane);
  }
  const bool is_feat = (t < 2) != (odd != 0);
  float bnd[4][2];
  bool unsafe = false;
#pragma unroll
  for (int p = 0; p < 4; p++)
#pragma unroll
    for (int hf = 0; hf < 2; hf++) {
      float n2 = 0.f;
#pragma unroll
      for (int c = 0; c < 3; c++) { const uint32_t v = q[p][2 * c + hf]; n2 = fmaf(bf_lo(v), bf_lo(v), fmaf(bf_hi(v), bf_hi(v), n2)); }
      n2 += __shfl_xor_sync(~0u, n2, 1);
      n2 += __shfl_xor_sync(~0u, n2, 2);
      bnd[p][hf] = sqrt_ap(n2) * kmax * 1.01f;
      unsafe |= !(bnd[p][hf] <= FAST_BOUND);
    }
  const bool slow = __any_sync(~0u, __syncthreads_or(unsafe));
#pragma unroll
  for (int p = 0; p < 4; p++)
#pragma unroll
    for (int hf = 0; hf < 2; hf++) {
      const uint32_t dst = sb + K2_Q + (wg * 4 + p) * 3072 + (w4 * 2 + hf) * 384 + lane * 4;
      sts32(dst, q[p][hf]);
      sts32(dst + 128, q[p][2 + hf]);
      const uint32_t v = q[p][4 + hf];
      uint32_t c2 = packbf(bf_lo(v) * 0.5f, bf_hi(v) * 0.5f);
      if (!is_feat) c2 = slow ? 0u : ((t & 1) ? 0x3F00u : packbf(-0.5f * bnd[p][hf], 0.5f));
      sts32(dst + 256, c2);
    }
  fence_async_smem();
  bar_sync(1 + wg, 128);
  PROF(tid == 0, 1, 2);
  const int row_g = mt0 * 64 + w4 * 16 + (lane >> 2);
  const int colgrp = (h >> 1) * 5;
  const uint64_t kd0 = mkdesc(sb + K2_K, 128, 384, 0), vd0 = mkdesc(sb + K2_V, 384, 128, 0);
  const uint64_t qd0 = mkdesc(sb + K2_Q + wg * 4 * 3072, 128, 384, 0);
  float o[12], s0[64];
  mbar_wait_u(bar, 0);
  wg_fence();
  issue_qk(s0, qd0, kd0);
  wg_commit();
  wg_wait<0>();
  pin(s0);
#pragma unroll 1
  for (int pass = 0; pass < 4; pass++) {
    const uint64_t qd = qd0 + pass * 192;
    const float g0 = g_GATE[row_g + pass * 64].y, g1 = g_GATE[row_g + pass * 64 + 8].y;
    if (!slow) {
      float s1[64];
      uint32_t p0[32], p1[32];
      uint64_t kd = kd0, vd = vd0;
#pragma unroll 1
      for (int j = 0; j < 7; j++) {
        attn_pair(s0, s1, p0, p1, o, qd, kd + 384, qd, kd + 768, vd, j, bar + 8 * (j + 1), cm, neg1);
        wg_wait<1>();
        pin(s0);
        kd += 768; vd += 768;
      }
      attn_pair(s0, s1, p0, p1, o, qd, kd + 384, qd0 + ((pass + 1) & 3) * 192, kd0, vd, 1, bar, cm, neg1);
      wg_wait<0>();
      pin(s0); pin(o);
    } else {
      uint32_t p[32];
      float m0 = -INFINITY, m1 = -INFINITY;
#pragma unroll
      for (int i = 0; i < 12; i++) o[i] = 0.f;
#pragma unroll 1
      for (int j = 0; j < 16; j++) {
        mbar_wait_u(bar + 8 * (j >> 1), 0);
        wg_fence();
        issue_qk(s0, qd, kd0 + j * 384);
        wg_commit();
        wg_wait<0>();
        pin(s0);
        float n0 = m0, n1 = m1;
#pragma unroll
        for (int g = 0; g < 16; g++) { n0 = fmaxf(n0, fmaxf(s0[4 * g], s0[4 * g + 1])); n1 = fmaxf(n1, fmaxf(s0[4 * g + 2], s0[4 * g + 3])); }
        n0 = fmaxf(n0, __shfl_xor_sync(~0u, n0, 1)); n1 = fmaxf(n1, __shfl_xor_sync(~0u, n1, 1));
        n0 = fmaxf(n0, __shfl_xor_sync(~0u, n0, 2)); n1 = fmaxf(n1, __shfl_xor_sync(~0u, n1, 2));
        const float c0 = ex2(m0 - n0), c1 = ex2(m1 - n1);
        m0 = n0; m1 = n1;
#pragma unroll
        for (int i = 0; i < 3; i++) { o[4 * i] *= c0; o[4 * i + 1] *= c0; o[4 * i + 2] *= c1; o[4 * i + 3] *= c1; }
#pragma unroll
        for (int g = 0; g < 16; g++) {
          const uint32_t sg = ((POLY_MASK >> g) & 1) ? 0x80008000u : 0u;
          p[2 * g] = packbf(ex2(s0[4 * g] - m0), ex2(s0[4 * g + 1] - m0)) ^ sg;
          p[2 * g + 1] = packbf(ex2(s0[4 * g + 2] - m1), ex2(s0[4 * g + 3] - m1)) ^ sg;
        }
        wg_fence();
        issue_pv(o, p, vd0 + j * 384, 1);
        wg_commit();
        wg_wait<0>();
        pin(o);
      }
    }
    store_o(o, odd, lane, (mt0 + pass) * 4 + w4, 80 + colgrp, 0.f, g0, g1);
    PROF(tid == 0, 1, 3 + pass);
    if (pass == 1 + wg) linear_readout(sb + K2_KV + wg * 2304, h, mt0, wg, w4, lane, row_g, colgrp);
  }
  PROF(tid == 0, 1, 7);
}

constexpr int K3_STAGE = 36864, K3_NST = 5, K3_XCH = K3_NST * K3_STAGE, K3_BAR = K3_XCH + 40960, K3_SMEM = K3_BAR + 128;

__global__ void __cluster_dims__(2, 1, 1) __launch_bounds__(288, 1) k3_out(const __grid_constant__ CUtensorMap mout) {
  extern __shared__ __align__(1024) uint8_t smem[];
  const uint32_t sb = smem_u32(smem);
  const uint32_t full = sb + K3_BAR, empty = full + 8 * K3_NST;
  const int warp = __shfl_sync(~0u, threadIdx.x >> 5, 0), lane = threadIdx.x & 31, wg = warp >> 2, w4 = warp & 3;
  const int bid = blockIdx.x, half = bid & 1, nt = (bid >> 1) & 3, mt = bid >> 3;
  PROF(threadIdx.x == 0, 2, 0);
  const uint8_t* ga = g_OAB + (size_t)(mt * 20 + half * 10) * 16384;
  const uint8_t* gb = g_WOI + (size_t)nt * 409600 + half * 204800;
  if (threadIdx.x == 256) {
    for (int i = 0; i < K3_NST; i++) { mbar_init(full + 8 * i, 1); mbar_init(empty + 8 * i, 2); }
    asm volatile("fence.mbarrier_init.release.cluster;" ::: "memory");
    for (int i = 0; i < K3_NST; i++) {
      mbar_expect(full + 8 * i, K3_STAGE);
      bulk_g2s(sb + i * K3_STAGE + 16384, gb + i * 20480, 20480, full + 8 * i);
    }
  }
  __syncthreads();
  asm volatile("barrier.cluster.arrive.relaxed.aligned;" ::: "memory");
  if (warp == 8) {
    if (lane == 0) {
      pdl_wait();
      PROF(true, 2, 1);
      fence_async_all();
      for (int i = 0; i < K3_NST; i++) bulk_g2s(sb + i * K3_STAGE, ga + i * 16384, 16384, full + 8 * i);
      for (int it = K3_NST; it < 10; it++) {
        const int s = it - K3_NST;
        mbar_wait(empty + 8 * s, 0);
        mbar_expect(full + 8 * s, K3_STAGE);
        bulk_g2s(sb + s * K3_STAGE, ga + it * 16384, 16384, full + 8 * s);
        bulk_g2s(sb + s * K3_STAGE + 16384, gb + it * 20480, 20480, full + 8 * s);
      }
    }
    __syncwarp();
    asm volatile("barrier.cluster.wait.aligned;" ::: "memory");
    asm volatile("barrier.cluster.arrive.release.aligned;" ::: "memory");
    asm volatile("barrier.cluster.wait.acquire.aligned;" ::: "memory");
  } else {
    float acc[80];
#pragma unroll 1
    for (int it = 0; it < 10; it++) {
      const int s = it % K3_NST;
      mbar_wait_u(full + 8 * s, it / K3_NST);
      PROF(threadIdx.x == 0 && it == 0, 2, 2);
      const uint32_t st = sb + s * K3_STAGE;
      const uint64_t ad = mkdesc(st + wg * 8192, 128, 1024, 0), bd = mkdesc(st + 16384, 2560, 128, 0);
      wg_fence();
#pragma unroll
      for (int kk = 0; kk < 4; kk++) mma_n160_ss_tb(acc, ad + kk * 16, bd + kk * 320, it | kk);
      wg_commit();
      wg_wait<1>();
      if (it > 0 && (threadIdx.x & 127) == 0) mbar_arrive(empty + 8 * ((it - 1) % K3_NST));
    }
    wg_wait<0>();
    pin(acc);
    PROF(threadIdx.x == 0, 2, 3);
    asm volatile("barrier.cluster.wait.aligned;" ::: "memory");
    uint32_t remote;
    asm volatile("mapa.shared::cluster.u32 %0, %1, %2;" : "=r"(remote) : "r"(sb + K3_XCH + threadIdx.x * 16), "r"(half ^ 1));
#pragma unroll
    for (int j = 0; j < 5; j++) {
      uint32_t v[4];
#pragma unroll
      for (int u = 0; u < 4; u++) v[u] = half ? packbf(acc[8 * j + 2 * u], acc[8 * j + 2 * u + 1]) : packbf(acc[40 + 8 * j + 2 * u], acc[41 + 8 * j + 2 * u]);
      asm volatile("st.shared::cluster.v4.b32 [%0], {%1,%2,%3,%4};" ::"r"(remote + j * 4096), "r"(v[0]), "r"(v[1]), "r"(v[2]), "r"(v[3]) : "memory");
    }
    asm volatile("barrier.cluster.arrive.release.aligned;" ::: "memory");
    asm volatile("barrier.cluster.wait.acquire.aligned;" ::: "memory");
    PROF(threadIdx.x == 0, 2, 5);
    const uint32_t ob = sb + K3_XCH + 20480 + wg * 10240;
    const uint32_t oa = ob + (w4 * 16 + (lane & 15)) * 160 + (lane >> 4) * 16;
    uint32_t pk[20];
#pragma unroll
    for (int j = 0; j < 5; j++) {
      const uint4 r = *(const uint4*)(smem + K3_XCH + j * 4096 + threadIdx.x * 16);
      const uint32_t rv[4] = {r.x, r.y, r.z, r.w};
#pragma unroll
      for (int u = 0; u < 4; u++) {
        const float v0 = half ? acc[40 + 8 * j + 2 * u] : acc[8 * j + 2 * u], v1 = half ? acc[41 + 8 * j + 2 * u] : acc[8 * j + 2 * u + 1];
        pk[4 * j + u] = packbf(v0 + bf_lo(rv[u]), v1 + bf_hi(rv[u]));
      }
    }
#pragma unroll
    for (int j = 0; j < 10; j += 2) stsm4(oa + j * 16, pk[2 * j], pk[2 * j + 1], pk[2 * j + 2], pk[2 * j + 3]);
    fence_async_smem();
    bar_sync(1 + wg, 128);
    PROF(threadIdx.x == 0, 2, 6);
    if ((threadIdx.x & 127) == 0) {
      asm volatile("cp.async.bulk.tensor.2d.global.shared::cta.bulk_group [%0, {%2,%3}], [%1];" ::"l"(&mout), "r"(ob), "r"(nt * 160 + half * 80),
                   "r"(mt * 128 + wg * 64) : "memory");
      asm volatile("cp.async.bulk.commit_group;" ::: "memory");
      asm volatile("cp.async.bulk.wait_group.read 0;" ::: "memory");
    }
    PROF(threadIdx.x == 0, 2, 4);
  }
}

typedef CUresult (*EncodeFn)(CUtensorMap*, CUtensorMapDataType, cuuint32_t, void*, const cuuint64_t*, const cuuint64_t*, const cuuint32_t*,
                             const cuuint32_t*, CUtensorMapInterleave, CUtensorMapSwizzle, CUtensorMapL2promotion, CUtensorMapFloatOOBfill);

void encode(EncodeFn fn, CUtensorMap* m, const void* p, int rank, const cuuint64_t* dims, const cuuint64_t* strides, const cuuint32_t* box,
            CUtensorMapSwizzle sw) {
  const cuuint32_t es[3] = {1, 1, 1};
  fn(m, CU_TENSOR_MAP_DATA_TYPE_BFLOAT16, rank, const_cast<void*>(p), dims, strides, box, es, CU_TENSOR_MAP_INTERLEAVE_NONE, sw,
     CU_TENSOR_MAP_L2_PROMOTION_L2_128B, CU_TENSOR_MAP_FLOAT_OOB_FILL_NONE);
}

}

extern "C" void kernel_launch(void* const* d_in, const int* in_sizes, int n_in, void* d_out, int out_size) {
  (void)in_sizes; (void)n_in; (void)out_size;
  const __nv_bfloat16* x = (const __nv_bfloat16*)d_in[0];
  const void* wa = d_in[1];
  const __nv_bfloat16* wphi = (const __nv_bfloat16*)d_in[2];
  const void* woa = d_in[3];
  const void* wb = d_in[5];
  const void* wob = d_in[6];
  const __nv_bfloat16* gate_w = (const __nv_bfloat16*)d_in[7];

  static EncodeFn enc = nullptr;
  if (!enc) {
    void* fn = nullptr;
    cudaDriverEntryPointQueryResult qr;
    cudaGetDriverEntryPoint("cuTensorMapEncodeTiled", &fn, cudaEnableDefault, &qr);
    enc = (EncodeFn)fn;
    cudaFuncSetAttribute(k1_qkv, cudaFuncAttributeMaxDynamicSharedMemorySize, K1_SMEM);
    cudaFuncSetAttribute(k2_attn, cudaFuncAttributeMaxDynamicSharedMemorySize, K2_SMEM);
    cudaFuncSetAttribute(k3_out, cudaFuncAttributeMaxDynamicSharedMemorySize, K3_SMEM);
  }
  K1Maps maps;
  CUtensorMap mout;
  {
    const cuuint64_t dx[2] = {640, 2048}, sx[1] = {1280};
    const cuuint32_t bx[2] = {32, 128}, bo[2] = {80, 64};
    encode(enc, &maps.x, x, 2, dx, sx, bx, CU_TENSOR_MAP_SWIZZLE_64B);
    encode(enc, &mout, d_out, 2, dx, sx, bo, CU_TENSOR_MAP_SWIZZLE_NONE);
    const cuuint64_t dw[3] = {640, 640, 3}, sw[2] = {3840, 1280};
    const cuuint32_t b64_1[3] = {64, 32, 1}, b16_1[3] = {16, 32, 1}, b64_2[3] = {64, 32, 2}, b16_2[3] = {16, 32, 2};
    encode(enc, &maps.a64_1, wa, 3, dw, sw, b64_1, CU_TENSOR_MAP_SWIZZLE_128B);
    encode(enc, &maps.a16_1, wa, 3, dw, sw, b16_1, CU_TENSOR_MAP_SWIZZLE_32B);
    encode(enc, &maps.a64_2, wa, 3, dw, sw, b64_2, CU_TENSOR_MAP_SWIZZLE_128B);
    encode(enc, &maps.a16_2, wa, 3, dw, sw, b16_2, CU_TENSOR_MAP_SWIZZLE_32B);
    encode(enc, &maps.b64_1, wb, 3, dw, sw, b64_1, CU_TENSOR_MAP_SWIZZLE_128B);
    encode(enc, &maps.b16_1, wb, 3, dw, sw, b16_1, CU_TENSOR_MAP_SWIZZLE_32B);
    encode(enc, &maps.b64_2, wb, 3, dw, sw, b64_2, CU_TENSOR_MAP_SWIZZLE_128B);
    encode(enc, &maps.b16_2, wb, 3, dw, sw, b16_2, CU_TENSOR_MAP_SWIZZLE_32B);
  }
  cudaStream_t st = cudaStreamPerThread;
  cudaLaunchAttribute pdl[1];
  pdl[0].id = cudaLaunchAttributeProgrammaticStreamSerialization;
  pdl[0].val.programmaticStreamSerializationAllowed = 1;
  cudaLaunchConfig_t c = {};
  c.stream = st;
  c.gridDim = dim3(128); c.blockDim = dim3(512); c.dynamicSmemBytes = K1_SMEM; c.attrs = nullptr; c.numAttrs = 0;
  cudaLaunchKernelEx(&c, k1_qkv, maps, x, wphi, gate_w, (const uint8_t*)wa, (const uint8_t*)wb,
                     (const uint8_t*)woa, (const uint8_t*)wob);
  c.gridDim = dim3(132); c.blockDim = dim3(256); c.dynamicSmemBytes = K2_SMEM; c.attrs = pdl; c.numAttrs = 1;
  cudaLaunchKernelEx(&c, k2_attn, 0x1F801F80u, 0xFFFFFFFFu);
  c.gridDim = dim3(128); c.blockDim = dim3(288); c.dynamicSmemBytes = K3_SMEM;
  cudaLaunchKernelEx(&c, k3_out, mout);
}
```

```cpp
#include <cuda_runtime.h>
#include <cuda_bf16.h>
#include <cuda.h>
#include <stdint.h>

namespace {

constexpr int SEQ = 2048, DM = 640, NH = 32, NCTA = 128;
constexpr int IMG_HEAD = SEQ * 48;
#define POLY_MASK 0x76DDu
constexpr float LOG2E = 1.4426950408889634f;
constexpr float QSCALE = 0.22360679774997896f * 1.4426950408889634f;
constexpr uint32_t BF_ONE = 0x3F80u;
constexpr uint32_t BF_MAGIC = 0x43E0u;
constexpr uint32_t BF_MU_HI = 0x4025u;
constexpr uint32_t BF_MU_LO = 0x3B8Bu;
constexpr float FAST_BOUND = 40.0f;

__device__ __align__(1024) uint8_t g_KV[2 * NH * IMG_HEAD];
__device__ __align__(1024) float2 g_KVP[NH * 16 * 480];
__device__ __align__(1024) uint32_t g_KVB[NH * 480];
__device__ __align__(1024) float g_KMAX[NH * 128];
__device__ __align__(1024) float2 g_GATE[SEQ];
__device__ __align__(1024) uint8_t g_OAB[16 * 20 * 16384];
__device__ __align__(1024) uint8_t g_WOI[4 * 409600];
__device__ __align__(1024) uint32_t g_CNT[80 * 8];
constexpr int C_START = 0, C_WO = 1, C_KV = 2, C_KVP = 10, C_KVB = 18, C_GATE = 26, C_OA = 42, C_OB = 58;

#define SPIN_LIMIT (1ll << 29)
#define SPIN_FAIL(code) __trap()
#define PROF(cond, slot)
__device__ __forceinline__ uint32_t smem_u32(const void* p) { return (uint32_t)__cvta_generic_to_shared(p); }
__device__ __forceinline__ void mbar_init(uint32_t a, uint32_t c) { asm volatile("mbarrier.init.shared::cta.b64 [%0], %1;" ::"r"(a), "r"(c) : "memory"); }
__device__ __forceinline__ void mbar_expect(uint32_t a, uint32_t b) { asm volatile("mbarrier.arrive.expect_tx.shared::cta.b64 _, [%0], %1;" ::"r"(a), "r"(b) : "memory"); }
__device__ __forceinline__ void mbar_arrive(uint32_t a) { asm volatile("mbarrier.arrive.shared::cta.b64 _, [%0];" ::"r"(a) : "memory"); }
__device__ __forceinline__ uint32_t mbar_try(uint32_t a, uint32_t ph) {
  uint32_t ok;
  asm volatile("{\n.reg .pred p;\nmbarrier.try_wait.parity.shared::cta.b64 p, [%1], %2;\nselp.u32 %0, 1, 0, p;\n}\n" : "=r"(ok) : "r"(a), "r"(ph) : "memory");
  return ok;
}
__device__ __forceinline__ void mbar_wait(uint32_t a, uint32_t ph) {
  if (mbar_try(a, ph)) return;
  const long long t0 = clock64();
  while (!mbar_try(a, ph))
    if (clock64() - t0 > SPIN_LIMIT) { SPIN_FAIL(1000 + (a & 0x1FF) * 2 + ph); break; }
}
__device__ __forceinline__ void mbar_wait_u(uint32_t a, uint32_t ph) {
#pragma unroll 1
  for (int n = 0; n < (1 << 18); n++)
    if (__all_sync(~0u, mbar_try(a, ph))) break;
}
__device__ __forceinline__ uint32_t mbar_wait_z(uint32_t a, uint32_t ph) {
  uint32_t ok = 0;
#pragma unroll 1
  for (int n = 0; n < (1 << 18); n++) {
    ok = mbar_try(a, ph);
    if (__all_sync(~0u, ok)) break;
  }
  return ok - 1;
}
__device__ __forceinline__ void mbar_arrive_if(uint32_t a, uint32_t flag) {
  asm volatile("{\n.reg .pred p;\nsetp.ne.u32 p, %1, 0;\n@p mbarrier.arrive.shared::cta.b64 _, [%0];\n}\n" ::"r"(a), "r"(flag) : "memory");
}
__device__ __forceinline__ void cnt_add(int slot) {
  asm volatile("fence.acq_rel.gpu;\nred.relaxed.gpu.global.add.u32 [%0], 1;" ::"l"(g_CNT + slot * 8) : "memory");
}
__device__ __forceinline__ void cnt_wait(int slot, uint32_t target) {
  uint32_t v;
  long long t0 = 0;
  for (;;) {
    asm volatile("ld.acquire.gpu.global.u32 %0, [%1];" : "=r"(v) : "l"(g_CNT + slot * 8) : "memory");
    if ((int32_t)(v - target) >= 0) break;
    if (!t0) t0 = clock64();
    else if (clock64() - t0 > SPIN_LIMIT) { SPIN_FAIL(slot); break; }
  }
}
__device__ __forceinline__ void tma5(uint32_t dst, const CUtensorMap* m, int c0, int c4, uint32_t bar) {
  asm volatile("cp.async.bulk.tensor.5d.shared::cluster.global.mbarrier::complete_tx::bytes [%0], [%1, {%3,%5,%5,%5,%4}], [%2];" ::"r"(dst), "l"(m), "r"(bar), "r"(c0), "r"(c4), "r"(0) : "memory");
}
__device__ __forceinline__ void bulk_g2s(uint32_t dst, const void* src, uint32_t bytes, uint32_t bar) {
  asm volatile("cp.async.bulk.shared::cluster.global.mbarrier::complete_tx::bytes [%0], [%1], %2, [%3];" ::"r"(dst), "l"(src), "r"(bytes), "r"(bar) : "memory");
}
__device__ __forceinline__ void prefetch_l2(const void* src, uint32_t bytes) { asm volatile("cp.async.bulk.prefetch.L2.global [%0], %1;" ::"l"(src), "r"(bytes) : "memory"); }
__device__ __forceinline__ void fence_async_smem() { asm volatile("fence.proxy.async.shared::cta;" ::: "memory"); }
__device__ __forceinline__ void fence_async_all() { asm volatile("fence.proxy.async;" ::: "memory"); }
__device__ __forceinline__ void bar_sync(int id, int n) { asm volatile("bar.sync %0, %1;" ::"r"(id), "r"(n) : "memory"); }
__device__ __forceinline__ void bar_arrive(int id, int n) { asm volatile("bar.arrive %0, %1;" ::"r"(id), "r"(n) : "memory"); }
__device__ __forceinline__ void wg_fence() { asm volatile("wgmma.fence.sync.aligned;" ::: "memory"); }
__device__ __forceinline__ void wg_commit() { asm volatile("wgmma.commit_group.sync.aligned;" ::: "memory"); }
template <int N> __device__ __forceinline__ void wg_wait() { asm volatile("wgmma.wait_group.sync.aligned %0;" ::"n"(N) : "memory"); }
template <int N> __device__ __forceinline__ void reg_inc() { asm volatile("setmaxnreg.inc.sync.aligned.u32 %0;" ::"n"(N)); }
template <int N> __device__ __forceinline__ void reg_dec() { asm volatile("setmaxnreg.dec.sync.aligned.u32 %0;" ::"n"(N)); }
template <int N> __device__ __forceinline__ void pin(float (&r)[N]) {
#pragma unroll
  for (int i = 0; i < N; i++) asm volatile("" : "+f"(r[i])::"memory");
}
template <int N> __device__ __forceinline__ void pin(uint32_t (&r)[N]) {
#pragma unroll
  for (int i = 0; i < N; i++) asm volatile("" : "+r"(r[i])::"memory");
}
__device__ __forceinline__ uint64_t mkdesc(uint32_t addr, uint32_t lbo, uint32_t sbo, uint32_t swz) {
  return (uint64_t)((addr & 0x3FFFF) >> 4) | ((uint64_t)(lbo >> 4) << 16) | ((uint64_t)(sbo >> 4) << 32) | ((uint64_t)swz << 62);
}
__device__ __forceinline__ float ex2(float x) { float y; asm("ex2.approx.ftz.f32 %0, %1;" : "=f"(y) : "f"(x)); return y; }
__device__ __forceinline__ float rcp(float x) { float y; asm("rcp.approx.ftz.f32 %0, %1;" : "=f"(y) : "f"(x)); return y; }
__device__ __forceinline__ float sqrt_ap(float x) { float y; asm("sqrt.approx.f32 %0, %1;" : "=f"(y) : "f"(x)); return y; }
__device__ __forceinline__ uint32_t packbf(float lo, float hi) { uint32_t d; asm("cvt.rn.bf16x2.f32 %0, %1, %2;" : "=r"(d) : "f"(hi), "f"(lo)); return d; }
__device__ __forceinline__ float bf_lo(uint32_t v) { return __uint_as_float(v << 16); }
__device__ __forceinline__ float bf_hi(uint32_t v) { return __uint_as_float(v & 0xFFFF0000u); }
__device__ __forceinline__ float bf_round(float x) { return bf_lo(packbf(x, 0.f)); }
__device__ __forceinline__ uint32_t ldg_cg(const void* p) { uint32_t v; asm volatile("ld.global.cg.b32 %0, [%1];" : "=r"(v) : "l"(p) : "memory"); return v; }
__device__ __forceinline__ uint4 ldg_cg4(const void* p) { uint4 v; asm volatile("ld.global.cg.v4.b32 {%0,%1,%2,%3}, [%4];" : "=r"(v.x), "=r"(v.y), "=r"(v.z), "=r"(v.w) : "l"(p) : "memory"); return v; }
__device__ __forceinline__ void sts32(uint32_t a, uint32_t v) { asm volatile("st.shared.b32 [%0], %1;" ::"r"(a), "r"(v) : "memory"); }
__device__ __forceinline__ void stsm4(uint32_t a, uint32_t r0, uint32_t r1, uint32_t r2, uint32_t r3) {
  asm volatile("stmatrix.sync.aligned.m8n8.x4.shared.b16 [%0], {%1,%2,%3,%4};" ::"r"(a), "r"(r0), "r"(r1), "r"(r2), "r"(r3) : "memory");
}

__device__ __forceinline__ void stsm2(uint32_t a, uint32_t r0, uint32_t r1) {
  asm volatile("stmatrix.sync.aligned.m8n8.x2.shared.b16 [%0], {%1,%2};" ::"r"(a), "r"(r0), "r"(r1) : "memory");
}
__device__ __forceinline__ uint4 ldg_x(const void* p) {
  uint4 v;
  asm volatile("ld.global.nc.L1::no_allocate.L2::128B.v4.b32 {%0,%1,%2,%3}, [%4];" : "=r"(v.x), "=r"(v.y), "=r"(v.z), "=r"(v.w) : "l"(p));
  return v;
}
__device__ __forceinline__ float2 lds_f2(uint32_t a) { float2 v; asm volatile("ld.shared.v2.f32 {%0,%1}, [%2];" : "=f"(v.x), "=f"(v.y) : "r"(a) : "memory"); return v; }
__device__ __forceinline__ void bulk_s2g(void* dst, uint32_t src, uint32_t bytes) {
  asm volatile("cp.async.bulk.global.shared::cta.bulk_group [%0], [%1], %2;" ::"l"(dst), "r"(src), "r"(bytes) : "memory");
}

__device__ __forceinline__ void mma_n24_ss_tb(float (&d)[12], uint64_t adesc, uint64_t bdesc, int acc) {
  asm volatile("{\n.reg .pred p;\nsetp.ne.b32 p, %14, 0;\n"
      "wgmma.mma_async.sync.aligned.m64n24k16.f32.bf16.bf16 "
      "{%0,%1,%2,%3,%4,%5,%6,%7,%8,%9,%10,%11}, "
      "%12, %13, p, 1, 1, 0, 1;\n}\n"
      : "+f"(d[0]), "+f"(d[1]), "+f"(d[2]), "+f"(d[3]), "+f"(d[4]), "+f"(d[5]), "+f"(d[6]), "+f"(d[7]),
        "+f"(d[8]), "+f"(d[9]), "+f"(d[10]), "+f"(d[11])
      : "l"(adesc), "l"(bdesc), "r"(acc));
}
__device__ __forceinline__ void mma_n192_rs_tb(float (&d)[96], uint32_t a0, uint32_t a1, uint32_t a2, uint32_t a3, uint64_t bdesc, int acc) {
  asm volatile("{\n.reg .pred p;\nsetp.ne.b32 p, %101, 0;\n"
      "wgmma.mma_async.sync.aligned.m64n192k16.f32.bf16.bf16 "
      "{%0,%1,%2,%3,%4,%5,%6,%7,%8,%9,%10,%11,%12,%13,%14,%15,"
      "%16,%17,%18,%19,%20,%21,%22,%23,%24,%25,%26,%27,%28,%29,%30,%31,"
      "%32,%33,%34,%35,%36,%37,%38,%39,%40,%41,%42,%43,%44,%45,%46,%47,"
      "%48,%49,%50,%51,%52,%53,%54,%55,%56,%57,%58,%59,%60,%61,%62,%63,"
      "%64,%65,%66,%67,%68,%69,%70,%71,%72,%73,%74,%75,%76,%77,%78,%79,"
      "%80,%81,%82,%83,%84,%85,%86,%87,%88,%89,%90,%91,%92,%93,%94,%95}, "
      "{%96,%97,%98,%99}, %100, p, 1, 1, 1;\n}\n"
      : "+f"(d[0]), "+f"(d[1]), "+f"(d[2]), "+f"(d[3]), "+f"(d[4]), "+f"(d[5]), "+f"(d[6]), "+f"(d[7]),
        "+f"(d[8]), "+f"(d[9]), "+f"(d[10]), "+f"(d[11]), "+f"(d[12]), "+f"(d[13]), "+f"(d[14]), "+f"(d[15]),
        "+f"(d[16]), "+f"(d[17]), "+f"(d[18]), "+f"(d[19]), "+f"(d[20]), "+f"(d[21]), "+f"(d[22]), "+f"(d[23]),
        "+f"(d[24]), "+f"(d[25]), "+f"(d[26]), "+f"(d[27]), "+f"(d[28]), "+f"(d[29]), "+f"(d[30]), "+f"(d[31]),
        "+f"(d[32]), "+f"(d[33]), "+f"(d[34]), "+f"(d[35]), "+f"(d[36]), "+f"(d[37]), "+f"(d[38]), "+f"(d[39]),
        "+f"(d[40]), "+f"(d[41]), "+f"(d[42]), "+f"(d[43]), "+f"(d[44]), "+f"(d[45]), "+f"(d[46]), "+f"(d[47]),
        "+f"(d[48]), "+f"(d[49]), "+f"(d[50]), "+f"(d[51]), "+f"(d[52]), "+f"(d[53]), "+f"(d[54]), "+f"(d[55]),
        "+f"(d[56]), "+f"(d[57]), "+f"(d[58]), "+f"(d[59]), "+f"(d[60]), "+f"(d[61]), "+f"(d[62]), "+f"(d[63]),
        "+f"(d[64]), "+f"(d[65]), "+f"(d[66]), "+f"(d[67]), "+f"(d[68]), "+f"(d[69]), "+f"(d[70]), "+f"(d[71]),
        "+f"(d[72]), "+f"(d[73]), "+f"(d[74]), "+f"(d[75]), "+f"(d[76]), "+f"(d[77]), "+f"(d[78]), "+f"(d[79]),
        "+f"(d[80]), "+f"(d[81]), "+f"(d[82]), "+f"(d[83]), "+f"(d[84]), "+f"(d[85]), "+f"(d[86]), "+f"(d[87]),
        "+f"(d[88]), "+f"(d[89]), "+f"(d[90]), "+f"(d[91]), "+f"(d[92]), "+f"(d[93]), "+f"(d[94]), "+f"(d[95])
      : "r"(a0), "r"(a1), "r"(a2), "r"(a3), "l"(bdesc), "r"(acc));
}
__device__ __forceinline__ void mma_n48_rs_tb(float (&d)[24], uint32_t a0, uint32_t a1, uint32_t a2, uint32_t a3, uint64_t bdesc, int acc) {
  asm volatile("{\n.reg .pred p;\nsetp.ne.b32 p, %29, 0;\n"
      "wgmma.mma_async.sync.aligned.m64n48k16.f32.bf16.bf16 "
      "{%0,%1,%2,%3,%4,%5,%6,%7,%8,%9,%10,%11,%12,%13,%14,%15,"
      "%16,%17,%18,%19,%20,%21,%22,%23}, "
      "{%24,%25,%26,%27}, %28, p, 1, 1, 1;\n}\n"
      : "+f"(d[0]), "+f"(d[1]), "+f"(d[2]), "+f"(d[3]), "+f"(d[4]), "+f"(d[5]), "+f"(d[6]), "+f"(d[7]),
        "+f"(d[8]), "+f"(d[9]), "+f"(d[10]), "+f"(d[11]), "+f"(d[12]), "+f"(d[13]), "+f"(d[14]), "+f"(d[15]),
        "+f"(d[16]), "+f"(d[17]), "+f"(d[18]), "+f"(d[19]), "+f"(d[20]), "+f"(d[21]), "+f"(d[22]), "+f"(d[23])
      : "r"(a0), "r"(a1), "r"(a2), "r"(a3), "l"(bdesc), "r"(acc));
}
__device__ __forceinline__ void mma_n128_ss(float (&d)[64], uint64_t adesc, uint64_t bdesc, int acc) {
  asm volatile("{\n.reg .pred p;\nsetp.ne.b32 p, %66, 0;\n"
      "wgmma.mma_async.sync.aligned.m64n128k16.f32.bf16.bf16 "
      "{%0,%1,%2,%3,%4,%5,%6,%7,%8,%9,%10,%11,%12,%13,%14,%15,"
      "%16,%17,%18,%19,%20,%21,%22,%23,%24,%25,%26,%27,%28,%29,%30,%31,"
      "%32,%33,%34,%35,%36,%37,%38,%39,%40,%41,%42,%43,%44,%45,%46,%47,"
      "%48,%49,%50,%51,%52,%53,%54,%55,%56,%57,%58,%59,%60,%61,%62,%63}, "
      "%64, %65, p, 1, 1, 0, 0;\n}\n"
      : "+f"(d[0]), "+f"(d[1]), "+f"(d[2]), "+f"(d[3]), "+f"(d[4]), "+f"(d[5]), "+f"(d[6]), "+f"(d[7]),
        "+f"(d[8]), "+f"(d[9]), "+f"(d[10]), "+f"(d[11]), "+f"(d[12]), "+f"(d[13]), "+f"(d[14]), "+f"(d[15]),
        "+f"(d[16]), "+f"(d[17]), "+f"(d[18]), "+f"(d[19]), "+f"(d[20]), "+f"(d[21]), "+f"(d[22]), "+f"(d[23]),
        "+f"(d[24]), "+f"(d[25]), "+f"(d[26]), "+f"(d[27]), "+f"(d[28]), "+f"(d[29]), "+f"(d[30]), "+f"(d[31]),
        "+f"(d[32]), "+f"(d[33]), "+f"(d[34]), "+f"(d[35]), "+f"(d[36]), "+f"(d[37]), "+f"(d[38]), "+f"(d[39]),
        "+f"(d[40]), "+f"(d[41]), "+f"(d[42]), "+f"(d[43]), "+f"(d[44]), "+f"(d[45]), "+f"(d[46]), "+f"(d[47]),
        "+f"(d[48]), "+f"(d[49]), "+f"(d[50]), "+f"(d[51]), "+f"(d[52]), "+f"(d[53]), "+f"(d[54]), "+f"(d[55]),
        "+f"(d[56]), "+f"(d[57]), "+f"(d[58]), "+f"(d[59]), "+f"(d[60]), "+f"(d[61]), "+f"(d[62]), "+f"(d[63])
      : "l"(adesc), "l"(bdesc), "r"(acc));
}
__device__ __forceinline__ void mma_n160_ss_tb(float (&d)[80], uint64_t adesc, uint64_t bdesc, int acc) {
  asm volatile("{\n.reg .pred p;\nsetp.ne.b32 p, %82, 0;\n"
      "wgmma.mma_async.sync.aligned.m64n160k16.f32.bf16.bf16 "
      "{%0,%1,%2,%3,%4,%5,%6,%7,%8,%9,%10,%11,%12,%13,%14,%15,"
      "%16,%17,%18,%19,%20,%21,%22,%23,%24,%25,%26,%27,%28,%29,%30,%31,"
      "%32,%33,%34,%35,%36,%37,%38,%39,%40,%41,%42,%43,%44,%45,%46,%47,"
      "%48,%49,%50,%51,%52,%53,%54,%55,%56,%57,%58,%59,%60,%61,%62,%63,"
      "%64,%65,%66,%67,%68,%69,%70,%71,%72,%73,%74,%75,%76,%77,%78,%79}, "
      "%80, %81, p, 1, 1, 0, 1;\n}\n"
      : "+f"(d[0]), "+f"(d[1]), "+f"(d[2]), "+f"(d[3]), "+f"(d[4]), "+f"(d[5]), "+f"(d[6]), "+f"(d[7]),
        "+f"(d[8]), "+f"(d[9]), "+f"(d[10]), "+f"(d[11]), "+f"(d[12]), "+f"(d[13]), "+f"(d[14]), "+f"(d[15]),
        "+f"(d[16]), "+f"(d[17]), "+f"(d[18]), "+f"(d[19]), "+f"(d[20]), "+f"(d[21]), "+f"(d[22]), "+f"(d[23]),
        "+f"(d[24]), "+f"(d[25]), "+f"(d[26]), "+f"(d[27]), "+f"(d[28]), "+f"(d[29]), "+f"(d[30]), "+f"(d[31]),
        "+f"(d[32]), "+f"(d[33]), "+f"(d[34]), "+f"(d[35]), "+f"(d[36]), "+f"(d[37]), "+f"(d[38]), "+f"(d[39]),
        "+f"(d[40]), "+f"(d[41]), "+f"(d[42]), "+f"(d[43]), "+f"(d[44]), "+f"(d[45]), "+f"(d[46]), "+f"(d[47]),
        "+f"(d[48]), "+f"(d[49]), "+f"(d[50]), "+f"(d[51]), "+f"(d[52]), "+f"(d[53]), "+f"(d[54]), "+f"(d[55]),
        "+f"(d[56]), "+f"(d[57]), "+f"(d[58]), "+f"(d[59]), "+f"(d[60]), "+f"(d[61]), "+f"(d[62]), "+f"(d[63]),
        "+f"(d[64]), "+f"(d[65]), "+f"(d[66]), "+f"(d[67]), "+f"(d[68]), "+f"(d[69]), "+f"(d[70]), "+f"(d[71]),
        "+f"(d[72]), "+f"(d[73]), "+f"(d[74]), "+f"(d[75]), "+f"(d[76]), "+f"(d[77]), "+f"(d[78]), "+f"(d[79])
      : "l"(adesc), "l"(bdesc), "r"(acc));
}
__device__ __forceinline__ void mma_n24_rs_tb(float (&d)[12], uint32_t a0, uint32_t a1, uint32_t a2, uint32_t a3, uint64_t bdesc, int acc) {
  asm volatile("{\n.reg .pred p;\nsetp.ne.b32 p, %17, 0;\n"
      "wgmma.mma_async.sync.aligned.m64n24k16.f32.bf16.bf16 "
      "{%0,%1,%2,%3,%4,%5,%6,%7,%8,%9,%10,%11}, "
      "{%12,%13,%14,%15}, %16, p, 1, 1, 1;\n}\n"
      : "+f"(d[0]), "+f"(d[1]), "+f"(d[2]), "+f"(d[3]), "+f"(d[4]), "+f"(d[5]), "+f"(d[6]), "+f"(d[7]),
        "+f"(d[8]), "+f"(d[9]), "+f"(d[10]), "+f"(d[11])
      : "r"(a0), "r"(a1), "r"(a2), "r"(a3), "l"(bdesc), "r"(acc));
}
__device__ __forceinline__ void mma_n24_ss_tatb(float (&d)[12], uint64_t adesc, uint64_t bdesc, int acc) {
  asm volatile("{\n.reg .pred p;\nsetp.ne.b32 p, %14, 0;\n"
      "wgmma.mma_async.sync.aligned.m64n24k16.f32.bf16.bf16 "
      "{%0,%1,%2,%3,%4,%5,%6,%7,%8,%9,%10,%11}, "
      "%12, %13, p, 1, 1, 1, 1;\n}\n"
      : "+f"(d[0]), "+f"(d[1]), "+f"(d[2]), "+f"(d[3]), "+f"(d[4]), "+f"(d[5]), "+f"(d[6]), "+f"(d[7]),
        "+f"(d[8]), "+f"(d[9]), "+f"(d[10]), "+f"(d[11])
      : "l"(adesc), "l"(bdesc), "r"(acc));
}

constexpr int W_STAGE = 30720, W_NST = 5;
constexpr int KV_CHUNK = 24576, KV_NST = 6;
constexpr int O_STAGE = 36864;
constexpr int OFF_GATE = KV_NST * KV_CHUNK;
constexpr int OFF_Q = W_NST * W_STAGE;
constexpr int OFF_V = OFF_Q + 24576;
constexpr int OFF_AQ = OFF_V + 24576;
constexpr int OFF_WPH = OFF_AQ + 24576;
constexpr int OFF_BAR = OFF_WPH + 4608;
constexpr int B_WF = 0, B_WE = 40, B_KF = 80, B_KE = 128, B_OF = 176, B_OE = 216, B_RF = 256, OFF_MISC = OFF_BAR + 272;
constexpr int SMEM_BYTES = OFF_MISC + 32;
constexpr int NB_STAGED = 1, NB_FREE = 2, NB_WG = 3, NB_PHIK = 5, NB_TAIL = 6, NB_GATE = 7, NB_KVB = 9, NB_READ = 11, NB_LAST = 12, NB_HELP = 13;

template <int SEC, int J, int HF>
__device__ __forceinline__ float2 grp(const float (&a1)[96], const float (&a2)[24]) {
  if constexpr (J < 8) return make_float2(a1[(8 * SEC + J) * 4 + 2 * HF], a1[(8 * SEC + J) * 4 + 2 * HF + 1]);
  else return make_float2(a2[(2 * SEC + J - 8) * 4 + 2 * HF], a2[(2 * SEC + J - 8) * 4 + 2 * HF + 1]);
}
__device__ __forceinline__ float sq2(float2 v) { return fmaf(v.x, v.x, v.y * v.y); }
__device__ __forceinline__ uint32_t pks(float2 v, float s) { return packbf(v.x * s, v.y * s); }

template <int SEC, int PR>
__device__ __forceinline__ void norms(const float (&a1)[96], const float (&a2)[24], int t, float (&n)[2][2]) {
  const float h0 = sq2(grp<SEC, 5 * PR + 2, 0>(a1, a2)), h1 = sq2(grp<SEC, 5 * PR + 2, 1>(a1, a2));
  n[0][0] = sq2(grp<SEC, 5 * PR, 0>(a1, a2)) + sq2(grp<SEC, 5 * PR + 1, 0>(a1, a2)) + (t < 2 ? h0 : 0.f);
  n[0][1] = sq2(grp<SEC, 5 * PR, 1>(a1, a2)) + sq2(grp<SEC, 5 * PR + 1, 1>(a1, a2)) + (t < 2 ? h1 : 0.f);
  n[1][0] = sq2(grp<SEC, 5 * PR + 3, 0>(a1, a2)) + sq2(grp<SEC, 5 * PR + 4, 0>(a1, a2)) + (t < 2 ? 0.f : h0);
  n[1][1] = sq2(grp<SEC, 5 * PR + 3, 1>(a1, a2)) + sq2(grp<SEC, 5 * PR + 4, 1>(a1, a2)) + (t < 2 ? 0.f : h1);
#pragma unroll
  for (int i = 0; i < 4; i++) n[i >> 1][i & 1] += __shfl_xor_sync(~0u, n[i >> 1][i & 1], 1);
#pragma unroll
  for (int i = 0; i < 4; i++) n[i >> 1][i & 1] += __shfl_xor_sync(~0u, n[i >> 1][i & 1], 2);
}

template <int SEC, int PR>
__device__ __forceinline__ void stage_pair(const float (&a1)[96], const float (&a2)[24], float sc0, float sc1, float sm, uint32_t xe0, uint32_t xe1,
                                           uint32_t xo0, uint32_t xo1, uint32_t ad01, uint32_t ad2, int t) {
  const uint32_t off = 2 * PR * 6144;
  stsm4(ad01 + off, pks(grp<SEC, 5 * PR, 0>(a1, a2), sc0), pks(grp<SEC, 5 * PR, 1>(a1, a2), sc1), pks(grp<SEC, 5 * PR + 1, 0>(a1, a2), sc0),
        pks(grp<SEC, 5 * PR + 1, 1>(a1, a2), sc1));
  stsm4(ad01 + off + 6144, pks(grp<SEC, 5 * PR + 3, 0>(a1, a2), sc0), pks(grp<SEC, 5 * PR + 3, 1>(a1, a2), sc1),
        pks(grp<SEC, 5 * PR + 4, 0>(a1, a2), sc0), pks(grp<SEC, 5 * PR + 4, 1>(a1, a2), sc1));
  const uint32_t m0 = pks(grp<SEC, 5 * PR + 2, 0>(a1, a2), sc0 * sm), m1 = pks(grp<SEC, 5 * PR + 2, 1>(a1, a2), sc1 * sm);
  const bool lo = t < 2;
  stsm4(ad2 + off, lo ? m0 : xe0, lo ? m1 : xe1, lo ? xo0 : m0, lo ? xo1 : m1);
}
template <int SEC, int PR>
__device__ __forceinline__ void frag_pair(const float (&a1)[96], const float (&a2)[24], uint32_t (&e)[6], uint32_t (&o)[6], int t) {
  e[0] = pks(grp<SEC, 5 * PR, 0>(a1, a2), 1.f); e[1] = pks(grp<SEC, 5 * PR, 1>(a1, a2), 1.f);
  e[2] = pks(grp<SEC, 5 * PR + 1, 0>(a1, a2), 1.f); e[3] = pks(grp<SEC, 5 * PR + 1, 1>(a1, a2), 1.f);
  o[0] = pks(grp<SEC, 5 * PR + 3, 0>(a1, a2), 1.f); o[1] = pks(grp<SEC, 5 * PR + 3, 1>(a1, a2), 1.f);
  o[2] = pks(grp<SEC, 5 * PR + 4, 0>(a1, a2), 1.f); o[3] = pks(grp<SEC, 5 * PR + 4, 1>(a1, a2), 1.f);
  const uint32_t m0 = pks(grp<SEC, 5 * PR + 2, 0>(a1, a2), 1.f), m1 = pks(grp<SEC, 5 * PR + 2, 1>(a1, a2), 1.f);
  e[4] = t < 2 ? m0 : 0u; e[5] = t < 2 ? m1 : 0u;
  o[4] = t < 2 ? 0u : m0; o[5] = t < 2 ? 0u : m1;
}

__device__ __forceinline__ void hedgehog(const float (&p)[12], uint32_t (&f)[10], int t) {
  const bool lo = t < 2;
#pragma unroll
  for (int hf = 0; hf < 2; hf++) {
    const float v[6] = {p[2 * hf], p[2 * hf + 1], p[4 + 2 * hf], p[5 + 2 * hf], p[8 + 2 * hf], p[9 + 2 * hf]};
    float mx = fmaxf(fmaxf(fmaxf(v[0], v[1]), fmaxf(v[2], v[3])), fmaxf(v[4], v[5]));
    float mn = fminf(fminf(fminf(v[0], v[1]), fminf(v[2], v[3])), fminf(v[4], v[5]));
    mx = fmaxf(mx, __shfl_xor_sync(~0u, mx, 1)); mn = fminf(mn, __shfl_xor_sync(~0u, mn, 1));
    mx = fmaxf(mx, __shfl_xor_sync(~0u, mx, 2)); mn = fminf(mn, __shfl_xor_sync(~0u, mn, 2));
    const float bp = -mx * LOG2E, bn = mn * LOG2E;
    float ep[4], en[4];
#pragma unroll
    for (int i = 0; i < 4; i++) { ep[i] = ex2(fmaf(v[i], LOG2E, bp)); en[i] = ex2(fmaf(v[i], -LOG2E, bn)); }
    const float sg = lo ? LOG2E : -LOG2E, bm = lo ? bp : bn;
    const float m0 = ex2(fmaf(v[4], sg, bm)), m1 = ex2(fmaf(v[5], sg, bm)), ms = m0 + m1;
    float sp = (ep[0] + ep[1]) + (ep[2] + ep[3]) + (lo ? ms : 0.f);
    float sn = (en[0] + en[1]) + (en[2] + en[3]) + (lo ? 0.f : ms);
    sp += __shfl_xor_sync(~0u, sp, 1); sn += __shfl_xor_sync(~0u, sn, 1);
    sp += __shfl_xor_sync(~0u, sp, 2); sn += __shfl_xor_sync(~0u, sn, 2);
    const float rp = rcp(sp), rn = rcp(sn), rm = lo ? rp : rn;
    f[0 + hf] = packbf(ep[0] * rp, ep[1] * rp);
    f[2 + hf] = packbf(ep[2] * rp, ep[3] * rp);
    f[4 + hf] = packbf(m0 * rm, m1 * rm);
    f[6 + hf] = packbf(en[0] * rn, en[1] * rn);
    f[8 + hf] = packbf(en[2] * rn, en[3] * rn);
  }
}

__device__ __forceinline__ uint32_t exp2_bits(float y0, float y1, uint32_t cm, uint32_t neg1) {
  uint32_t w, m, r;
  asm("prmt.b32 %0, %1, %2, 0x6521;" : "=r"(w) : "r"(__float_as_uint(y0)), "r"(__float_as_uint(y1)));
  asm("lop3.b32 %0, %1, 0x007F007F, %2, 0xEA;" : "=r"(m) : "r"(w), "r"(cm));
  const uint32_t e = m * neg1 + w;
  asm("fma.rn.bf16x2 %0, %1, %2, %3;" : "=r"(r) : "r"(w), "r"(m), "r"(e));
  return r;
}
__device__ __forceinline__ void exp_tile(const float (&s)[64], uint32_t (&p)[32], uint32_t cm, uint32_t neg1) {
#pragma unroll
  for (int g = 0; g < 16; g++) {
    if ((POLY_MASK >> g) & 1) {
      p[2 * g] = exp2_bits(s[4 * g], s[4 * g + 1], cm, neg1);
      p[2 * g + 1] = exp2_bits(s[4 * g + 2], s[4 * g + 3], cm, neg1);
    } else {
      p[2 * g] = packbf(ex2(s[4 * g]), ex2(s[4 * g + 1]));
      p[2 * g + 1] = packbf(ex2(s[4 * g + 2]), ex2(s[4 * g + 3]));
    }
  }
}
constexpr uint64_t NO_LBO = ~(0x3FFFull << 16);
__device__ __forceinline__ void issue_qk(float (&s)[64], uint64_t qd, uint64_t kd) {
  mma_n128_ss(s, qd, kd, 0);
  mma_n128_ss(s, (qd + 16) & NO_LBO, (kd + 16) & NO_LBO, 1);
}
__device__ __forceinline__ void issue_pv(float (&o)[12], const uint32_t (&p)[32], uint64_t vd, int acc) {
#pragma unroll
  for (int kk = 0; kk < 8; kk++) mma_n24_rs_tb(o, p[4 * kk], p[4 * kk + 1], p[4 * kk + 2], p[4 * kk + 3], vd + kk * 48, acc | kk);
}
__device__ __forceinline__ void attn_pair(float (&s0)[64], float (&s1)[64], uint32_t (&p0)[32], uint32_t (&p1)[32], float (&o)[12],
                                          uint64_t qd1, uint64_t kd1, uint64_t vd, uint64_t qd2, uint64_t kd2, int acc, uint32_t full_next,
                                          uint32_t ph_next, uint32_t empty_prev, uint32_t lead, uint32_t cm, uint32_t neg1) {
  wg_fence();
  issue_qk(s1, qd1, kd1);
  wg_commit();
  exp_tile(s0, p0, cm, neg1);
  wg_fence();
  issue_pv(o, p0, vd, acc);
  wg_commit();
  wg_wait<1>();
  pin(s1); pin(p1);
  mbar_arrive_if(empty_prev, lead);
  mbar_wait_u(full_next, ph_next);
  wg_fence();
  issue_qk(s0, qd2, kd2);
  wg_commit();
  exp_tile(s1, p1, cm, neg1);
  wg_fence();
  issue_pv(o, p1, vd + 384, 1);
  wg_commit();
}
__device__ __forceinline__ void store_o(const float (&o)[12], int h, int col0, uint8_t* base, int lane, float eps, float s0, float s1) {
  const int odd = h & 1;
  const int src = (lane & ~3) | (odd ? 0 : 2);
  const float l0 = __shfl_sync(~0u, o[8], src) + eps, l1 = __shfl_sync(~0u, o[10], src) + eps;
  const float r0 = s0 * rcp(l0), r1 = s1 * rcp(l1);
  const int g2 = col0 + (h >> 1) * 5 + 2, g0 = odd ? g2 + 1 : g2 - 2, g1 = g0 + 1;
  uint8_t* c0 = base + (g0 >> 3) * 16384 + (g0 & 7) * 128;
  uint8_t* c1 = base + (g1 >> 3) * 16384 + (g1 & 7) * 128;
  uint8_t* c2 = base + (g2 >> 3) * 16384 + (g2 & 7) * 128;
  *(uint32_t*)c0 = packbf(o[0] * r0, o[1] * r0); *(uint32_t*)(c0 + 1024) = packbf(o[2] * r1, o[3] * r1);
  *(uint32_t*)c1 = packbf(o[4] * r0, o[5] * r0); *(uint32_t*)(c1 + 1024) = packbf(o[6] * r1, o[7] * r1);
  if (((lane & 3) < 2) != (odd != 0)) { *(uint32_t*)c2 = packbf(o[8] * r0, o[9] * r0); *(uint32_t*)(c2 + 1024) = packbf(o[10] * r1, o[11] * r1); }
}

struct Maps { CUtensorMap a64, a16, b64, b16, out; };

__device__ __forceinline__ void w_load(const Maps& m, int it, uint32_t d, uint32_t b, int hg) {
  const int kb = (it % 10) * 2, c = hg * 80;
  const bool w0 = it < 10;
  const CUtensorMap *p64 = w0 ? &m.b64 : &m.a64, *q64 = w0 ? &m.a64 : &m.b64, *p16 = w0 ? &m.b16 : &m.a16, *q16 = w0 ? &m.a16 : &m.b16;
  mbar_expect(b, W_STAGE);
  tma5(d, p64, 640 + c, kb, b);
  tma5(d + 8192, p64, 1280 + c, kb, b);
  tma5(d + 16384, q64, c, kb, b);
  tma5(d + 24576, p16, 640 + c + 64, kb, b);
  tma5(d + 26624, p16, 1280 + c + 64, kb, b);
  tma5(d + 28672, q16, c + 64, kb, b);
}
__device__ __forceinline__ void x_load(uint4 (&v)[4], const uint8_t* p, int it) {
  const uint8_t* q = p + (it % 10) * 128;
  v[0] = ldg_x(q); v[1] = ldg_x(q + 8 * 1280); v[2] = ldg_x(q + 64); v[3] = ldg_x(q + 8 * 1280 + 64);
}
__device__ __forceinline__ void gemm_step(float (&a1)[96], float (&a2)[24], uint4 (&xv)[4], uint32_t (&f)[4][4], uint32_t (&fp)[4][4],
                                          const uint8_t* xp, int it, int acc, uint32_t sb, uint32_t bars, uint32_t lead) {
  const int s = it % W_NST;
  const uint32_t z = mbar_wait_z(bars + B_WF + 8 * s, (it / W_NST) & 1);
  f[0][0] = xv[0].x ^ z; f[0][1] = xv[1].x ^ z; f[0][2] = xv[0].y ^ z; f[0][3] = xv[1].y ^ z;
  f[1][0] = xv[0].z ^ z; f[1][1] = xv[1].z ^ z; f[1][2] = xv[0].w ^ z; f[1][3] = xv[1].w ^ z;
  f[2][0] = xv[2].x ^ z; f[2][1] = xv[3].x ^ z; f[2][2] = xv[2].y ^ z; f[2][3] = xv[3].y ^ z;
  f[3][0] = xv[2].z ^ z; f[3][1] = xv[3].z ^ z; f[3][2] = xv[2].w ^ z; f[3][3] = xv[3].w ^ z;
#pragma unroll
  for (int i = 0; i < 4; i++) pin(f[i]);
  x_load(xv, xp, it + 2);
  const uint64_t b1 = mkdesc(sb + s * W_STAGE, 8192, 1024, 1), b2 = mkdesc(sb + s * W_STAGE + 24576, 2048, 256, 3);
  wg_fence();
#pragma unroll
  for (int kk = 0; kk < 4; kk++) {
    mma_n192_rs_tb(a1, f[kk][0], f[kk][1], f[kk][2], f[kk][3], b1 + kk * 128, acc | kk);
    mma_n48_rs_tb(a2, f[kk][0], f[kk][1], f[kk][2], f[kk][3], b2 + kk * 32, acc | kk);
  }
  wg_commit();
  wg_wait<1>();
#pragma unroll
  for (int i = 0; i < 4; i++) pin(fp[i]);
  mbar_arrive_if(bars + B_WE + 8 * ((it + W_NST - 1) % W_NST), lead && acc);
}

__global__ void __cluster_dims__(2, 1, 1) __launch_bounds__(384, 1)
fused_block(const __grid_constant__ Maps maps, const __nv_bfloat16* __restrict__ x, const __nv_bfloat16* __restrict__ wphi,
            const __nv_bfloat16* __restrict__ gate_w, const uint8_t* __restrict__ wa, const uint8_t* __restrict__ wb,
            const uint8_t* __restrict__ woa, const uint8_t* __restrict__ wob, uint32_t cm, uint32_t neg1) {
  extern __shared__ __align__(1024) uint8_t smem[];
  const uint32_t sb = smem_u32(smem), bars = sb + OFF_BAR;
  const int warp = __shfl_sync(~0u, threadIdx.x >> 5, 0), lane = threadIdx.x & 31, wg = warp >> 2;
  const int bid = blockIdx.x;
  const int mt = (bid & 3) + 4 * (bid >> 5), hg = (bid >> 2) & 7;
  const int half = bid & 1, nt = (bid >> 1) & 3, mt3 = bid >> 3;
  PROF(threadIdx.x == 0, 0);
  if (threadIdx.x == 256) {
    for (int i = 0; i < W_NST; i++) { mbar_init(bars + B_WF + 8 * i, 1); mbar_init(bars + B_WE + 8 * i, 2); }
    for (int i = 0; i < KV_NST; i++) { mbar_init(bars + B_KF + 8 * i, 1); mbar_init(bars + B_KE + 8 * i, 2); }
    for (int i = 0; i < 5; i++) { mbar_init(bars + B_OF + 8 * i, 1); mbar_init(bars + B_OE + 8 * i, 2); }
    mbar_init(bars + B_RF, 1);
    asm volatile("fence.mbarrier_init.release.cluster;" ::: "memory");
    for (int it = 0; it < W_NST; it++) w_load(maps, it, sb + it * W_STAGE, bars + B_WF + 8 * it, hg);
  }
  __syncthreads();

  if (wg == 2) {
    reg_dec<40>();
    if (threadIdx.x == 288) *(volatile uint32_t*)(smem + OFF_MISC + 16) = atomicAdd(g_CNT + C_START * 8, 1u) / NCTA + 1;
    bar_sync(NB_HELP, 128);
    const uint32_t epoch = *(volatile uint32_t*)(smem + OFF_MISC + 16);
    if (warp == 8) {
      if (lane == 0) {
        for (int it = W_NST; it < 20; it++) {
          const int s = it % W_NST;
          mbar_wait(bars + B_WE + 8 * s, ((it / W_NST) - 1) & 1);
          w_load(maps, it, sb + s * W_STAGE, bars + B_WF + 8 * s, hg);
        }
        cnt_wait(C_KV + hg, 16 * epoch);
        fence_async_all();
        for (int c = 0; c < 32; c++) {
          const int s = (c + 4) % KV_NST;
          const uint8_t* src = g_KV + (size_t)(hg * 4 + (c >> 3)) * IMG_HEAD + (c & 7) * 12288;
          mbar_wait(bars + B_KE + 8 * s, (c / KV_NST) & 1);
          mbar_expect(bars + B_KF + 8 * s, KV_CHUNK);
          bulk_g2s(sb + s * KV_CHUNK, src, 12288, bars + B_KF + 8 * s);
          bulk_g2s(sb + s * KV_CHUNK + 12288, src + (size_t)NH * IMG_HEAD, 12288, bars + B_KF + 8 * s);
        }
        cnt_wait(C_WO, NCTA * epoch);
        cnt_wait(C_OA + mt3, 8 * epoch);
        fence_async_all();
        for (int it = 0; it < 10; it++) {
          const int s = it % 5, ks = (it < 5 ? 0 : 5) + half * 5 + it;
          if (it == 0) mbar_wait(bars + B_RF, 0);
          else if (it < 3) mbar_wait(bars + B_KE + 8 * it, 1);
          else if (it < 5) mbar_wait(bars + B_KE + 8 * (it + 1), 0);
          else {
            if (it == 5) { cnt_wait(C_OB + mt3, 8 * epoch); fence_async_all(); }
            mbar_wait(bars + B_OE + 8 * s, 0);
          }
          const uint32_t d = s == 0 ? sb + OFF_V : sb + (s - 1) * O_STAGE;
          mbar_expect(bars + B_OF + 8 * s, O_STAGE);
          bulk_g2s(d, g_OAB + (size_t)(mt3 * 20 + ks) * 16384, 16384, bars + B_OF + 8 * s);
          bulk_g2s(d + 16384, g_WOI + (size_t)nt * 409600 + ks * 20480, 20480, bars + B_OF + 8 * s);
        }
      }
    } else {
      const int ht = threadIdx.x - 288;
      for (const long long t0 = clock64(); !mbar_try(bars + B_WF, 0) && clock64() - t0 < 3000;) {}
      if (ht == 0) { prefetch_l2(wa + (size_t)bid * 19200, 19200); prefetch_l2(wb + (size_t)bid * 19200, 19200); }
      {
        const int i = ht / 24, slot = ht % 24;
        int d = -1;
        if (i & 1) { if (slot < 16) d = slot + 4; else if (slot >= 20) d = slot - 20; }
        else if (slot < 20) d = slot;
        uint2 v[5] = {};
        if (d >= 0) {
#pragma unroll
          for (int u = 0; u < 5; u++) v[u] = __ldg((const uint2*)(wphi + ((hg * 4 + i) * 20 + d) * 20) + u);
        }
        uint8_t* dst = smem + OFF_WPH + i * 1152 + (slot >> 3) * 384 + (slot & 7) * 16;
        *(uint4*)dst = make_uint4(v[0].x, v[0].y, v[1].x, v[1].y);
        *(uint4*)(dst + 128) = make_uint4(v[2].x, v[2].y, v[3].x, v[3].y);
        *(uint4*)(dst + 256) = make_uint4(v[4].x, v[4].y, v[4].x, v[4].y);
      }
      fence_async_smem();
      for (int r = (ht >> 4); r < 18; r += 6) {
        const int row = mt * 128 + hg * 16 + min(r, 15), hl = lane & 15;
        uint4 xv[5];
#pragma unroll
        for (int i = 0; i < 5; i++) xv[i] = __ldg((const uint4*)(x + (size_t)row * DM + i * 128 + hl * 8));
        float acc = 0.f;
#pragma unroll
        for (int i = 0; i < 5; i++) {
          const uint4 gw = __ldg((const uint4*)(gate_w + i * 128 + hl * 8));
          const uint32_t xa[4] = {xv[i].x, xv[i].y, xv[i].z, xv[i].w}, ga[4] = {gw.x, gw.y, gw.z, gw.w};
#pragma unroll
          for (int u = 0; u < 4; u++) {
            uint32_t p;
            asm("mul.rn.bf16x2 %0, %1, %2;" : "=r"(p) : "r"(xa[u]), "r"(ga[u]));
            acc += bf_lo(p) + bf_hi(p);
          }
        }
#pragma unroll
        for (int o = 8; o; o >>= 1) acc += __shfl_xor_sync(~0u, acc, o);
        if (hl == 0 && r < 16) {
          const float g = bf_round(__fdividef(1.f, 1.f + __expf(-bf_round(acc))));
          g_GATE[row] = make_float2(g, bf_round(1.f - g));
        }
      }
      for (int kg = bid; kg < 160; kg += NCTA) {
        const uint8_t* src = (kg < 80 ? woa + (size_t)kg * 10240 : wob + (size_t)(kg - 80) * 10240) + (ht & 7) * 1280 + (ht >> 3) * 16;
        uint8_t* dst = g_WOI + kg * 2560 + (ht & 7) * 16;
        uint4 v[7];
#pragma unroll
        for (int u = 0; u < 7; u++)
          if ((ht >> 3) + u * 12 < 80) v[u] = __ldg((const uint4*)(src + u * 192));
#pragma unroll
        for (int u = 0; u < 7; u++) {
          const int c = (ht >> 3) + u * 12;
          if (c < 80) *(uint4*)(dst + (size_t)(c / 20) * 409600 + (c % 20) * 128) = v[u];
        }
      }
      bar_sync(NB_HELP, 96);
      if (ht == 0) { cnt_add(C_GATE + mt); cnt_add(C_WO); }
      if (warp == 9) {
        bar_sync(NB_STAGED, 288);
        if (lane < 8) {
          bulk_s2g(g_KV + (size_t)((lane >> 2) * NH + hg * 4 + (lane & 3)) * IMG_HEAD + (size_t)mt * 6144, sb + OFF_Q + lane * 6144, 6144);
          asm volatile("cp.async.bulk.commit_group;" ::: "memory");
          asm volatile("cp.async.bulk.wait_group 0;" ::: "memory");
          fence_async_all();
        }
        __syncwarp();
        if (lane == 0) { cnt_add(C_KV + hg); cnt_wait(C_KV + hg, 16 * epoch); }
        __syncwarp();
#pragma unroll 1
        for (int i = 0; i < 4; i++) {
          const uint4 v = ldg_cg4(g_KMAX + (hg * 4 + i) * 128 + lane * 4);
          const uint32_t m = __reduce_max_sync(~0u, max(max(v.x, v.y), max(v.z, v.w)));
          if (lane == 0) *(volatile float*)(smem + OFF_MISC + i * 4) = sqrt_ap(__uint_as_float(m)) * (QSCALE * 1.02f);
        }
      }
      bar_arrive(NB_FREE, 352);
      bar_sync(NB_TAIL, 352);
      if (ht == 0) { cnt_add(C_KVP + hg); cnt_wait(C_GATE + mt, 8 * epoch); }
      bar_sync(NB_HELP, 96);
      if (warp == 9) {
        for (int e = lane; e < 64; e += 32) *(uint4*)(smem + OFF_GATE + e * 16) = ldg_cg4(g_GATE + mt * 128 + e * 2);
        bar_arrive(NB_GATE, 160);
        bar_arrive(NB_GATE + 1, 160);
      }
      if (ht == 0) cnt_wait(C_KVP + hg, 16 * epoch);
      bar_sync(NB_HELP, 96);
      for (int e = ht; e < 120; e += 96) {
        const int idx = (hg * 4 + e / 30) * 480 + mt * 30 + e % 30;
        const float2* src = g_KVP + (size_t)(hg * 4 + e / 30) * 16 * 480 + mt * 30 + e % 30;
        float sx = 0.f, sy = 0.f;
#pragma unroll 8
        for (int m = 0; m < 16; m++) {
          float2 v;
          asm volatile("ld.global.cg.v2.f32 {%0,%1}, [%2];" : "=f"(v.x), "=f"(v.y) : "l"(src + m * 480) : "memory");
          sx += v.x; sy += v.y;
        }
        g_KVB[idx] = packbf(sx, sy);
      }
      bar_sync(NB_HELP, 96);
      if (ht == 0) { cnt_add(C_KVB + hg); cnt_wait(C_KVB + hg, 16 * epoch); }
      bar_sync(NB_HELP, 96);
      if (warp == 9) {
        for (int e = lane; e < 480; e += 32) *(uint4*)(smem + OFF_V + e * 16) = ldg_cg4(g_KVB + hg * 4 * 480 + e * 4);
        fence_async_smem();
        bar_arrive(NB_KVB, 160);
        bar_arrive(NB_KVB + 1, 160);
        bar_sync(NB_READ, 288);
        if (lane == 0) { mbar_arrive(bars + B_RF); cnt_add(C_OA + mt); }
        bar_sync(NB_LAST, 288);
        if (lane == 0) cnt_add(C_OB + mt);
      }
    }
  } else {
    reg_inc<232>();
    const int w4 = warp & 3, t = lane & 3;
    const uint32_t lead = (threadIdx.x & 127) == 0;
    const int rg = wg * 8 + w4 * 2, mi = lane >> 3;
    bool slow;
    {
      const uint32_t sbase = sb + OFF_Q + (rg + (mi & 1)) * 384 + (lane & 7) * 16;
      const uint32_t ad01 = sbase + (mi >> 1) * 128, ad2 = sbase + (mi >> 1) * 6144 + 256;
      const uint8_t* xp = (const uint8_t*)x + (size_t)(mt * 128 + wg * 64 + w4 * 16 + (lane >> 2)) * 1280 + t * 16;
      float a1[96], a2[24];
      uint4 xa[4], xb[4];
      uint32_t fa[4][4] = {}, fb[4][4] = {};
      x_load(xa, xp, 0);
      x_load(xb, xp, 1);
#pragma unroll 1
      for (int tile = 0; tile < 2; tile++) {
#pragma unroll 1
        for (int ks = 0; ks < 10; ks += 2) {
          gemm_step(a1, a2, xa, fa, fb, xp, tile * 10 + ks, ks, sb, bars, lead);
          gemm_step(a1, a2, xb, fb, fa, xp, tile * 10 + ks + 1, 1, sb, bars, lead);
        }
        wg_wait<0>();
        pin(a1); pin(a2);
#pragma unroll
        for (int i = 0; i < 4; i++) pin(fb[i]);
        PROF(threadIdx.x == 0, 2 + 2 * tile);
        if (tile == 0) {
          mbar_arrive_if(bars + B_WE + 8 * 4, lead);
          const bool p0 = (POLY_MASK >> rg) & 1, p1 = (POLY_MASK >> (rg + 1)) & 1;
          const uint32_t kp = (t & 1) ? 0u : (BF_ONE | (BF_MAGIC << 16)), km = (t & 1) ? BF_MU_LO : (BF_ONE | (BF_MU_HI << 16));
          const uint32_t vp = (t & 1) ? 0u : (BF_ONE | 0x8000u), vm = (t & 1) ? 0u : BF_ONE;
          const uint32_t k0 = p0 ? kp : km, k1 = p1 ? kp : km, v0 = p0 ? vp : vm, v1 = p1 ? vp : vm;
          const float s0 = p0 ? -1.f : 1.f, s1 = p1 ? -1.f : 1.f;
          stage_pair<0, 0>(a1, a2, 1.f, 1.f, 1.f, k0, k1, k0, k1, ad01, ad2, t);
          stage_pair<0, 1>(a1, a2, 1.f, 1.f, 1.f, k0, k1, k0, k1, ad01, ad2, t);
          stage_pair<1, 0>(a1, a2, s0, s1, 1.f, v0, v1, v0, v1, ad01 + 24576, ad2 + 24576, t);
          stage_pair<1, 1>(a1, a2, s0, s1, 1.f, v0, v1, v0, v1, ad01 + 24576, ad2 + 24576, t);
          stage_pair<2, 0>(a1, a2, 1.f, 1.f, 0.5f, 0u, 0u, 0u, 0u, ad01 + 49152, ad2 + 49152, t);
          stage_pair<2, 1>(a1, a2, 1.f, 1.f, 0.5f, 0u, 0u, 0u, 0u, ad01 + 49152, ad2 + 49152, t);
          float n0[2][2], n1[2][2];
          norms<0, 0>(a1, a2, t, n0);
          norms<0, 1>(a1, a2, t, n1);
          const uint32_t m0 = __reduce_max_sync(~0u, __float_as_uint(fmaxf(n0[0][0], n0[0][1])));
          const uint32_t m1 = __reduce_max_sync(~0u, __float_as_uint(fmaxf(n0[1][0], n0[1][1])));
          const uint32_t m2 = __reduce_max_sync(~0u, __float_as_uint(fmaxf(n1[0][0], n1[0][1])));
          const uint32_t m3 = __reduce_max_sync(~0u, __float_as_uint(fmaxf(n1[1][0], n1[1][1])));
          if (lane < 4) g_KMAX[(hg * 4 + lane) * 128 + mt * 8 + warp] = __uint_as_float(lane == 0 ? m0 : lane == 1 ? m1 : lane == 2 ? m2 : m3);
          fence_async_smem();
          bar_arrive(NB_STAGED, 288);
          PROF(threadIdx.x == 0, 3);
        }
      }
#pragma unroll
      for (int s = 2; s < KV_NST; s++) mbar_arrive_if(bars + B_KE + 8 * s, lead);
      float n0[2][2], n1[2][2];
      norms<2, 0>(a1, a2, t, n0);
      norms<2, 1>(a1, a2, t, n1);
      bar_sync(NB_FREE, 352);
      const float4 km = *(const float4*)(smem + OFF_MISC);
      const float b[4][2] = {{sqrt_ap(n0[0][0]) * km.x, sqrt_ap(n0[0][1]) * km.x}, {sqrt_ap(n0[1][0]) * km.y, sqrt_ap(n0[1][1]) * km.y},
                             {sqrt_ap(n1[0][0]) * km.z, sqrt_ap(n1[0][1]) * km.z}, {sqrt_ap(n1[1][0]) * km.w, sqrt_ap(n1[1][1]) * km.w}};
      bool unsafe = false;
#pragma unroll
      for (int i = 0; i < 8; i++) unsafe |= !(b[i >> 1][i & 1] <= FAST_BOUND);
      uint32_t any;
      asm volatile("{\n.reg .pred p, q;\nsetp.ne.u32 p, %1, 0;\nbar.red.or.pred q, %2, 128, p;\nselp.u32 %0, 1, 0, q;\n}\n"
                   : "=r"(any) : "r"((uint32_t)unsafe), "r"(NB_WG + wg) : "memory");
      slow = __any_sync(~0u, any);
      uint32_t xq[4][2];
#pragma unroll
      for (int i = 0; i < 8; i++) xq[i >> 1][i & 1] = slow ? 0u : ((t & 1) ? 0x3F00u : packbf(-0.5f * b[i >> 1][i & 1], 0.5f));
      stage_pair<2, 0>(a1, a2, QSCALE, QSCALE, 0.5f, xq[0][0], xq[0][1], xq[1][0], xq[1][1], ad01, ad2, t);
      stage_pair<2, 1>(a1, a2, QSCALE, QSCALE, 0.5f, xq[2][0], xq[2][1], xq[3][0], xq[3][1], ad01, ad2, t);
      const uint32_t one = (t & 1) ? 0u : BF_ONE;
      stage_pair<1, 0>(a1, a2, 1.f, 1.f, 1.f, one, one, one, one, ad01 + 24576, ad2 + 24576, t);
      stage_pair<1, 1>(a1, a2, 1.f, 1.f, 1.f, one, one, one, one, ad01 + 24576, ad2 + 24576, t);
      uint32_t fk[4][6];
      frag_pair<0, 0>(a1, a2, fk[0], fk[1], t);
      frag_pair<0, 1>(a1, a2, fk[2], fk[3], t);
      float pk[4][12];
      wg_fence();
#pragma unroll
      for (int i = 0; i < 4; i++) {
        const uint64_t wd = mkdesc(sb + OFF_WPH + i * 1152, 384, 128, 0);
        mma_n24_rs_tb(pk[i], fk[i][0], fk[i][1], fk[i][2], fk[i][3], wd, 0);
        mma_n24_rs_tb(pk[i], fk[i][4], fk[i][5], 0u, 0u, (wd + 48) & NO_LBO, 1);
      }
      wg_commit();
      mbar_wait_u(bars + B_WE + 8 * 1, 1);
      wg_wait<0>();
#pragma unroll
      for (int i = 0; i < 4; i++) pin(fk[i]);
      const uint32_t pka = sb + (rg + (mi & 1)) * 640 + (mi >> 1) * 128 + (lane & 7) * 16;
#pragma unroll
      for (int i = 0; i < 4; i++) {
        pin(pk[i]);
        uint32_t f[10];
        hedgehog(pk[i], f, t);
        stsm4(pka + i * 10240, f[0], f[1], f[2], f[3]);
        stsm4(pka + i * 10240 + 256, f[4], f[5], f[6], f[7]);
        stsm2(pka + i * 10240 + 512, f[8], f[9]);
      }
      fence_async_smem();
      bar_sync(NB_PHIK, 256);
      float kv[2][12];
      wg_fence();
#pragma unroll
      for (int j = 0; j < 2; j++) {
        const uint64_t ad = mkdesc(sb + (wg * 2 + j) * 10240, 640, 128, 0), vd = mkdesc(sb + OFF_V + (wg * 2 + j) * 6144, 384, 128, 0);
#pragma unroll
        for (int ks = 0; ks < 8; ks++) mma_n24_ss_tatb(kv[j], ad + ks * 80, vd + ks * 48, ks);
      }
      wg_commit();
      wg_wait<0>();
      mbar_arrive_if(bars + B_KE, lead);
      mbar_arrive_if(bars + B_KE + 8, lead);
#pragma unroll
      for (int j = 0; j < 2; j++) {
        pin(kv[j]);
        float2* dst = g_KVP + (size_t)((hg * 4 + wg * 2 + j) * 16 + mt) * 480 + w4 * 192 + lane;
        if (w4 < 3) { dst[0] = make_float2(kv[j][0], kv[j][1]); dst[32] = make_float2(kv[j][4], kv[j][5]); dst[64] = make_float2(kv[j][8], kv[j][9]); }
        if (w4 < 2) { dst[96] = make_float2(kv[j][2], kv[j][3]); dst[128] = make_float2(kv[j][6], kv[j][7]); dst[160] = make_float2(kv[j][10], kv[j][11]); }
      }
      bar_arrive(NB_TAIL, 352);
      PROF(threadIdx.x == 0, 5);
    }
    {
      uint8_t* obase = g_OAB + (size_t)mt * (20 * 16384) + rg * 1024 + lane * 4;
      const uint32_t gate = sb + OFF_GATE + (wg * 64 + w4 * 16 + (lane >> 2)) * 8;
      const uint64_t kd0 = mkdesc(sb, 128, 384, 0), vd0 = mkdesc(sb + 12288, 384, 128, 0);
      const uint64_t qd0 = mkdesc(sb + OFF_Q + wg * 3072, 128, 384, 0);
      float o[12], s0[64];
      mbar_wait_u(bars + B_KF + 8 * 4, 0);
      wg_fence();
      issue_qk(s0, qd0, kd0 + 4 * (KV_CHUNK >> 4));
      wg_commit();
      wg_wait<0>();
      pin(s0);
      int slot = 4, ph = 0;
#pragma unroll 1
      for (int pass = 0; pass < 4; pass++) {
        const uint64_t qd = qd0 + pass * 384;
        if (!slow) {
          float s1[64];
          uint32_t p0[32], p1[32] = {};
#pragma unroll 1
          for (int j = 0; j < 7; j++) {
            const int nx = slot == 5 ? 0 : slot + 1, pv = slot == 0 ? 5 : slot - 1, phn = nx == 4 ? ph ^ 1 : ph;
            attn_pair(s0, s1, p0, p1, o, qd, kd0 + slot * 1536 + 384, vd0 + slot * 1536, qd, kd0 + nx * 1536, j, bars + B_KF + 8 * nx, phn,
                      bars + B_KE + 8 * pv, lead && j, cm, neg1);
            wg_wait<1>();
            pin(s0); pin(p0);
            slot = nx; ph = phn;
          }
          const int last = pass == 3;
          const int nx = last ? slot : (slot == 5 ? 0 : slot + 1), pv = slot == 0 ? 5 : slot - 1, phn = (!last && nx == 4) ? ph ^ 1 : ph;
          attn_pair(s0, s1, p0, p1, o, qd, kd0 + slot * 1536 + 384, vd0 + slot * 1536, last ? qd : qd + 384, kd0 + nx * 1536, 1,
                    bars + B_KF + 8 * nx, phn, bars + B_KE + 8 * pv, lead, cm, neg1);
          wg_wait<0>();
          pin(s0); pin(o); pin(p0); pin(p1);
          mbar_arrive_if(bars + B_KE + 8 * slot, lead);
          slot = nx; ph = phn;
        } else {
          uint32_t p[32];
          float m0 = -INFINITY, m1 = -INFINITY;
#pragma unroll
          for (int i = 0; i < 12; i++) o[i] = 0.f;
#pragma unroll 1
          for (int j = 0; j < 16; j++) {
            mbar_wait_u(bars + B_KF + 8 * slot, ph);
            wg_fence();
            issue_qk(s0, qd, kd0 + slot * 1536 + (j & 1) * 384);
            wg_commit();
            wg_wait<0>();
            pin(s0);
            float n0 = m0, n1 = m1;
#pragma unroll
            for (int g = 0; g < 16; g++) { n0 = fmaxf(n0, fmaxf(s0[4 * g], s0[4 * g + 1])); n1 = fmaxf(n1, fmaxf(s0[4 * g + 2], s0[4 * g + 3])); }
            n0 = fmaxf(n0, __shfl_xor_sync(~0u, n0, 1)); n1 = fmaxf(n1, __shfl_xor_sync(~0u, n1, 1));
            n0 = fmaxf(n0, __shfl_xor_sync(~0u, n0, 2)); n1 = fmaxf(n1, __shfl_xor_sync(~0u, n1, 2));
            const float c0 = ex2(m0 - n0), c1 = ex2(m1 - n1);
            m0 = n0; m1 = n1;
#pragma unroll
            for (int i = 0; i < 3; i++) { o[4 * i] *= c0; o[4 * i + 1] *= c0; o[4 * i + 2] *= c1; o[4 * i + 3] *= c1; }
#pragma unroll
            for (int g = 0; g < 16; g++) {
              const uint32_t sg = ((POLY_MASK >> g) & 1) ? 0x80008000u : 0u;
              p[2 * g] = packbf(ex2(s0[4 * g] - m0), ex2(s0[4 * g + 1] - m0)) ^ sg;
              p[2 * g + 1] = packbf(ex2(s0[4 * g + 2] - m1), ex2(s0[4 * g + 3] - m1)) ^ sg;
            }
            wg_fence();
            issue_pv(o, p, vd0 + slot * 1536 + (j & 1) * 384, 1);
            wg_commit();
            wg_wait<0>();
            pin(o); pin(p);
            if (j & 1) {
              mbar_arrive_if(bars + B_KE + 8 * slot, lead);
              slot = slot == 5 ? 0 : slot + 1;
              if (slot == 4) ph ^= 1;
            }
          }
        }
        if (pass == 0) bar_sync(NB_GATE + wg, 160);
        store_o(o, hg * 4 + pass, 80, obase, lane, 0.f, lds_f2(gate).y, lds_f2(gate + 64).y);
        PROF(threadIdx.x == 0, 6 + pass);
        if (pass == 1 + wg) {
          float pq[4][12];
          wg_fence();
#pragma unroll
          for (int i = 0; i < 4; i++) {
            const uint64_t ad = mkdesc(sb + OFF_AQ + i * 6144 + wg * 3072, 128, 384, 0), wd = mkdesc(sb + OFF_WPH + i * 1152, 384, 128, 0);
            mma_n24_ss_tb(pq[i], ad, wd, 0);
            mma_n24_ss_tb(pq[i], (ad + 16) & NO_LBO, (wd + 48) & NO_LBO, 1);
          }
          wg_commit();
          bar_sync(NB_KVB + wg, 160);
          wg_wait<0>();
          uint32_t f[4][10];
#pragma unroll
          for (int i = 0; i < 4; i++) { pin(pq[i]); hedgehog(pq[i], f[i], t); }
#pragma unroll
          for (int i = 0; i < 4; i++) pin(f[i]);
          wg_fence();
#pragma unroll
          for (int i = 0; i < 4; i++) {
            const uint64_t kvd = mkdesc(sb + OFF_V + i * 1920, 384, 128, 0);
            mma_n24_rs_tb(pq[i], f[i][0], f[i][1], f[i][2], f[i][3], kvd, 0);
            mma_n24_rs_tb(pq[i], f[i][4], f[i][5], f[i][6], f[i][7], kvd + 48, 1);
            mma_n24_rs_tb(pq[i], f[i][8], f[i][9], 0u, 0u, (kvd + 96) & NO_LBO, 1);
          }
          wg_commit();
          wg_wait<0>();
#pragma unroll
          for (int i = 0; i < 4; i++) pin(f[i]);
          const float g0 = lds_f2(gate).x, g1 = lds_f2(gate + 64).x;
#pragma unroll
          for (int i = 0; i < 4; i++) { pin(pq[i]); store_o(pq[i], hg * 4 + i, 0, obase, lane, 1e-6f, g0, g1); }
          bar_arrive(NB_READ, 288);
        }
      }
      bar_arrive(NB_LAST, 288);
    }
    {
      asm volatile("barrier.cluster.arrive.relaxed.aligned;" ::: "memory");
      float acc[80];
#pragma unroll 1
      for (int it = 0; it < 10; it++) {
        const int s = it % 5;
        mbar_wait_u(bars + B_OF + 8 * s, it / 5);
        PROF(threadIdx.x == 0 && (it == 0 || it == 5), 10 + it / 5);
        const uint32_t st = s == 0 ? sb + OFF_V : sb + (s - 1) * O_STAGE;
        const uint64_t ad = mkdesc(st + wg * 8192, 128, 1024, 0), bd = mkdesc(st + 16384, 2560, 128, 0);
        wg_fence();
#pragma unroll
        for (int kk = 0; kk < 4; kk++) mma_n160_ss_tb(acc, ad + kk * 16, bd + kk * 320, it | kk);
        wg_commit();
        wg_wait<1>();
        mbar_arrive_if(bars + B_OE + 8 * ((it + 4) % 5), lead && it);
      }
      wg_wait<0>();
      pin(acc);
      PROF(threadIdx.x == 0, 12);
      asm volatile("barrier.cluster.wait.aligned;" ::: "memory");
      uint32_t remote;
      asm volatile("mapa.shared::cluster.u32 %0, %1, %2;" : "=r"(remote) : "r"(sb + OFF_Q + threadIdx.x * 16), "r"(half ^ 1));
#pragma unroll
      for (int j = 0; j < 5; j++) {
        uint32_t v[4];
#pragma unroll
        for (int u = 0; u < 4; u++) v[u] = half ? packbf(acc[8 * j + 2 * u], acc[8 * j + 2 * u + 1]) : packbf(acc[40 + 8 * j + 2 * u], acc[41 + 8 * j + 2 * u]);
        asm volatile("st.shared::cluster.v4.b32 [%0], {%1,%2,%3,%4};" ::"r"(remote + j * 4096), "r"(v[0]), "r"(v[1]), "r"(v[2]), "r"(v[3]) : "memory");
      }
      asm volatile("barrier.cluster.arrive.release.aligned;" ::: "memory");
      asm volatile("barrier.cluster.wait.acquire.aligned;" ::: "memory");
      PROF(threadIdx.x == 0, 13);
      const uint32_t ob = sb + wg * 10240;
      const uint32_t oa = ob + (w4 * 16 + (lane & 15)) * 160 + (lane >> 4) * 16;
      uint32_t pk[20];
#pragma unroll
      for (int j = 0; j < 5; j++) {
        const uint4 r = *(const uint4*)(smem + OFF_Q + j * 4096 + threadIdx.x * 16);
        const uint32_t rv[4] = {r.x, r.y, r.z, r.w};
#pragma unroll
        for (int u = 0; u < 4; u++) {
          const float v0 = half ? acc[40 + 8 * j + 2 * u] : acc[8 * j + 2 * u], v1 = half ? acc[41 + 8 * j + 2 * u] : acc[8 * j + 2 * u + 1];
          pk[4 * j + u] = packbf(v0 + bf_lo(rv[u]), v1 + bf_hi(rv[u]));
        }
      }
#pragma unroll
      for (int j = 0; j < 10; j += 2) stsm4(oa + j * 16, pk[2 * j], pk[2 * j + 1], pk[2 * j + 2], pk[2 * j + 3]);
      fence_async_smem();
      bar_sync(NB_WG + wg, 128);
      if (lead) {
        asm volatile("cp.async.bulk.tensor.2d.global.shared::cta.bulk_group [%0, {%2,%3}], [%1];" ::"l"(&maps.out), "r"(ob), "r"(nt * 160 + half * 80),
                     "r"(mt3 * 128 + wg * 64) : "memory");
        asm volatile("cp.async.bulk.commit_group;" ::: "memory");
        asm volatile("cp.async.bulk.wait_group.read 0;" ::: "memory");
      }
      PROF(threadIdx.x == 0, 14);
    }
  }
}

typedef CUresult (*EncodeFn)(CUtensorMap*, CUtensorMapDataType, cuuint32_t, void*, const cuuint64_t*, const cuuint64_t*, const cuuint32_t*,
                             const cuuint32_t*, CUtensorMapInterleave, CUtensorMapSwizzle, CUtensorMapL2promotion, CUtensorMapFloatOOBfill);

void encode(EncodeFn fn, CUtensorMap* m, const void* p, int rank, const cuuint64_t* dims, const cuuint64_t* strides, const cuuint32_t* box,
            CUtensorMapSwizzle sw) {
  const cuuint32_t es[5] = {1, 1, 1, 1, 1};
  fn(m, CU_TENSOR_MAP_DATA_TYPE_BFLOAT16, rank, const_cast<void*>(p), dims, strides, box, es, CU_TENSOR_MAP_INTERLEAVE_NONE, sw,
     CU_TENSOR_MAP_L2_PROMOTION_L2_128B, CU_TENSOR_MAP_FLOAT_OOB_FILL_NONE);
}

}

extern "C" void kernel_launch(void* const* d_in, const int* in_sizes, int n_in, void* d_out, int out_size) {
  (void)in_sizes; (void)n_in; (void)out_size;
  static EncodeFn enc = nullptr;
  if (!enc) {
    void* fn = nullptr;
    cudaDriverEntryPointQueryResult qr;
    cudaGetDriverEntryPoint("cuTensorMapEncodeTiled", &fn, cudaEnableDefault, &qr);
    enc = (EncodeFn)fn;
    cudaFuncSetAttribute(fused_block, cudaFuncAttributeMaxDynamicSharedMemorySize, SMEM_BYTES);
  }
  Maps maps;
  {
    const cuuint64_t dx[2] = {640, 2048}, sx[1] = {1280};
    const cuuint32_t bo[2] = {80, 64};
    encode(enc, &maps.out, d_out, 2, dx, sx, bo, CU_TENSOR_MAP_SWIZZLE_NONE);
    const cuuint64_t dw[5] = {1920, 2, 4, 4, 20}, sw[4] = {3840, 8 * 3840, 2 * 3840, 32 * 3840};
    const cuuint32_t b64[5] = {64, 2, 4, 4, 2}, b16[5] = {16, 2, 4, 4, 2};
    encode(enc, &maps.a64, d_in[1], 5, dw, sw, b64, CU_TENSOR_MAP_SWIZZLE_128B);
    encode(enc, &maps.a16, d_in[1], 5, dw, sw, b16, CU_TENSOR_MAP_SWIZZLE_32B);
    encode(enc, &maps.b64, d_in[5], 5, dw, sw, b64, CU_TENSOR_MAP_SWIZZLE_128B);
    encode(enc, &maps.b16, d_in[5], 5, dw, sw, b16, CU_TENSOR_MAP_SWIZZLE_32B);
  }
  fused_block<<<NCTA, 384, SMEM_BYTES, cudaStreamPerThread>>>(maps, (const __nv_bfloat16*)d_in[0], (const __nv_bfloat16*)d_in[2],
                                                               (const __nv_bfloat16*)d_in[7], (const uint8_t*)d_in[1], (const uint8_t*)d_in[5],
                                                               (const uint8_t*)d_in[3], (const uint8_t*)d_in[6], 0x1F801F80u, 0xFFFFFFFFu);
}
```

```cpp
#include <cuda_runtime.h>
#include <cuda_bf16.h>
#include <cuda.h>
#include <stdint.h>

#define PFNS 100
#define PFMODE 1
#define NOPF 0
#define PROFH(x) PROF(lane == 0, x)
namespace {

constexpr int SEQ = 2048, DM = 640, NH = 32, NCTA = 128;
constexpr int IMG_HEAD = SEQ * 48;
#define POLY_MASK 0x76DDu
constexpr float LOG2E = 1.4426950408889634f;
constexpr float QSCALE = 0.22360679774997896f * 1.4426950408889634f;
constexpr uint32_t BF_ONE = 0x3F80u;
constexpr uint32_t BF_MAGIC = 0x43E0u;
constexpr uint32_t BF_MU_HI = 0x4025u;
constexpr uint32_t BF_MU_LO = 0x3B8Bu;
constexpr float FAST_BOUND = 40.0f;

__device__ __align__(1024) uint8_t g_KV[2 * NH * IMG_HEAD];
__device__ __align__(1024) float2 g_KVP[NH * 16 * 480];
__device__ __align__(1024) uint32_t g_KVB[NH * 480];
__device__ __align__(1024) float g_KMAX[NH * 128];
__device__ __align__(1024) float2 g_GATE[SEQ];
__device__ __align__(1024) uint8_t g_OAB[16 * 20 * 16384];
__device__ __align__(1024) uint8_t g_WOI[4 * 409600];
__device__ __align__(1024) uint32_t g_CNT[80 * 8];
constexpr int C_START = 0, C_WO = 1, C_KV = 2, C_KVP = 10, C_KVB = 18, C_GATE = 26, C_OA = 42, C_OB = 58;

#define SPIN_LIMIT (1ll << 29)
#define SPIN_FAIL(code) __trap()
#define PROF(cond, slot)
__device__ __forceinline__ uint32_t smem_u32(const void* p) { return (uint32_t)__cvta_generic_to_shared(p); }
__device__ __forceinline__ void mbar_init(uint32_t a, uint32_t c) { asm volatile("mbarrier.init.shared::cta.b64 [%0], %1;" ::"r"(a), "r"(c) : "memory"); }
__device__ __forceinline__ void mbar_expect(uint32_t a, uint32_t b) { asm volatile("mbarrier.arrive.expect_tx.shared::cta.b64 _, [%0], %1;" ::"r"(a), "r"(b) : "memory"); }
__device__ __forceinline__ void mbar_arrive(uint32_t a) { asm volatile("mbarrier.arrive.shared::cta.b64 _, [%0];" ::"r"(a) : "memory"); }
__device__ __forceinline__ uint32_t mbar_try(uint32_t a, uint32_t ph) {
  uint32_t ok;
  asm volatile("{\n.reg .pred p;\nmbarrier.try_wait.parity.shared::cta.b64 p, [%1], %2;\nselp.u32 %0, 1, 0, p;\n}\n" : "=r"(ok) : "r"(a), "r"(ph) : "memory");
  return ok;
}
__device__ __forceinline__ void mbar_wait(uint32_t a, uint32_t ph) {
  if (mbar_try(a, ph)) return;
  const long long t0 = clock64();
  while (!mbar_try(a, ph))
    if (clock64() - t0 > SPIN_LIMIT) { SPIN_FAIL(1000 + (a & 0x1FF) * 2 + ph); break; }
}
__device__ __forceinline__ void mbar_wait_u(uint32_t a, uint32_t ph) {
#pragma unroll 1
  for (int n = 0; n < (1 << 18); n++)
    if (__all_sync(~0u, mbar_try(a, ph))) break;
}
__device__ __forceinline__ uint32_t mbar_wait_z(uint32_t a, uint32_t ph) {
  uint32_t ok = 0;
#pragma unroll 1
  for (int n = 0; n < (1 << 18); n++) {
    ok = mbar_try(a, ph);
    if (__all_sync(~0u, ok)) break;
  }
  return ok - 1;
}
__device__ __forceinline__ void mbar_arrive_if(uint32_t a, uint32_t flag) {
  asm volatile("{\n.reg .pred p;\nsetp.ne.u32 p, %1, 0;\n@p mbarrier.arrive.shared::cta.b64 _, [%0];\n}\n" ::"r"(a), "r"(flag) : "memory");
}
__device__ __forceinline__ void mbar_arrive_pair(uint32_t a, uint32_t flag) {
  asm volatile("{\n.reg .pred p;\n.reg .b32 r0, r1;\nsetp.ne.u32 p, %1, 0;\nmapa.shared::cluster.u32 r0, %0, 0;\nmapa.shared::cluster.u32 r1, %0, 1;\n"
               "@p mbarrier.arrive.relaxed.cluster.shared::cluster.b64 _, [r0];\n@p mbarrier.arrive.relaxed.cluster.shared::cluster.b64 _, [r1];\n}\n" ::"r"(a), "r"(flag) : "memory");
}
__device__ __forceinline__ void cnt_add(int slot) {
  asm volatile("fence.acq_rel.gpu;\nred.relaxed.gpu.global.add.u32 [%0], 1;" ::"l"(g_CNT + slot * 8) : "memory");
}
__device__ __forceinline__ void cnt_wait(int slot, uint32_t target) {
  uint32_t v;
  long long t0 = 0;
  for (;;) {
    asm volatile("ld.acquire.gpu.global.u32 %0, [%1];" : "=r"(v) : "l"(g_CNT + slot * 8) : "memory");
    if ((int32_t)(v - target) >= 0) break;
    if (!t0) t0 = clock64();
    else if (clock64() - t0 > SPIN_LIMIT) { SPIN_FAIL(slot); break; }
  }
}
__device__ __forceinline__ void tma5(uint32_t dst, const CUtensorMap* m, int c0, int c4, uint32_t bar) {
  asm volatile("cp.async.bulk.tensor.5d.shared::cluster.global.mbarrier::complete_tx::bytes [%0], [%1, {%3,%5,%5,%5,%4}], [%2];" ::"r"(dst), "l"(m), "r"(bar), "r"(c0), "r"(c4), "r"(0) : "memory");
}
__device__ __forceinline__ void bulk_g2s(uint32_t dst, const void* src, uint32_t bytes, uint32_t bar) {
  asm volatile("cp.async.bulk.shared::cluster.global.mbarrier::complete_tx::bytes [%0], [%1], %2, [%3];" ::"r"(dst), "l"(src), "r"(bytes), "r"(bar) : "memory");
}
__device__ __forceinline__ void prefetch_l2(const void* src, uint32_t bytes) { asm volatile("cp.async.bulk.prefetch.L2.global [%0], %1;" ::"l"(src), "r"(bytes) : "memory"); }
__device__ __forceinline__ void fence_async_smem() { asm volatile("fence.proxy.async.shared::cta;" ::: "memory"); }
__device__ __forceinline__ void fence_async_all() { asm volatile("fence.proxy.async;" ::: "memory"); }
__device__ __forceinline__ void bar_sync(int id, int n) { asm volatile("bar.sync %0, %1;" ::"r"(id), "r"(n) : "memory"); }
__device__ __forceinline__ void bar_arrive(int id, int n) { asm volatile("bar.arrive %0, %1;" ::"r"(id), "r"(n) : "memory"); }
__device__ __forceinline__ void wg_fence() { asm volatile("wgmma.fence.sync.aligned;" ::: "memory"); }
__device__ __forceinline__ void wg_commit() { asm volatile("wgmma.commit_group.sync.aligned;" ::: "memory"); }
template <int N> __device__ __forceinline__ void wg_wait() { asm volatile("wgmma.wait_group.sync.aligned %0;" ::"n"(N) : "memory"); }
template <int N> __device__ __forceinline__ void reg_inc() { asm volatile("setmaxnreg.inc.sync.aligned.u32 %0;" ::"n"(N)); }
template <int N> __device__ __forceinline__ void reg_dec() { asm volatile("setmaxnreg.dec.sync.aligned.u32 %0;" ::"n"(N)); }
template <int N> __device__ __forceinline__ void pin(float (&r)[N]) {
#pragma unroll
  for (int i = 0; i < N; i++) asm volatile("" : "+f"(r[i])::"memory");
}
template <int N> __device__ __forceinline__ void pin(uint32_t (&r)[N]) {
#pragma unroll
  for (int i = 0; i < N; i++) asm volatile("" : "+r"(r[i])::"memory");
}
__device__ __forceinline__ uint64_t mkdesc(uint32_t addr, uint32_t lbo, uint32_t sbo, uint32_t swz) {
  return (uint64_t)((addr & 0x3FFFF) >> 4) | ((uint64_t)(lbo >> 4) << 16) | ((uint64_t)(sbo >> 4) << 32) | ((uint64_t)swz << 62);
}
__device__ __forceinline__ float ex2(float x) { float y; asm("ex2.approx.ftz.f32 %0, %1;" : "=f"(y) : "f"(x)); return y; }
__device__ __forceinline__ float rcp(float x) { float y; asm("rcp.approx.ftz.f32 %0, %1;" : "=f"(y) : "f"(x)); return y; }
__device__ __forceinline__ float sqrt_ap(float x) { float y; asm("sqrt.approx.f32 %0, %1;" : "=f"(y) : "f"(x)); return y; }
__device__ __forceinline__ uint32_t packbf(float lo, float hi) { uint32_t d; asm("cvt.rn.bf16x2.f32 %0, %1, %2;" : "=r"(d) : "f"(hi), "f"(lo)); return d; }
__device__ __forceinline__ float bf_lo(uint32_t v) { return __uint_as_float(v << 16); }
__device__ __forceinline__ float bf_hi(uint32_t v) { return __uint_as_float(v & 0xFFFF0000u); }
__device__ __forceinline__ float bf_round(float x) { return bf_lo(packbf(x, 0.f)); }
__device__ __forceinline__ uint32_t ldg_cg(const void* p) { uint32_t v; asm volatile("ld.global.cg.b32 %0, [%1];" : "=r"(v) : "l"(p) : "memory"); return v; }
__device__ __forceinline__ uint4 ldg_cg4(const void* p) { uint4 v; asm volatile("ld.global.cg.v4.b32 {%0,%1,%2,%3}, [%4];" : "=r"(v.x), "=r"(v.y), "=r"(v.z), "=r"(v.w) : "l"(p) : "memory"); return v; }
__device__ __forceinline__ void sts32(uint32_t a, uint32_t v) { asm volatile("st.shared.b32 [%0], %1;" ::"r"(a), "r"(v) : "memory"); }
__device__ __forceinline__ void stsm4(uint32_t a, uint32_t r0, uint32_t r1, uint32_t r2, uint32_t r3) {
  asm volatile("stmatrix.sync.aligned.m8n8.x4.shared.b16 [%0], {%1,%2,%3,%4};" ::"r"(a), "r"(r0), "r"(r1), "r"(r2), "r"(r3) : "memory");
}

__device__ __forceinline__ void stsm2(uint32_t a, uint32_t r0, uint32_t r1) {
  asm volatile("stmatrix.sync.aligned.m8n8.x2.shared.b16 [%0], {%1,%2};" ::"r"(a), "r"(r0), "r"(r1) : "memory");
}
__device__ __forceinline__ uint4 ldg_x(const void* p) {
  uint4 v;
  asm volatile("ld.global.nc.L1::no_allocate.L2::128B.v4.b32 {%0,%1,%2,%3}, [%4];" : "=r"(v.x), "=r"(v.y), "=r"(v.z), "=r"(v.w) : "l"(p));
  return v;
}
__device__ __forceinline__ float2 lds_f2(uint32_t a) { float2 v; asm volatile("ld.shared.v2.f32 {%0,%1}, [%2];" : "=f"(v.x), "=f"(v.y) : "r"(a) : "memory"); return v; }
__device__ __forceinline__ void bulk_s2g(void* dst, uint32_t src, uint32_t bytes) {
  asm volatile("cp.async.bulk.global.shared::cta.bulk_group [%0], [%1], %2;" ::"l"(dst), "r"(src), "r"(bytes) : "memory");
}

__device__ __forceinline__ void mma_n24_ss_tb(float (&d)[12], uint64_t adesc, uint64_t bdesc, int acc) {
  asm volatile("{\n.reg .pred p;\nsetp.ne.b32 p, %14, 0;\n"
      "wgmma.mma_async.sync.aligned.m64n24k16.f32.bf16.bf16 "
      "{%0,%1,%2,%3,%4,%5,%6,%7,%8,%9,%10,%11}, "
      "%12, %13, p, 1, 1, 0, 1;\n}\n"
      : "+f"(d[0]), "+f"(d[1]), "+f"(d[2]), "+f"(d[3]), "+f"(d[4]), "+f"(d[5]), "+f"(d[6]), "+f"(d[7]),
        "+f"(d[8]), "+f"(d[9]), "+f"(d[10]), "+f"(d[11])
      : "l"(adesc), "l"(bdesc), "r"(acc));
}
__device__ __forceinline__ void mma_n192_rs_tb(float (&d)[96], uint32_t a0, uint32_t a1, uint32_t a2, uint32_t a3, uint64_t bdesc, int acc) {
  asm volatile("{\n.reg .pred p;\nsetp.ne.b32 p, %101, 0;\n"
      "wgmma.mma_async.sync.aligned.m64n192k16.f32.bf16.bf16 "
      "{%0,%1,%2,%3,%4,%5,%6,%7,%8,%9,%10,%11,%12,%13,%14,%15,"
      "%16,%17,%18,%19,%20,%21,%22,%23,%24,%25,%26,%27,%28,%29,%30,%31,"
      "%32,%33,%34,%35,%36,%37,%38,%39,%40,%41,%42,%43,%44,%45,%46,%47,"
      "%48,%49,%50,%51,%52,%53,%54,%55,%56,%57,%58,%59,%60,%61,%62,%63,"
      "%64,%65,%66,%67,%68,%69,%70,%71,%72,%73,%74,%75,%76,%77,%78,%79,"
      "%80,%81,%82,%83,%84,%85,%86,%87,%88,%89,%90,%91,%92,%93,%94,%95}, "
      "{%96,%97,%98,%99}, %100, p, 1, 1, 1;\n}\n"
      : "+f"(d[0]), "+f"(d[1]), "+f"(d[2]), "+f"(d[3]), "+f"(d[4]), "+f"(d[5]), "+f"(d[6]), "+f"(d[7]),
        "+f"(d[8]), "+f"(d[9]), "+f"(d[10]), "+f"(d[11]), "+f"(d[12]), "+f"(d[13]), "+f"(d[14]), "+f"(d[15]),
        "+f"(d[16]), "+f"(d[17]), "+f"(d[18]), "+f"(d[19]), "+f"(d[20]), "+f"(d[21]), "+f"(d[22]), "+f"(d[23]),
        "+f"(d[24]), "+f"(d[25]), "+f"(d[26]), "+f"(d[27]), "+f"(d[28]), "+f"(d[29]), "+f"(d[30]), "+f"(d[31]),
        "+f"(d[32]), "+f"(d[33]), "+f"(d[34]), "+f"(d[35]), "+f"(d[36]), "+f"(d[37]), "+f"(d[38]), "+f"(d[39]),
        "+f"(d[40]), "+f"(d[41]), "+f"(d[42]), "+f"(d[43]), "+f"(d[44]), "+f"(d[45]), "+f"(d[46]), "+f"(d[47]),
        "+f"(d[48]), "+f"(d[49]), "+f"(d[50]), "+f"(d[51]), "+f"(d[52]), "+f"(d[53]), "+f"(d[54]), "+f"(d[55]),
        "+f"(d[56]), "+f"(d[57]), "+f"(d[58]), "+f"(d[59]), "+f"(d[60]), "+f"(d[61]), "+f"(d[62]), "+f"(d[63]),
        "+f"(d[64]), "+f"(d[65]), "+f"(d[66]), "+f"(d[67]), "+f"(d[68]), "+f"(d[69]), "+f"(d[70]), "+f"(d[71]),
        "+f"(d[72]), "+f"(d[73]), "+f"(d[74]), "+f"(d[75]), "+f"(d[76]), "+f"(d[77]), "+f"(d[78]), "+f"(d[79]),
        "+f"(d[80]), "+f"(d[81]), "+f"(d[82]), "+f"(d[83]), "+f"(d[84]), "+f"(d[85]), "+f"(d[86]), "+f"(d[87]),
        "+f"(d[88]), "+f"(d[89]), "+f"(d[90]), "+f"(d[91]), "+f"(d[92]), "+f"(d[93]), "+f"(d[94]), "+f"(d[95])
      : "r"(a0), "r"(a1), "r"(a2), "r"(a3), "l"(bdesc), "r"(acc));
}
__device__ __forceinline__ void mma_n48_rs_tb(float (&d)[24], uint32_t a0, uint32_t a1, uint32_t a2, uint32_t a3, uint64_t bdesc, int acc) {
  asm volatile("{\n.reg .pred p;\nsetp.ne.b32 p, %29, 0;\n"
      "wgmma.mma_async.sync.aligned.m64n48k16.f32.bf16.bf16 "
      "{%0,%1,%2,%3,%4,%5,%6,%7,%8,%9,%10,%11,%12,%13,%14,%15,"
      "%16,%17,%18,%19,%20,%21,%22,%23}, "
      "{%24,%25,%26,%27}, %28, p, 1, 1, 1;\n}\n"
      : "+f"(d[0]), "+f"(d[1]), "+f"(d[2]), "+f"(d[3]), "+f"(d[4]), "+f"(d[5]), "+f"(d[6]), "+f"(d[7]),
        "+f"(d[8]), "+f"(d[9]), "+f"(d[10]), "+f"(d[11]), "+f"(d[12]), "+f"(d[13]), "+f"(d[14]), "+f"(d[15]),
        "+f"(d[16]), "+f"(d[17]), "+f"(d[18]), "+f"(d[19]), "+f"(d[20]), "+f"(d[21]), "+f"(d[22]), "+f"(d[23])
      : "r"(a0), "r"(a1), "r"(a2), "r"(a3), "l"(bdesc), "r"(acc));
}
__device__ __forceinline__ void mma_n128_ss(float (&d)[64], uint64_t adesc, uint64_t bdesc, int acc) {
  asm volatile("{\n.reg .pred p;\nsetp.ne.b32 p, %66, 0;\n"
      "wgmma.mma_async.sync.aligned.m64n128k16.f32.bf16.bf16 "
      "{%0,%1,%2,%3,%4,%5,%6,%7,%8,%9,%10,%11,%12,%13,%14,%15,"
      "%16,%17,%18,%19,%20,%21,%22,%23,%24,%25,%26,%27,%28,%29,%30,%31,"
      "%32,%33,%34,%35,%36,%37,%38,%39,%40,%41,%42,%43,%44,%45,%46,%47,"
      "%48,%49,%50,%51,%52,%53,%54,%55,%56,%57,%58,%59,%60,%61,%62,%63}, "
      "%64, %65, p, 1, 1, 0, 0;\n}\n"
      : "+f"(d[0]), "+f"(d[1]), "+f"(d[2]), "+f"(d[3]), "+f"(d[4]), "+f"(d[5]), "+f"(d[6]), "+f"(d[7]),
        "+f"(d[8]), "+f"(d[9]), "+f"(d[10]), "+f"(d[11]), "+f"(d[12]), "+f"(d[13]), "+f"(d[14]), "+f"(d[15]),
        "+f"(d[16]), "+f"(d[17]), "+f"(d[18]), "+f"(d[19]), "+f"(d[20]), "+f"(d[21]), "+f"(d[22]), "+f"(d[23]),
        "+f"(d[24]), "+f"(d[25]), "+f"(d[26]), "+f"(d[27]), "+f"(d[28]), "+f"(d[29]), "+f"(d[30]), "+f"(d[31]),
        "+f"(d[32]), "+f"(d[33]), "+f"(d[34]), "+f"(d[35]), "+f"(d[36]), "+f"(d[37]), "+f"(d[38]), "+f"(d[39]),
        "+f"(d[40]), "+f"(d[41]), "+f"(d[42]), "+f"(d[43]), "+f"(d[44]), "+f"(d[45]), "+f"(d[46]), "+f"(d[47]),
        "+f"(d[48]), "+f"(d[49]), "+f"(d[50]), "+f"(d[51]), "+f"(d[52]), "+f"(d[53]), "+f"(d[54]), "+f"(d[55]),
        "+f"(d[56]), "+f"(d[57]), "+f"(d[58]), "+f"(d[59]), "+f"(d[60]), "+f"(d[61]), "+f"(d[62]), "+f"(d[63])
      : "l"(adesc), "l"(bdesc), "r"(acc));
}
__device__ __forceinline__ void mma_n160_ss_tb(float (&d)[80], uint64_t adesc, uint64_t bdesc, int acc) {
  asm volatile("{\n.reg .pred p;\nsetp.ne.b32 p, %82, 0;\n"
      "wgmma.mma_async.sync.aligned.m64n160k16.f32.bf16.bf16 "
      "{%0,%1,%2,%3,%4,%5,%6,%7,%8,%9,%10,%11,%12,%13,%14,%15,"
      "%16,%17,%18,%19,%20,%21,%22,%23,%24,%25,%26,%27,%28,%29,%30,%31,"
      "%32,%33,%34,%35,%36,%37,%38,%39,%40,%41,%42,%43,%44,%45,%46,%47,"
      "%48,%49,%50,%51,%52,%53,%54,%55,%56,%57,%58,%59,%60,%61,%62,%63,"
      "%64,%65,%66,%67,%68,%69,%70,%71,%72,%73,%74,%75,%76,%77,%78,%79}, "
      "%80, %81, p, 1, 1, 0, 1;\n}\n"
      : "+f"(d[0]), "+f"(d[1]), "+f"(d[2]), "+f"(d[3]), "+f"(d[4]), "+f"(d[5]), "+f"(d[6]), "+f"(d[7]),
        "+f"(d[8]), "+f"(d[9]), "+f"(d[10]), "+f"(d[11]), "+f"(d[12]), "+f"(d[13]), "+f"(d[14]), "+f"(d[15]),
        "+f"(d[16]), "+f"(d[17]), "+f"(d[18]), "+f"(d[19]), "+f"(d[20]), "+f"(d[21]), "+f"(d[22]), "+f"(d[23]),
        "+f"(d[24]), "+f"(d[25]), "+f"(d[26]), "+f"(d[27]), "+f"(d[28]), "+f"(d[29]), "+f"(d[30]), "+f"(d[31]),
        "+f"(d[32]), "+f"(d[33]), "+f"(d[34]), "+f"(d[35]), "+f"(d[36]), "+f"(d[37]), "+f"(d[38]), "+f"(d[39]),
        "+f"(d[40]), "+f"(d[41]), "+f"(d[42]), "+f"(d[43]), "+f"(d[44]), "+f"(d[45]), "+f"(d[46]), "+f"(d[47]),
        "+f"(d[48]), "+f"(d[49]), "+f"(d[50]), "+f"(d[51]), "+f"(d[52]), "+f"(d[53]), "+f"(d[54]), "+f"(d[55]),
        "+f"(d[56]), "+f"(d[57]), "+f"(d[58]), "+f"(d[59]), "+f"(d[60]), "+f"(d[61]), "+f"(d[62]), "+f"(d[63]),
        "+f"(d[64]), "+f"(d[65]), "+f"(d[66]), "+f"(d[67]), "+f"(d[68]), "+f"(d[69]), "+f"(d[70]), "+f"(d[71]),
        "+f"(d[72]), "+f"(d[73]), "+f"(d[74]), "+f"(d[75]), "+f"(d[76]), "+f"(d[77]), "+f"(d[78]), "+f"(d[79])
      : "l"(adesc), "l"(bdesc), "r"(acc));
}
__device__ __forceinline__ void mma_n24_rs_tb(float (&d)[12], uint32_t a0, uint32_t a1, uint32_t a2, uint32_t a3, uint64_t bdesc, int acc) {
  asm volatile("{\n.reg .pred p;\nsetp.ne.b32 p, %17, 0;\n"
      "wgmma.mma_async.sync.aligned.m64n24k16.f32.bf16.bf16 "
      "{%0,%1,%2,%3,%4,%5,%6,%7,%8,%9,%10,%11}, "
      "{%12,%13,%14,%15}, %16, p, 1, 1, 1;\n}\n"
      : "+f"(d[0]), "+f"(d[1]), "+f"(d[2]), "+f"(d[3]), "+f"(d[4]), "+f"(d[5]), "+f"(d[6]), "+f"(d[7]),
        "+f"(d[8]), "+f"(d[9]), "+f"(d[10]), "+f"(d[11])
      : "r"(a0), "r"(a1), "r"(a2), "r"(a3), "l"(bdesc), "r"(acc));
}
__device__ __forceinline__ void mma_n24_ss_tatb(float (&d)[12], uint64_t adesc, uint64_t bdesc, int acc) {
  asm volatile("{\n.reg .pred p;\nsetp.ne.b32 p, %14, 0;\n"
      "wgmma.mma_async.sync.aligned.m64n24k16.f32.bf16.bf16 "
      "{%0,%1,%2,%3,%4,%5,%6,%7,%8,%9,%10,%11}, "
      "%12, %13, p, 1, 1, 1, 1;\n}\n"
      : "+f"(d[0]), "+f"(d[1]), "+f"(d[2]), "+f"(d[3]), "+f"(d[4]), "+f"(d[5]), "+f"(d[6]), "+f"(d[7]),
        "+f"(d[8]), "+f"(d[9]), "+f"(d[10]), "+f"(d[11])
      : "l"(adesc), "l"(bdesc), "r"(acc));
}

constexpr int W_STAGE = 30720, W_NST = 5;
constexpr int KV_CHUNK = 24576, KV_NST = 6;
constexpr int O_STAGE = 36864;
constexpr int OFF_GATE = KV_NST * KV_CHUNK;
constexpr int OFF_Q = W_NST * W_STAGE;
constexpr int OFF_V = OFF_Q + 24576;
constexpr int OFF_AQ = OFF_V + 24576;
constexpr int OFF_WPH = OFF_AQ + 24576;
constexpr int OFF_BAR = OFF_WPH + 4608;
constexpr int B_WF = 0, B_WE = 40, B_KF = 80, B_KE = 128, B_OF = 176, B_OE = 216, B_RF = 256, OFF_MISC = OFF_BAR + 272;
constexpr int SMEM_BYTES = OFF_MISC + 32;
constexpr int NB_STAGED = 1, NB_FREE = 2, NB_WG = 3, NB_PHIK = 5, NB_TAIL = 6, NB_GATE = 7, NB_KVB = 9, NB_READ = 11, NB_LAST = 12, NB_HELP = 13;

template <int SEC, int J, int HF>
__device__ __forceinline__ float2 grp(const float (&a1)[96], const float (&a2)[24]) {
  constexpr int S = SEC & 3, J1 = (SEC & 4) ? J - 2 : J, J2 = (SEC & 4) ? J : J - 8;
  if constexpr (J1 >= 0 && J1 < 8) return make_float2(a1[(8 * S + J1) * 4 + 2 * HF], a1[(8 * S + J1) * 4 + 2 * HF + 1]);
  else return make_float2(a2[(2 * S + J2) * 4 + 2 * HF], a2[(2 * S + J2) * 4 + 2 * HF + 1]);
}
__device__ __forceinline__ float sq2(float2 v) { return fmaf(v.x, v.x, v.y * v.y); }
__device__ __forceinline__ uint32_t pks(float2 v, float s) { return packbf(v.x * s, v.y * s); }

template <int SEC, int PR>
__device__ __forceinline__ void norms(const float (&a1)[96], const float (&a2)[24], int t, float (&n)[2][2]) {
  const float h0 = sq2(grp<SEC, 5 * PR + 2, 0>(a1, a2)), h1 = sq2(grp<SEC, 5 * PR + 2, 1>(a1, a2));
  n[0][0] = sq2(grp<SEC, 5 * PR, 0>(a1, a2)) + sq2(grp<SEC, 5 * PR + 1, 0>(a1, a2)) + (t < 2 ? h0 : 0.f);
  n[0][1] = sq2(grp<SEC, 5 * PR, 1>(a1, a2)) + sq2(grp<SEC, 5 * PR + 1, 1>(a1, a2)) + (t < 2 ? h1 : 0.f);
  n[1][0] = sq2(grp<SEC, 5 * PR + 3, 0>(a1, a2)) + sq2(grp<SEC, 5 * PR + 4, 0>(a1, a2)) + (t < 2 ? 0.f : h0);
  n[1][1] = sq2(grp<SEC, 5 * PR + 3, 1>(a1, a2)) + sq2(grp<SEC, 5 * PR + 4, 1>(a1, a2)) + (t < 2 ? 0.f : h1);
#pragma unroll
  for (int i = 0; i < 4; i++) n[i >> 1][i & 1] += __shfl_xor_sync(~0u, n[i >> 1][i & 1], 1);
#pragma unroll
  for (int i = 0; i < 4; i++) n[i >> 1][i & 1] += __shfl_xor_sync(~0u, n[i >> 1][i & 1], 2);
}

template <int SEC, int PR>
__device__ __forceinline__ void stage_pair(const float (&a1)[96], const float (&a2)[24], float sc0, float sc1, float sm, uint32_t xe0, uint32_t xe1,
                                           uint32_t xo0, uint32_t xo1, uint32_t ad01, uint32_t ad2, int t) {
  const uint32_t off = 2 * PR * 6144;
  stsm4(ad01 + off, pks(grp<SEC, 5 * PR, 0>(a1, a2), sc0), pks(grp<SEC, 5 * PR, 1>(a1, a2), sc1), pks(grp<SEC, 5 * PR + 1, 0>(a1, a2), sc0),
        pks(grp<SEC, 5 * PR + 1, 1>(a1, a2), sc1));
  stsm4(ad01 + off + 6144, pks(grp<SEC, 5 * PR + 3, 0>(a1, a2), sc0), pks(grp<SEC, 5 * PR + 3, 1>(a1, a2), sc1),
        pks(grp<SEC, 5 * PR + 4, 0>(a1, a2), sc0), pks(grp<SEC, 5 * PR + 4, 1>(a1, a2), sc1));
  const uint32_t m0 = pks(grp<SEC, 5 * PR + 2, 0>(a1, a2), sc0 * sm), m1 = pks(grp<SEC, 5 * PR + 2, 1>(a1, a2), sc1 * sm);
  const bool lo = t < 2;
  stsm4(ad2 + off, lo ? m0 : xe0, lo ? m1 : xe1, lo ? xo0 : m0, lo ? xo1 : m1);
}
template <int SEC, int PR>
__device__ __forceinline__ void frag_pair(const float (&a1)[96], const float (&a2)[24], uint32_t (&e)[6], uint32_t (&o)[6], int t) {
  e[0] = pks(grp<SEC, 5 * PR, 0>(a1, a2), 1.f); e[1] = pks(grp<SEC, 5 * PR, 1>(a1, a2), 1.f);
  e[2] = pks(grp<SEC, 5 * PR + 1, 0>(a1, a2), 1.f); e[3] = pks(grp<SEC, 5 * PR + 1, 1>(a1, a2), 1.f);
  o[0] = pks(grp<SEC, 5 * PR + 3, 0>(a1, a2), 1.f); o[1] = pks(grp<SEC, 5 * PR + 3, 1>(a1, a2), 1.f);
  o[2] = pks(grp<SEC, 5 * PR + 4, 0>(a1, a2), 1.f); o[3] = pks(grp<SEC, 5 * PR + 4, 1>(a1, a2), 1.f);
  const uint32_t m0 = pks(grp<SEC, 5 * PR + 2, 0>(a1, a2), 1.f), m1 = pks(grp<SEC, 5 * PR + 2, 1>(a1, a2), 1.f);
  e[4] = t < 2 ? m0 : 0u; e[5] = t < 2 ? m1 : 0u;
  o[4] = t < 2 ? 0u : m0; o[5] = t < 2 ? 0u : m1;
}

__device__ __forceinline__ void hedgehog(const float (&p)[12], uint32_t (&f)[10], int t) {
  const bool lo = t < 2;
#pragma unroll
  for (int hf = 0; hf < 2; hf++) {
    const float v[6] = {p[2 * hf], p[2 * hf + 1], p[4 + 2 * hf], p[5 + 2 * hf], p[8 + 2 * hf], p[9 + 2 * hf]};
    float mx = fmaxf(fmaxf(fmaxf(v[0], v[1]), fmaxf(v[2], v[3])), fmaxf(v[4], v[5]));
    float mn = fminf(fminf(fminf(v[0], v[1]), fminf(v[2], v[3])), fminf(v[4], v[5]));
    mx = fmaxf(mx, __shfl_xor_sync(~0u, mx, 1)); mn = fminf(mn, __shfl_xor_sync(~0u, mn, 1));
    mx = fmaxf(mx, __shfl_xor_sync(~0u, mx, 2)); mn = fminf(mn, __shfl_xor_sync(~0u, mn, 2));
    const float bp = -mx * LOG2E, bn = mn * LOG2E;
    float ep[4], en[4];
#pragma unroll
    for (int i = 0; i < 4; i++) { ep[i] = ex2(fmaf(v[i], LOG2E, bp)); en[i] = ex2(fmaf(v[i], -LOG2E, bn)); }
    const float sg = lo ? LOG2E : -LOG2E, bm = lo ? bp : bn;
    const float m0 = ex2(fmaf(v[4], sg, bm)), m1 = ex2(fmaf(v[5], sg, bm)), ms = m0 + m1;
    float sp = (ep[0] + ep[1]) + (ep[2] + ep[3]) + (lo ? ms : 0.f);
    float sn = (en[0] + en[1]) + (en[2] + en[3]) + (lo ? 0.f : ms);
    sp += __shfl_xor_sync(~0u, sp, 1); sn += __shfl_xor_sync(~0u, sn, 1);
    sp += __shfl_xor_sync(~0u, sp, 2); sn += __shfl_xor_sync(~0u, sn, 2);
    const float rp = rcp(sp), rn = rcp(sn), rm = lo ? rp : rn;
    f[0 + hf] = packbf(ep[0] * rp, ep[1] * rp);
    f[2 + hf] = packbf(ep[2] * rp, ep[3] * rp);
    f[4 + hf] = packbf(m0 * rm, m1 * rm);
    f[6 + hf] = packbf(en[0] * rn, en[1] * rn);
    f[8 + hf] = packbf(en[2] * rn, en[3] * rn);
  }
}

template <int O>
__device__ __forceinline__ void epilogue0(const float (&a1)[96], const float (&a2)[24], int rg, int lane, uint32_t ad01, uint32_t ad2, float* kmx) {
  const int t = lane & 3;
  const bool p0 = (POLY_MASK >> rg) & 1, p1 = (POLY_MASK >> (rg + 1)) & 1;
  const uint32_t kp = (t & 1) ? 0u : (BF_ONE | (BF_MAGIC << 16)), km = (t & 1) ? BF_MU_LO : (BF_ONE | (BF_MU_HI << 16));
  const uint32_t vp = (t & 1) ? 0u : (BF_ONE | 0x8000u), vm = (t & 1) ? 0u : BF_ONE;
  const uint32_t k0 = p0 ? kp : km, k1 = p1 ? kp : km, v0 = p0 ? vp : vm, v1 = p1 ? vp : vm;
  const float s0 = p0 ? -1.f : 1.f, s1 = p1 ? -1.f : 1.f;
  stage_pair<O + 0, 0>(a1, a2, 1.f, 1.f, 1.f, k0, k1, k0, k1, ad01, ad2, t);
  stage_pair<O + 0, 1>(a1, a2, 1.f, 1.f, 1.f, k0, k1, k0, k1, ad01, ad2, t);
  stage_pair<O + 1, 0>(a1, a2, s0, s1, 1.f, v0, v1, v0, v1, ad01 + 24576, ad2 + 24576, t);
  stage_pair<O + 1, 1>(a1, a2, s0, s1, 1.f, v0, v1, v0, v1, ad01 + 24576, ad2 + 24576, t);
  stage_pair<O + 2, 0>(a1, a2, 1.f, 1.f, 0.5f, 0u, 0u, 0u, 0u, ad01 + 49152, ad2 + 49152, t);
  stage_pair<O + 2, 1>(a1, a2, 1.f, 1.f, 0.5f, 0u, 0u, 0u, 0u, ad01 + 49152, ad2 + 49152, t);
  float n0[2][2], n1[2][2];
  norms<O + 0, 0>(a1, a2, t, n0);
  norms<O + 0, 1>(a1, a2, t, n1);
  const uint32_t m0 = __reduce_max_sync(~0u, __float_as_uint(fmaxf(n0[0][0], n0[0][1])));
  const uint32_t m1 = __reduce_max_sync(~0u, __float_as_uint(fmaxf(n0[1][0], n0[1][1])));
  const uint32_t m2 = __reduce_max_sync(~0u, __float_as_uint(fmaxf(n1[0][0], n1[0][1])));
  const uint32_t m3 = __reduce_max_sync(~0u, __float_as_uint(fmaxf(n1[1][0], n1[1][1])));
  if (lane < 4) *kmx = __uint_as_float(lane == 0 ? m0 : lane == 1 ? m1 : lane == 2 ? m2 : m3);
}

template <int O>
__device__ __forceinline__ bool epilogue1(const float (&a1)[96], const float (&a2)[24], uint32_t (&fk)[4][6], const uint8_t* smem, int wg, int t,
                                          uint32_t ad01, uint32_t ad2) {
  float n0[2][2], n1[2][2];
  norms<O + 2, 0>(a1, a2, t, n0);
  norms<O + 2, 1>(a1, a2, t, n1);
  bar_sync(NB_FREE, 288);
  const float4 km = *(const float4*)(smem + OFF_MISC);
  const float b[4][2] = {{sqrt_ap(n0[0][0]) * km.x, sqrt_ap(n0[0][1]) * km.x}, {sqrt_ap(n0[1][0]) * km.y, sqrt_ap(n0[1][1]) * km.y},
                         {sqrt_ap(n1[0][0]) * km.z, sqrt_ap(n1[0][1]) * km.z}, {sqrt_ap(n1[1][0]) * km.w, sqrt_ap(n1[1][1]) * km.w}};
  bool unsafe = false;
#pragma unroll
  for (int i = 0; i < 8; i++) unsafe |= !(b[i >> 1][i & 1] <= FAST_BOUND);
  uint32_t any;
  asm volatile("{\n.reg .pred p, q;\nsetp.ne.u32 p, %1, 0;\nbar.red.or.pred q, %2, 128, p;\nselp.u32 %0, 1, 0, q;\n}\n"
               : "=r"(any) : "r"((uint32_t)unsafe), "r"(NB_WG + wg) : "memory");
  const bool slow = __any_sync(~0u, any);
  uint32_t xq[4][2];
#pragma unroll
  for (int i = 0; i < 8; i++) xq[i >> 1][i & 1] = slow ? 0u : ((t & 1) ? 0x3F00u : packbf(-0.5f * b[i >> 1][i & 1], 0.5f));
  stage_pair<O + 2, 0>(a1, a2, QSCALE, QSCALE, 0.5f, xq[0][0], xq[0][1], xq[1][0], xq[1][1], ad01, ad2, t);
  stage_pair<O + 2, 1>(a1, a2, QSCALE, QSCALE, 0.5f, xq[2][0], xq[2][1], xq[3][0], xq[3][1], ad01, ad2, t);
  const uint32_t one = (t & 1) ? 0u : BF_ONE;
  stage_pair<O + 1, 0>(a1, a2, 1.f, 1.f, 1.f, one, one, one, one, ad01 + 24576, ad2 + 24576, t);
  stage_pair<O + 1, 1>(a1, a2, 1.f, 1.f, 1.f, one, one, one, one, ad01 + 24576, ad2 + 24576, t);
  frag_pair<O + 0, 0>(a1, a2, fk[0], fk[1], t);
  frag_pair<O + 0, 1>(a1, a2, fk[2], fk[3], t);
  return slow;
}

__device__ __forceinline__ uint32_t exp2_bits(float y0, float y1, uint32_t cm, uint32_t neg1) {
  uint32_t w, m, r;
  asm("prmt.b32 %0, %1, %2, 0x6521;" : "=r"(w) : "r"(__float_as_uint(y0)), "r"(__float_as_uint(y1)));
  asm("lop3.b32 %0, %1, 0x007F007F, %2, 0xEA;" : "=r"(m) : "r"(w), "r"(cm));
  const uint32_t e = m * neg1 + w;
  asm("fma.rn.bf16x2 %0, %1, %2, %3;" : "=r"(r) : "r"(w), "r"(m), "r"(e));
  return r;
}
__device__ __forceinline__ void exp_tile(const float (&s)[64], uint32_t (&p)[32], uint32_t cm, uint32_t neg1) {
#pragma unroll
  for (int g = 0; g < 16; g++) {
    if ((POLY_MASK >> g) & 1) {
      p[2 * g] = exp2_bits(s[4 * g], s[4 * g + 1], cm, neg1);
      p[2 * g + 1] = exp2_bits(s[4 * g + 2], s[4 * g + 3], cm, neg1);
    } else {
      p[2 * g] = packbf(ex2(s[4 * g]), ex2(s[4 * g + 1]));
      p[2 * g + 1] = packbf(ex2(s[4 * g + 2]), ex2(s[4 * g + 3]));
    }
  }
}
constexpr uint64_t NO_LBO = ~(0x3FFFull << 16);
__device__ __forceinline__ void issue_qk(float (&s)[64], uint64_t qd, uint64_t kd) {
  mma_n128_ss(s, qd, kd, 0);
  mma_n128_ss(s, (qd + 16) & NO_LBO, (kd + 16) & NO_LBO, 1);
}
__device__ __forceinline__ void issue_pv(float (&o)[12], const uint32_t (&p)[32], uint64_t vd, int acc) {
#pragma unroll
  for (int kk = 0; kk < 8; kk++) mma_n24_rs_tb(o, p[4 * kk], p[4 * kk + 1], p[4 * kk + 2], p[4 * kk + 3], vd + kk * 48, acc | kk);
}
__device__ __forceinline__ void attn_pair(float (&s0)[64], float (&s1)[64], uint32_t (&p0)[32], uint32_t (&p1)[32], float (&o)[12],
                                          uint64_t qd1, uint64_t kd1, uint64_t vd, uint64_t qd2, uint64_t kd2, int acc, uint32_t full_next,
                                          uint32_t ph_next, uint32_t empty_prev, uint32_t lead, uint32_t cm, uint32_t neg1) {
  wg_fence();
  issue_qk(s1, qd1, kd1);
  wg_commit();
  exp_tile(s0, p0, cm, neg1);
  wg_fence();
  issue_pv(o, p0, vd, acc);
  wg_commit();
  wg_wait<1>();
  pin(s1); pin(p1);
  mbar_arrive_if(empty_prev, lead);
  mbar_wait_u(full_next, ph_next);
  wg_fence();
  issue_qk(s0, qd2, kd2);
  wg_commit();
  exp_tile(s1, p1, cm, neg1);
  wg_fence();
  issue_pv(o, p1, vd + 384, 1);
  wg_commit();
}
__device__ __forceinline__ int bgroup(int G) {
  const int hg = G / 10, j = G % 10;
  return (hg >> 2) * 40 + (j < 7 ? (hg & 3) * 7 + j : 28 + (hg & 3) * 3 + j - 7);
}
template <bool BRANCH_B>
__device__ __forceinline__ void store_o(const float (&o)[12], int h, uint8_t* base, int lane, float eps, float s0, float s1) {
  const int odd = h & 1;
  const int src = (lane & ~3) | (odd ? 0 : 2);
  const float l0 = __shfl_sync(~0u, o[8], src) + eps, l1 = __shfl_sync(~0u, o[10], src) + eps;
  const float r0 = s0 * rcp(l0), r1 = s1 * rcp(l1);
  int g2 = (h >> 1) * 5 + 2, g0 = odd ? g2 + 1 : g2 - 2;
  if (BRANCH_B) { g2 = 80 + bgroup(g2); g0 = 80 + bgroup(g0); }
  const int g1 = g0 + 1;
  uint8_t* c0 = base + (g0 >> 3) * 16384 + (g0 & 7) * 128;
  uint8_t* c1 = base + (g1 >> 3) * 16384 + (g1 & 7) * 128;
  uint8_t* c2 = base + (g2 >> 3) * 16384 + (g2 & 7) * 128;
  *(uint32_t*)c0 = packbf(o[0] * r0, o[1] * r0); *(uint32_t*)(c0 + 1024) = packbf(o[2] * r1, o[3] * r1);
  *(uint32_t*)c1 = packbf(o[4] * r0, o[5] * r0); *(uint32_t*)(c1 + 1024) = packbf(o[6] * r1, o[7] * r1);
  if (((lane & 3) < 2) != (odd != 0)) { *(uint32_t*)c2 = packbf(o[8] * r0, o[9] * r0); *(uint32_t*)(c2 + 1024) = packbf(o[10] * r1, o[11] * r1); }
}

struct Maps { CUtensorMap a64, a16, b64, b16, out; };

__device__ __forceinline__ void w_load(const Maps& m, int it, uint32_t d, uint32_t b, int hg) {
  const int kb = (it % 10) * 2, c = hg * 80 + (hg & 1) * 16, c2 = hg * 80 + ((hg & 1) ? 0 : 64);
  const bool w0 = it < 10;
  const CUtensorMap *p64 = w0 ? &m.b64 : &m.a64, *q64 = w0 ? &m.a64 : &m.b64, *p16 = w0 ? &m.b16 : &m.a16, *q16 = w0 ? &m.a16 : &m.b16;
  mbar_expect(b, W_STAGE);
  tma5(d, p64, 640 + c, kb, b);
  tma5(d + 8192, p64, 1280 + c, kb, b);
  tma5(d + 16384, q64, c, kb, b);
  tma5(d + 24576, p16, 640 + c2, kb, b);
  tma5(d + 26624, p16, 1280 + c2, kb, b);
  tma5(d + 28672, q16, c2, kb, b);
}
__device__ __forceinline__ void x_load(uint4 (&v)[4], const uint8_t* p, int it) {
  const uint8_t* q = p + (it % 10) * 128;
  v[0] = ldg_x(q); v[1] = ldg_x(q + 8 * 1280); v[2] = ldg_x(q + 64); v[3] = ldg_x(q + 8 * 1280 + 64);
}
__device__ __forceinline__ void gemm_step(float (&a1)[96], float (&a2)[24], uint4 (&xv)[4], uint32_t (&f)[4][4], uint32_t (&fp)[4][4],
                                          const uint8_t* xp, int it, int acc, uint32_t sb, uint32_t bars, uint32_t lead) {
  const int s = it % W_NST;
  const uint32_t z = mbar_wait_z(bars + B_WF + 8 * s, (it / W_NST) & 1);
  f[0][0] = xv[0].x ^ z; f[0][1] = xv[1].x ^ z; f[0][2] = xv[0].y ^ z; f[0][3] = xv[1].y ^ z;
  f[1][0] = xv[0].z ^ z; f[1][1] = xv[1].z ^ z; f[1][2] = xv[0].w ^ z; f[1][3] = xv[1].w ^ z;
  f[2][0] = xv[2].x ^ z; f[2][1] = xv[3].x ^ z; f[2][2] = xv[2].y ^ z; f[2][3] = xv[3].y ^ z;
  f[3][0] = xv[2].z ^ z; f[3][1] = xv[3].z ^ z; f[3][2] = xv[2].w ^ z; f[3][3] = xv[3].w ^ z;
#pragma unroll
  for (int i = 0; i < 4; i++) pin(f[i]);
  x_load(xv, xp, it + 2);
  const uint64_t b1 = mkdesc(sb + s * W_STAGE, 8192, 1024, 1), b2 = mkdesc(sb + s * W_STAGE + 24576, 2048, 256, 3);
  wg_fence();
#pragma unroll
  for (int kk = 0; kk < 4; kk++) {
    mma_n192_rs_tb(a1, f[kk][0], f[kk][1], f[kk][2], f[kk][3], b1 + kk * 128, acc | kk);
    mma_n48_rs_tb(a2, f[kk][0], f[kk][1], f[kk][2], f[kk][3], b2 + kk * 32, acc | kk);
  }
  wg_commit();
  wg_wait<1>();
#pragma unroll
  for (int i = 0; i < 4; i++) pin(fp[i]);
  mbar_arrive_pair(bars + B_WE + 8 * ((it + W_NST - 1) % W_NST), lead && acc);
}

__global__ void __cluster_dims__(2, 1, 1) __launch_bounds__(384, 1)
fused_block(const __grid_constant__ Maps maps, const __nv_bfloat16* __restrict__ x, const __nv_bfloat16* __restrict__ wphi,
            const __nv_bfloat16* __restrict__ gate_w, const uint8_t* __restrict__ wa, const uint8_t* __restrict__ wb,
            const uint8_t* __restrict__ woa, const uint8_t* __restrict__ wob, uint32_t cm, uint32_t neg1) {
  extern __shared__ __align__(1024) uint8_t smem[];
  const uint32_t sb = smem_u32(smem), bars = sb + OFF_BAR;
  const int warp = __shfl_sync(~0u, threadIdx.x >> 5, 0), lane = threadIdx.x & 31, wg = warp >> 2;
  const int bid = blockIdx.x;
#define K1MAP 2
  const int mt = K1MAP == 3 ? (bid & 3) + 4 * (bid >> 5) : K1MAP == 2 ? (bid & 1) + 2 * (bid >> 4) : K1MAP == 1 ? bid >> 3 : K1MAP == 4 ? (bid & 7) + 8 * (bid >> 6) : bid & 15;
  const int hg = K1MAP == 3 ? (bid >> 2) & 7 : K1MAP == 2 ? (bid >> 1) & 7 : K1MAP == 1 ? bid & 7 : K1MAP == 4 ? (bid >> 3) & 7 : bid >> 4;
  const int half = bid & 1, nt = (bid >> 1) & 3, mt3 = bid >> 3;
  PROF(threadIdx.x == 0, 0);
  const uint8_t* xp = (const uint8_t*)x + (size_t)(mt * 128 + (warp & 7) * 16 + (lane >> 2)) * 1280 + (lane & 3) * 16;
  uint4 xa[4], xb[4];
  if (wg < 2) { x_load(xa, xp, 0); x_load(xb, xp, 1); }
  if (warp == 8) {
    if (lane < 4) asm volatile("prefetch.tensormap [%0];" ::"l"(&maps.a64 + lane) : "memory");
    const int cnt = lane < W_NST ? 1 : lane < 2 * W_NST ? 4 : lane < 16 ? 1 : lane < 22 ? 2 : lane < 27 ? 1 : 2;
    mbar_init(bars + 8 * lane, cnt);
    if (lane == 0) mbar_init(bars + B_RF, 1);
    asm volatile("fence.mbarrier_init.release.cluster;" ::: "memory");
  }
  __syncthreads();
  asm volatile("barrier.cluster.arrive.relaxed.aligned;" ::: "memory");

  if (wg == 2) {
    reg_dec<40>();
    if (warp != 8) asm volatile("barrier.cluster.wait.aligned;" ::: "memory");
    if (warp == 8) {
      if (lane == 0) for (int it = 0; it < 20; it++) {
        const int s = it % W_NST;
        if (it >= W_NST) mbar_wait(bars + B_WE + 8 * s, ((it / W_NST) - 1) & 1);
        PROF(lane == 0 && it == 5, 1); PROF(lane == 0 && it == 7, 15); PROF(lane == 0 && it == 9, 16); PROF(lane == 0 && it == 11, 26); PROF(lane == 0 && it == 13, 30); PROF(lane == 0 && it == 4, 31);
        w_load(maps, it, sb + s * W_STAGE, bars + B_WF + 8 * s, hg);
      }
      __syncwarp();
      asm volatile("barrier.cluster.wait.aligned;" ::: "memory");
      bar_sync(NB_HELP, 128);
      const uint32_t epoch = *(volatile uint32_t*)(smem + OFF_MISC + 16);
      if (lane == 0) {
        cnt_wait(C_KV + hg, 16 * epoch);
        fence_async_all();
        for (int c = 0; c < 32; c++) {
          const int s = (c + 4) % KV_NST;
          const uint8_t* src = g_KV + (size_t)(hg * 4 + (c >> 3)) * IMG_HEAD + (c & 7) * 12288;
          mbar_wait(bars + B_KE + 8 * s, (c / KV_NST) & 1);
          mbar_expect(bars + B_KF + 8 * s, KV_CHUNK);
          bulk_g2s(sb + s * KV_CHUNK, src, 12288, bars + B_KF + 8 * s);
          bulk_g2s(sb + s * KV_CHUNK + 12288, src + (size_t)NH * IMG_HEAD, 12288, bars + B_KF + 8 * s);
        }
        cnt_wait(C_WO, NCTA * epoch);
        cnt_wait(C_OA + mt3, 8 * epoch);
        fence_async_all();
        for (int it = 0; it < 10; it++) {
          const int s = it % 5, ks = (it < 5 ? 0 : 5) + half * 5 + it;
          if (it == 0) mbar_wait(bars + B_RF, 0);
          else if (it < 3) mbar_wait(bars + B_KE + 8 * it, 1);
          else if (it < 5) mbar_wait(bars + B_KE + 8 * (it + 1), 0);
          else {
            if (it == 8) { PROF(true, 28); cnt_wait(C_OB + mt3, 8 * epoch); PROF(true, 29); fence_async_all(); }
            mbar_wait(bars + B_OE + 8 * s, 0);
          }
          const uint32_t d = s == 0 ? sb + OFF_V : sb + (s - 1) * O_STAGE;
          mbar_expect(bars + B_OF + 8 * s, O_STAGE);
          bulk_g2s(d, g_OAB + (size_t)(mt3 * 20 + ks) * 16384, 16384, bars + B_OF + 8 * s);
          bulk_g2s(d + 16384, g_WOI + (size_t)nt * 409600 + ks * 20480, 20480, bars + B_OF + 8 * s);
        }
      }
    } else {
      if (warp == 9) {
        uint32_t epoch = 0;
        if (lane == 0) { epoch = atomicAdd(g_CNT + C_START * 8, 1u) / NCTA + 1; *(volatile uint32_t*)(smem + OFF_MISC + 16) = epoch; }
        epoch = __shfl_sync(~0u, epoch, 0);
        bar_arrive(NB_HELP, 128);
#pragma unroll 1
        for (int e = lane; e < 96; e += 32) {
          const int i = e / 24, slot = e % 24;
          int d = -1;
          if (i & 1) { if (slot < 16) d = slot + 4; else if (slot >= 20) d = slot - 20; }
          else if (slot < 20) d = slot;
          uint2 v[5] = {};
          if (d >= 0) {
#pragma unroll
            for (int u = 0; u < 5; u++) v[u] = __ldg((const uint2*)(wphi + ((hg * 4 + i) * 20 + d) * 20) + u);
          }
          uint8_t* dst = smem + OFF_WPH + i * 1152 + (slot >> 3) * 384 + (slot & 7) * 16;
          *(uint4*)dst = make_uint4(v[0].x, v[0].y, v[1].x, v[1].y);
          *(uint4*)(dst + 128) = make_uint4(v[2].x, v[2].y, v[3].x, v[3].y);
          *(uint4*)(dst + 256) = make_uint4(v[4].x, v[4].y, v[4].x, v[4].y);
        }
        fence_async_smem();
        PROF(lane == 0, 17);
        bar_sync(NB_STAGED, 288);
        PROFH(21);
        if (lane < 8) {
          bulk_s2g(g_KV + (size_t)((lane >> 2) * NH + hg * 4 + (lane & 3)) * IMG_HEAD + (size_t)mt * 6144, sb + OFF_Q + lane * 6144, 6144);
          asm volatile("cp.async.bulk.commit_group;" ::: "memory");
          asm volatile("cp.async.bulk.wait_group 0;" ::: "memory");
          fence_async_all();
        }
        __syncwarp();
        PROFH(22);
        if (lane == 0) { cnt_add(C_KV + hg); cnt_wait(C_KV + hg, 16 * epoch); }
        __syncwarp();
        PROFH(23);
        uint4 km[4];
#pragma unroll
        for (int i = 0; i < 4; i++) km[i] = ldg_cg4(g_KMAX + (hg * 4 + i) * 128 + lane * 4);
#pragma unroll
        for (int i = 0; i < 4; i++) {
          const uint32_t m = __reduce_max_sync(~0u, max(max(km[i].x, km[i].y), max(km[i].z, km[i].w)));
          if (lane == 0) *(volatile float*)(smem + OFF_MISC + i * 4) = sqrt_ap(__uint_as_float(m)) * (QSCALE * 1.02f);
        }
        PROFH(24);
        bar_arrive(NB_FREE, 288);
        bar_sync(NB_TAIL, 288);
        if (lane == 0) { cnt_add(C_KVP + hg); cnt_wait(C_GATE + mt, 8 * epoch); }
        __syncwarp();
        {
          const uint4 g0 = ldg_cg4(g_GATE + mt * 128 + lane * 2), g1 = ldg_cg4(g_GATE + mt * 128 + 64 + lane * 2);
          *(uint4*)(smem + OFF_GATE + lane * 16) = g0;
          *(uint4*)(smem + OFF_GATE + 512 + lane * 16) = g1;
        }
        bar_arrive(NB_GATE, 160);
        bar_arrive(NB_GATE + 1, 160);
        if (lane == 0) cnt_wait(C_KVB + hg, 16 * epoch);
        __syncwarp();
#pragma unroll 1
        for (int e0 = 0; e0 < 480; e0 += 160) {
          uint4 v[5];
#pragma unroll
          for (int u = 0; u < 5; u++) v[u] = ldg_cg4(g_KVB + hg * 4 * 480 + (e0 + u * 32 + lane) * 4);
#pragma unroll
          for (int u = 0; u < 5; u++) *(uint4*)(smem + OFF_V + (e0 + u * 32 + lane) * 16) = v[u];
        }
        fence_async_smem();
        PROF(lane == 0, 25);
        bar_arrive(NB_KVB, 160);
        bar_arrive(NB_KVB + 1, 160);
        bar_sync(NB_READ, 288);
        if (lane == 0) { mbar_arrive(bars + B_RF); cnt_add(C_OA + mt); }
        __syncwarp();
        bar_sync(NB_LAST, 288);
        if (lane == 0) cnt_add(C_OB + mt);
        PROF(lane == 0, 27);
      } else {
        const int ht = threadIdx.x - 320;
        if (warp == 10 && !NOPF) {
          const int r = bid >> 1, sec = bid & 1;
#pragma unroll 1
          for (int kb = 0; kb < 20; kb++) {
            const size_t row = (size_t)((kb % 10) * 64 + r) * 3840;
            const uint8_t *two = (kb < 10 ? wb : wa) + row, *one = (kb < 10 ? wa : wb) + row;
            const uint8_t* p = nullptr;
            if (lane < 15) p = (sec ? two + 1920 : lane < 10 ? one : two) + lane * 128;
            else if (lane < 31 && kb < 10) p = (const uint8_t*)x + (size_t)(bid * 16 + lane - 15) * 1280 + kb * 128;
            if (p) asm volatile("prefetch.global.L2 [%0];" ::"l"(p));
            __nanosleep(PFNS);
          }
        }
        bar_sync(NB_HELP, 128);
        const uint32_t epoch = *(volatile uint32_t*)(smem + OFF_MISC + 16);
        {
          const int row = mt * 128 + hg * 16 + (ht >> 2), q = ht & 3;
          float acc = 0.f;
#pragma unroll 1
          for (int i0 = 0; i0 < 20; i0 += 5) {
            uint4 xv[5];
#pragma unroll
            for (int i = 0; i < 5; i++) xv[i] = __ldg((const uint4*)(x + (size_t)row * DM + (i0 + i) * 32 + q * 8));
#pragma unroll
            for (int i = 0; i < 5; i++) {
              const uint4 gw = __ldg((const uint4*)(gate_w + (i0 + i) * 32 + q * 8));
              const uint32_t xa[4] = {xv[i].x, xv[i].y, xv[i].z, xv[i].w}, ga[4] = {gw.x, gw.y, gw.z, gw.w};
#pragma unroll
              for (int u = 0; u < 4; u++) {
                uint32_t p;
                asm("mul.rn.bf16x2 %0, %1, %2;" : "=r"(p) : "r"(xa[u]), "r"(ga[u]));
                acc += bf_lo(p) + bf_hi(p);
              }
            }
          }
          acc += __shfl_xor_sync(~0u, acc, 1);
          acc += __shfl_xor_sync(~0u, acc, 2);
          if (q == 0) {
            const float g = bf_round(__fdividef(1.f, 1.f + __expf(-bf_round(acc))));
            g_GATE[row] = make_float2(g, bf_round(1.f - g));
          }
        }
        bar_sync(NB_HELP, 64);
        if (ht == 0) cnt_add(C_GATE + mt);
        PROF(ht == 0, 18);
        if (ht == 0) cnt_wait(C_KVP + hg, 16 * epoch);
        bar_sync(NB_HELP, 64);
        if (ht < 60) {
          const int hd = hg * 4 + ht / 15, e = mt * 30 + (ht % 15) * 2;
          const float2* src = g_KVP + (size_t)hd * 16 * 480 + e;
          float4 s = make_float4(0.f, 0.f, 0.f, 0.f);
#pragma unroll 1
          for (int m0 = 0; m0 < 16; m0 += 4) {
            uint4 v[4];
#pragma unroll
            for (int m = 0; m < 4; m++) v[m] = ldg_cg4(src + (m0 + m) * 480);
#pragma unroll
            for (int m = 0; m < 4; m++) {
              s.x += __uint_as_float(v[m].x); s.y += __uint_as_float(v[m].y); s.z += __uint_as_float(v[m].z); s.w += __uint_as_float(v[m].w);
            }
          }
          *(uint2*)(g_KVB + hd * 480 + e) = make_uint2(packbf(s.x, s.y), packbf(s.z, s.w));
        }
        bar_sync(NB_HELP, 64);
        if (ht == 0) cnt_add(C_KVB + hg);
        PROF(ht == 0, 20);
#pragma unroll 1
        for (int kg = bid; kg < 160; kg += NCTA) {
          const uint8_t* src = (kg < 80 ? woa + (size_t)kg * 10240 : wob + (size_t)(kg - 80) * 10240) + (ht & 7) * 1280 + (ht >> 3) * 16;
          uint8_t* dst = g_WOI + (kg < 80 ? kg : 80 + bgroup(kg - 80)) * 2560 + (ht & 7) * 16;
#pragma unroll 1
          for (int c0 = 0; c0 < 80; c0 += 40) {
            uint4 v[5];
#pragma unroll
            for (int u = 0; u < 5; u++) v[u] = __ldg((const uint4*)(src + (c0 + u * 8) * 16));
#pragma unroll
            for (int u = 0; u < 5; u++) {
              const int c = c0 + u * 8 + (ht >> 3);
              *(uint4*)(dst + (size_t)(c / 20) * 409600 + (c % 20) * 128) = v[u];
            }
          }
        }
        bar_sync(NB_HELP, 64);
        if (ht == 0) cnt_add(C_WO);
        PROF(ht == 0, 19);
      }
    }
  } else {
    reg_inc<232>();
    asm volatile("barrier.cluster.wait.aligned;" ::: "memory");
    const int w4 = warp & 3, t = lane & 3;
    const uint32_t lead = (threadIdx.x & 127) == 0;
    const int rg = wg * 8 + w4 * 2, mi = lane >> 3;
    bool slow;
    {
      const uint32_t sbase = sb + OFF_Q + (rg + (mi & 1)) * 384 + (lane & 7) * 16;
      const uint32_t ad01 = sbase + (mi >> 1) * 128, ad2 = sbase + (mi >> 1) * 6144 + 256;
      float a1[96], a2[24];
      uint32_t fa[4][4] = {}, fb[4][4] = {};
#pragma unroll 1
      for (int tile = 0; tile < 2; tile++) {
#pragma unroll 1
        for (int ks = 0; ks < 10; ks += 2) {
          gemm_step(a1, a2, xa, fa, fb, xp, tile * 10 + ks, ks, sb, bars, lead);
          gemm_step(a1, a2, xb, fb, fa, xp, tile * 10 + ks + 1, 1, sb, bars, lead);
        }
        wg_wait<0>();
        pin(a1); pin(a2);
#pragma unroll
        for (int i = 0; i < 4; i++) pin(fb[i]);
        PROF(threadIdx.x == 0, 2 + 2 * tile);
        if (tile == 0) {
          mbar_arrive_pair(bars + B_WE + 8 * 4, lead);
          float* kmx = g_KMAX + (hg * 4 + (lane & 3)) * 128 + mt * 8 + warp;
          if (hg & 1) epilogue0<4>(a1, a2, rg, lane, ad01, ad2, kmx);
          else epilogue0<0>(a1, a2, rg, lane, ad01, ad2, kmx);
          fence_async_smem();
          bar_arrive(NB_STAGED, 288);
          PROF(threadIdx.x == 0, 3);
        }
      }
#pragma unroll
      for (int s = 2; s < KV_NST; s++) mbar_arrive_if(bars + B_KE + 8 * s, lead);
      uint32_t fk[4][6];
      if (hg & 1) slow = epilogue1<4>(a1, a2, fk, smem, wg, t, ad01, ad2);
      else slow = epilogue1<0>(a1, a2, fk, smem, wg, t, ad01, ad2);
      float pk[4][12];
      wg_fence();
#pragma unroll
      for (int i = 0; i < 4; i++) {
        const uint64_t wd = mkdesc(sb + OFF_WPH + i * 1152, 384, 128, 0);
        mma_n24_rs_tb(pk[i], fk[i][0], fk[i][1], fk[i][2], fk[i][3], wd, 0);
        mma_n24_rs_tb(pk[i], fk[i][4], fk[i][5], 0u, 0u, (wd + 48) & NO_LBO, 1);
      }
      wg_commit();
      mbar_wait_u(bars + B_WE + 8 * 1, 1);
      wg_wait<0>();
#pragma unroll
      for (int i = 0; i < 4; i++) pin(fk[i]);
      const uint32_t pka = sb + (rg + (mi & 1)) * 640 + (mi >> 1) * 128 + (lane & 7) * 16;
#pragma unroll
      for (int i = 0; i < 4; i++) {
        pin(pk[i]);
        uint32_t f[10];
        hedgehog(pk[i], f, t);
        stsm4(pka + i * 10240, f[0], f[1], f[2], f[3]);
        stsm4(pka + i * 10240 + 256, f[4], f[5], f[6], f[7]);
        stsm2(pka + i * 10240 + 512, f[8], f[9]);
      }
      fence_async_smem();
      bar_sync(NB_PHIK, 256);
      float kv[2][12];
      wg_fence();
#pragma unroll
      for (int j = 0; j < 2; j++) {
        const uint64_t ad = mkdesc(sb + (wg * 2 + j) * 10240, 640, 128, 0), vd = mkdesc(sb + OFF_V + (wg * 2 + j) * 6144, 384, 128, 0);
#pragma unroll
        for (int ks = 0; ks < 8; ks++) mma_n24_ss_tatb(kv[j], ad + ks * 80, vd + ks * 48, ks);
      }
      wg_commit();
      wg_wait<0>();
      mbar_arrive_if(bars + B_KE, lead);
      mbar_arrive_if(bars + B_KE + 8, lead);
#pragma unroll
      for (int j = 0; j < 2; j++) {
        pin(kv[j]);
        float2* dst = g_KVP + (size_t)((hg * 4 + wg * 2 + j) * 16 + mt) * 480 + w4 * 192 + lane;
        if (w4 < 3) { dst[0] = make_float2(kv[j][0], kv[j][1]); dst[32] = make_float2(kv[j][4], kv[j][5]); dst[64] = make_float2(kv[j][8], kv[j][9]); }
        if (w4 < 2) { dst[96] = make_float2(kv[j][2], kv[j][3]); dst[128] = make_float2(kv[j][6], kv[j][7]); dst[160] = make_float2(kv[j][10], kv[j][11]); }
      }
      bar_arrive(NB_TAIL, 288);
      PROF(threadIdx.x == 0, 5);
    }
    {
      uint8_t* obase = g_OAB + (size_t)mt * (20 * 16384) + rg * 1024 + lane * 4;
      const uint32_t gate = sb + OFF_GATE + (wg * 64 + w4 * 16 + (lane >> 2)) * 8;
      const uint64_t kd0 = mkdesc(sb, 128, 384, 0), vd0 = mkdesc(sb + 12288, 384, 128, 0);
      const uint64_t qd0 = mkdesc(sb + OFF_Q + wg * 3072, 128, 384, 0);
      float o[12], s0[64];
      mbar_wait_u(bars + B_KF + 8 * 4, 0);
      wg_fence();
      issue_qk(s0, qd0, kd0 + 4 * (KV_CHUNK >> 4));
      wg_commit();
      wg_wait<0>();
      pin(s0);
      int slot = 4, ph = 0;
#pragma unroll 1
      for (int pass = 0; pass < 4; pass++) {
        const uint64_t qd = qd0 + pass * 384;
        if (!slow) {
          float s1[64];
          uint32_t p0[32], p1[32] = {};
#pragma unroll 1
          for (int j = 0; j < 7; j++) {
            const int nx = slot == 5 ? 0 : slot + 1, pv = slot == 0 ? 5 : slot - 1, phn = nx == 4 ? ph ^ 1 : ph;
            attn_pair(s0, s1, p0, p1, o, qd, kd0 + slot * 1536 + 384, vd0 + slot * 1536, qd, kd0 + nx * 1536, j, bars + B_KF + 8 * nx, phn,
                      bars + B_KE + 8 * pv, lead && j, cm, neg1);
            wg_wait<1>();
            pin(s0); pin(p0);
            slot = nx; ph = phn;
          }
          const int last = pass == 3;
          const int nx = last ? slot : (slot == 5 ? 0 : slot + 1), pv = slot == 0 ? 5 : slot - 1, phn = (!last && nx == 4) ? ph ^ 1 : ph;
          attn_pair(s0, s1, p0, p1, o, qd, kd0 + slot * 1536 + 384, vd0 + slot * 1536, last ? qd : qd + 384, kd0 + nx * 1536, 1,
                    bars + B_KF + 8 * nx, phn, bars + B_KE + 8 * pv, lead, cm, neg1);
          wg_wait<0>();
          pin(s0); pin(o); pin(p0); pin(p1);
          mbar_arrive_if(bars + B_KE + 8 * slot, lead);
          slot = nx; ph = phn;
        } else {
          uint32_t p[32];
          float m0 = -INFINITY, m1 = -INFINITY;
#pragma unroll
          for (int i = 0; i < 12; i++) o[i] = 0.f;
#pragma unroll 1
          for (int j = 0; j < 16; j++) {
            mbar_wait_u(bars + B_KF + 8 * slot, ph);
            wg_fence();
            issue_qk(s0, qd, kd0 + slot * 1536 + (j & 1) * 384);
            wg_commit();
            wg_wait<0>();
            pin(s0);
            float n0 = m0, n1 = m1;
#pragma unroll
            for (int g = 0; g < 16; g++) { n0 = fmaxf(n0, fmaxf(s0[4 * g], s0[4 * g + 1])); n1 = fmaxf(n1, fmaxf(s0[4 * g + 2], s0[4 * g + 3])); }
            n0 = fmaxf(n0, __shfl_xor_sync(~0u, n0, 1)); n1 = fmaxf(n1, __shfl_xor_sync(~0u, n1, 1));
            n0 = fmaxf(n0, __shfl_xor_sync(~0u, n0, 2)); n1 = fmaxf(n1, __shfl_xor_sync(~0u, n1, 2));
            const float c0 = ex2(m0 - n0), c1 = ex2(m1 - n1);
            m0 = n0; m1 = n1;
#pragma unroll
            for (int i = 0; i < 3; i++) { o[4 * i] *= c0; o[4 * i + 1] *= c0; o[4 * i + 2] *= c1; o[4 * i + 3] *= c1; }
#pragma unroll
            for (int g = 0; g < 16; g++) {
              const uint32_t sg = ((POLY_MASK >> g) & 1) ? 0x80008000u : 0u;
              p[2 * g] = packbf(ex2(s0[4 * g] - m0), ex2(s0[4 * g + 1] - m0)) ^ sg;
              p[2 * g + 1] = packbf(ex2(s0[4 * g + 2] - m1), ex2(s0[4 * g + 3] - m1)) ^ sg;
            }
            wg_fence();
            issue_pv(o, p, vd0 + slot * 1536 + (j & 1) * 384, 1);
            wg_commit();
            wg_wait<0>();
            pin(o); pin(p);
            if (j & 1) {
              mbar_arrive_if(bars + B_KE + 8 * slot, lead);
              slot = slot == 5 ? 0 : slot + 1;
              if (slot == 4) ph ^= 1;
            }
          }
        }
        if (pass == 0) bar_sync(NB_GATE + wg, 160);
        store_o<true>(o, hg * 4 + pass, obase, lane, 0.f, lds_f2(gate).y, lds_f2(gate + 64).y);
        PROF(threadIdx.x == 0, 6 + pass);
        if (pass == 1 + wg) {
          float pq[4][12];
          wg_fence();
#pragma unroll
          for (int i = 0; i < 4; i++) {
            const uint64_t ad = mkdesc(sb + OFF_AQ + i * 6144 + wg * 3072, 128, 384, 0), wd = mkdesc(sb + OFF_WPH + i * 1152, 384, 128, 0);
            mma_n24_ss_tb(pq[i], ad, wd, 0);
            mma_n24_ss_tb(pq[i], (ad + 16) & NO_LBO, (wd + 48) & NO_LBO, 1);
          }
          wg_commit();
          bar_sync(NB_KVB + wg, 160);
          wg_wait<0>();
          uint32_t f[4][10];
#pragma unroll
          for (int i = 0; i < 4; i++) { pin(pq[i]); hedgehog(pq[i], f[i], t); }
#pragma unroll
          for (int i = 0; i < 4; i++) pin(f[i]);
          wg_fence();
#pragma unroll
          for (int i = 0; i < 4; i++) {
            const uint64_t kvd = mkdesc(sb + OFF_V + i * 1920, 384, 128, 0);
            mma_n24_rs_tb(pq[i], f[i][0], f[i][1], f[i][2], f[i][3], kvd, 0);
            mma_n24_rs_tb(pq[i], f[i][4], f[i][5], f[i][6], f[i][7], kvd + 48, 1);
            mma_n24_rs_tb(pq[i], f[i][8], f[i][9], 0u, 0u, (kvd + 96) & NO_LBO, 1);
          }
          wg_commit();
          wg_wait<0>();
#pragma unroll
          for (int i = 0; i < 4; i++) pin(f[i]);
          const float g0 = lds_f2(gate).x, g1 = lds_f2(gate + 64).x;
#pragma unroll
          for (int i = 0; i < 4; i++) { pin(pq[i]); store_o<false>(pq[i], hg * 4 + i, obase, lane, 1e-6f, g0, g1); }
        }
        if (pass == 2) bar_arrive(NB_READ, 288);
      }
      bar_arrive(NB_LAST, 288);
    }
    {
      asm volatile("barrier.cluster.arrive.relaxed.aligned;" ::: "memory");
      float acc[80];
#pragma unroll 1
      for (int it = 0; it < 10; it++) {
        const int s = it % 5;
        mbar_wait_u(bars + B_OF + 8 * s, it / 5);
        PROF(threadIdx.x == 0 && (it == 0 || it == 8), 10 + it / 8);
        const uint32_t st = s == 0 ? sb + OFF_V : sb + (s - 1) * O_STAGE;
        const uint64_t ad = mkdesc(st + wg * 8192, 128, 1024, 0), bd = mkdesc(st + 16384, 2560, 128, 0);
        wg_fence();
#pragma unroll
        for (int kk = 0; kk < 4; kk++) mma_n160_ss_tb(acc, ad + kk * 16, bd + kk * 320, it | kk);
        wg_commit();
        wg_wait<1>();
        mbar_arrive_if(bars + B_OE + 8 * ((it + 4) % 5), lead && it);
      }
      wg_wait<0>();
      pin(acc);
      PROF(threadIdx.x == 0, 12);
      asm volatile("barrier.cluster.wait.aligned;" ::: "memory");
      uint32_t remote;
      asm volatile("mapa.shared::cluster.u32 %0, %1, %2;" : "=r"(remote) : "r"(sb + OFF_Q + threadIdx.x * 16), "r"(half ^ 1));
#pragma unroll
      for (int j = 0; j < 5; j++) {
        uint32_t v[4];
#pragma unroll
        for (int u = 0; u < 4; u++) v[u] = half ? packbf(acc[8 * j + 2 * u], acc[8 * j + 2 * u + 1]) : packbf(acc[40 + 8 * j + 2 * u], acc[41 + 8 * j + 2 * u]);
        asm volatile("st.shared::cluster.v4.b32 [%0], {%1,%2,%3,%4};" ::"r"(remote + j * 4096), "r"(v[0]), "r"(v[1]), "r"(v[2]), "r"(v[3]) : "memory");
      }
      asm volatile("barrier.cluster.arrive.release.aligned;" ::: "memory");
      asm volatile("barrier.cluster.wait.acquire.aligned;" ::: "memory");
      PROF(threadIdx.x == 0, 13);
      const uint32_t ob = sb + wg * 10240;
      const uint32_t oa = ob + (w4 * 16 + (lane & 15)) * 160 + (lane >> 4) * 16;
      uint32_t pk[20];
#pragma unroll
      for (int j = 0; j < 5; j++) {
        const uint4 r = *(const uint4*)(smem + OFF_Q + j * 4096 + threadIdx.x * 16);
        const uint32_t rv[4] = {r.x, r.y, r.z, r.w};
#pragma unroll
        for (int u = 0; u < 4; u++) {
          const float v0 = half ? acc[40 + 8 * j + 2 * u] : acc[8 * j + 2 * u], v1 = half ? acc[41 + 8 * j + 2 * u] : acc[8 * j + 2 * u + 1];
          pk[4 * j + u] = packbf(v0 + bf_lo(rv[u]), v1 + bf_hi(rv[u]));
        }
      }
#pragma unroll
      for (int j = 0; j < 10; j += 2) stsm4(oa + j * 16, pk[2 * j], pk[2 * j + 1], pk[2 * j + 2], pk[2 * j + 3]);
      fence_async_smem();
      bar_sync(NB_WG + wg, 128);
      if (lead) {
        asm volatile("cp.async.bulk.tensor.2d.global.shared::cta.bulk_group [%0, {%2,%3}], [%1];" ::"l"(&maps.out), "r"(ob), "r"(nt * 160 + half * 80),
                     "r"(mt3 * 128 + wg * 64) : "memory");
        asm volatile("cp.async.bulk.commit_group;" ::: "memory");
        asm volatile("cp.async.bulk.wait_group.read 0;" ::: "memory");
      }
      PROF(threadIdx.x == 0, 14);
    }
  }
}

typedef CUresult (*EncodeFn)(CUtensorMap*, CUtensorMapDataType, cuuint32_t, void*, const cuuint64_t*, const cuuint64_t*, const cuuint32_t*,
                             const cuuint32_t*, CUtensorMapInterleave, CUtensorMapSwizzle, CUtensorMapL2promotion, CUtensorMapFloatOOBfill);

void encode(EncodeFn fn, CUtensorMap* m, const void* p, int rank, const cuuint64_t* dims, const cuuint64_t* strides, const cuuint32_t* box,
            CUtensorMapSwizzle sw) {
  const cuuint32_t es[5] = {1, 1, 1, 1, 1};
  fn(m, CU_TENSOR_MAP_DATA_TYPE_BFLOAT16, rank, const_cast<void*>(p), dims, strides, box, es, CU_TENSOR_MAP_INTERLEAVE_NONE, sw,
     CU_TENSOR_MAP_L2_PROMOTION_L2_128B, CU_TENSOR_MAP_FLOAT_OOB_FILL_NONE);
}

}

extern "C" void kernel_launch(void* const* d_in, const int* in_sizes, int n_in, void* d_out, int out_size) {
  (void)in_sizes; (void)n_in; (void)out_size;
  static EncodeFn enc = nullptr;
  if (!enc) {
    void* fn = nullptr;
    cudaDriverEntryPointQueryResult qr;
    cudaGetDriverEntryPoint("cuTensorMapEncodeTiled", &fn, cudaEnableDefault, &qr);
    enc = (EncodeFn)fn;
    cudaFuncSetAttribute(fused_block, cudaFuncAttributeMaxDynamicSharedMemorySize, SMEM_BYTES);
  }
  Maps maps;
  {
    const cuuint64_t dx[2] = {640, 2048}, sx[1] = {1280};
    const cuuint32_t bo[2] = {80, 64};
    encode(enc, &maps.out, d_out, 2, dx, sx, bo, CU_TENSOR_MAP_SWIZZLE_NONE);
    const cuuint64_t dw[5] = {1920, 2, 4, 4, 20}, sw[4] = {3840, 8 * 3840, 2 * 3840, 32 * 3840};
    const cuuint32_t b64[5] = {64, 2, 4, 4, 2}, b16[5] = {16, 2, 4, 4, 2};
    encode(enc, &maps.a64, d_in[1], 5, dw, sw, b64, CU_TENSOR_MAP_SWIZZLE_128B);
    encode(enc, &maps.a16, d_in[1], 5, dw, sw, b16, CU_TENSOR_MAP_SWIZZLE_32B);
    encode(enc, &maps.b64, d_in[5], 5, dw, sw, b64, CU_TENSOR_MAP_SWIZZLE_128B);
    encode(enc, &maps.b16, d_in[5], 5, dw, sw, b16, CU_TENSOR_MAP_SWIZZLE_32B);
  }
  fused_block<<<NCTA, 384, SMEM_BYTES, cudaStreamPerThread>>>(maps, (const __nv_bfloat16*)d_in[0], (const __nv_bfloat16*)d_in[2],
                                                               (const __nv_bfloat16*)d_in[7], (const uint8_t*)d_in[1], (const uint8_t*)d_in[5],
                                                               (const uint8_t*)d_in[3], (const uint8_t*)d_in[6], 0x1F801F80u, 0xFFFFFFFFu);
}
```

```cpp
#include <cuda_runtime.h>
#include <cuda_bf16.h>
#include <cuda.h>
#include <stdint.h>

namespace {

constexpr int SEQ = 2048, DM = 640, NH = 32, NCTA = 128;
constexpr int IMG_HEAD = SEQ * 48;
#define POLY_MASK 0x76DDu
constexpr float LOG2E = 1.4426950408889634f;
constexpr float QSCALE = 0.22360679774997896f * 1.4426950408889634f;
constexpr uint32_t BF_ONE = 0x3F80u;
constexpr uint32_t BF_MAGIC = 0x43E0u;
constexpr uint32_t BF_MU_HI = 0x4025u;
constexpr uint32_t BF_MU_LO = 0x3B8Bu;
constexpr float FAST_BOUND = 40.0f;

__device__ __align__(1024) uint8_t g_KV[2 * NH * IMG_HEAD];
__device__ __align__(1024) float2 g_KVP[NH * 16 * 480];
__device__ __align__(1024) uint32_t g_KVB[NH * 480];
__device__ __align__(1024) float4 g_KMAX[8 * 16];
__device__ __align__(1024) float2 g_GATE[SEQ];
__device__ __align__(1024) uint8_t g_OAB[16 * 2 * 160 * 1024];
__device__ __align__(1024) uint8_t g_WOI[4 * 409600];
__device__ __align__(1024) uint32_t g_CNT[80 * 8];
constexpr int C_START = 0, C_WO = 1, C_KV = 2, C_KVP = 10, C_KVB = 18, C_GATE = 26, C_OA = 42, C_OB = 58;

#define SPIN_LIMIT (1ll << 29)
#define SPIN_FAIL(code) __trap()
#define PROF(cond, slot)
__device__ __forceinline__ uint32_t smem_u32(const void* p) { return (uint32_t)__cvta_generic_to_shared(p); }
__device__ __forceinline__ void mbar_init(uint32_t a, uint32_t c) { asm volatile("mbarrier.init.shared::cta.b64 [%0], %1;" ::"r"(a), "r"(c) : "memory"); }
__device__ __forceinline__ void mbar_expect(uint32_t a, uint32_t b) { asm volatile("mbarrier.arrive.expect_tx.shared::cta.b64 _, [%0], %1;" ::"r"(a), "r"(b) : "memory"); }
__device__ __forceinline__ void mbar_arrive(uint32_t a) { asm volatile("mbarrier.arrive.shared::cta.b64 _, [%0];" ::"r"(a) : "memory"); }
__device__ __forceinline__ uint32_t mbar_try(uint32_t a, uint32_t ph) {
  uint32_t ok;
  asm volatile("{\n.reg .pred p;\nmbarrier.try_wait.parity.shared::cta.b64 p, [%1], %2;\nselp.u32 %0, 1, 0, p;\n}\n" : "=r"(ok) : "r"(a), "r"(ph) : "memory");
  return ok;
}
__device__ __forceinline__ void mbar_wait(uint32_t a, uint32_t ph) {
  if (mbar_try(a, ph)) return;
  const long long t0 = clock64();
  while (!mbar_try(a, ph))
    if (clock64() - t0 > SPIN_LIMIT) { SPIN_FAIL(1000 + (a & 0x1FF) * 2 + ph); break; }
}
__device__ __forceinline__ void mbar_wait_u(uint32_t a, uint32_t ph) {
#pragma unroll 1
  for (int n = 0; n < (1 << 18); n++)
    if (__all_sync(~0u, mbar_try(a, ph))) break;
}
__device__ __forceinline__ uint32_t mbar_wait_z(uint32_t a, uint32_t ph) {
  uint32_t ok = 0;
#pragma unroll 1
  for (int n = 0; n < (1 << 18); n++) {
    ok = mbar_try(a, ph);
    if (__all_sync(~0u, ok)) break;
  }
  return ok - 1;
}
__device__ __forceinline__ uint32_t mbar_test(uint32_t a, uint32_t ph) {
  uint32_t ok;
  asm volatile("{\n.reg .pred p;\nmbarrier.test_wait.parity.shared::cta.b64 p, [%1], %2;\nselp.u32 %0, 1, 0, p;\n}\n" : "=r"(ok) : "r"(a), "r"(ph) : "memory");
  return ok;
}
__device__ __forceinline__ void mbar_arrive_if(uint32_t a, uint32_t flag) {
  asm volatile("{\n.reg .pred p;\nsetp.ne.u32 p, %1, 0;\n@p mbarrier.arrive.shared::cta.b64 _, [%0];\n}\n" ::"r"(a), "r"(flag) : "memory");
}
__device__ __forceinline__ void cnt_add_done(int slot) { asm volatile("red.relaxed.gpu.global.add.u32 [%0], 1;" ::"l"(g_CNT + slot * 8) : "memory"); }
__device__ __forceinline__ void cnt_add(int slot) {
  asm volatile("fence.acq_rel.gpu;" ::: "memory");
  cnt_add_done(slot);
}
__device__ __forceinline__ void cnt_wait(int slot, uint32_t target) {
  uint32_t v;
  long long t0 = 0;
  for (;;) {
    asm volatile("ld.relaxed.gpu.global.u32 %0, [%1];" : "=r"(v) : "l"(g_CNT + slot * 8) : "memory");
    if ((int32_t)(v - target) >= 0) break;
    __nanosleep(40);
    if (!t0) t0 = clock64();
    else if (clock64() - t0 > SPIN_LIMIT) { SPIN_FAIL(slot); break; }
  }
  asm volatile("ld.acquire.gpu.global.u32 %0, [%1];" : "=r"(v) : "l"(g_CNT + slot * 8) : "memory");
}
__device__ __forceinline__ void bulk_commit_wait() { asm volatile("cp.async.bulk.commit_group;\ncp.async.bulk.wait_group 0;" ::: "memory"); }
__device__ __forceinline__ void tma5(uint32_t dst, const CUtensorMap* m, int c0, int c4, uint32_t bar) {
  asm volatile("cp.async.bulk.tensor.5d.shared::cluster.global.mbarrier::complete_tx::bytes [%0], [%1, {%3,%5,%5,%5,%4}], [%2];" ::"r"(dst), "l"(m), "r"(bar), "r"(c0), "r"(c4), "r"(0) : "memory");
}
__device__ __forceinline__ void bulk_g2s(uint32_t dst, const void* src, uint32_t bytes, uint32_t bar) {
  asm volatile("cp.async.bulk.shared::cluster.global.mbarrier::complete_tx::bytes [%0], [%1], %2, [%3];" ::"r"(dst), "l"(src), "r"(bytes), "r"(bar) : "memory");
}
__device__ __forceinline__ void fence_async_smem() { asm volatile("fence.proxy.async.shared::cta;" ::: "memory"); }
__device__ __forceinline__ void bar_sync(int id, int n) { asm volatile("bar.sync %0, %1;" ::"r"(id), "r"(n) : "memory"); }
__device__ __forceinline__ void bar_arrive(int id, int n) { asm volatile("bar.arrive %0, %1;" ::"r"(id), "r"(n) : "memory"); }
__device__ __forceinline__ void wg_fence() { asm volatile("wgmma.fence.sync.aligned;" ::: "memory"); }
__device__ __forceinline__ void wg_commit() { asm volatile("wgmma.commit_group.sync.aligned;" ::: "memory"); }
template <int N> __device__ __forceinline__ void wg_wait() { asm volatile("wgmma.wait_group.sync.aligned %0;" ::"n"(N) : "memory"); }
template <int N> __device__ __forceinline__ void reg_inc() { asm volatile("setmaxnreg.inc.sync.aligned.u32 %0;" ::"n"(N)); }
template <int N> __device__ __forceinline__ void reg_dec() { asm volatile("setmaxnreg.dec.sync.aligned.u32 %0;" ::"n"(N)); }
template <int N> __device__ __forceinline__ void pin(float (&r)[N]) {
#pragma unroll
  for (int i = 0; i < N; i++) asm volatile("" : "+f"(r[i])::"memory");
}
template <int N> __device__ __forceinline__ void pin(uint32_t (&r)[N]) {
#pragma unroll
  for (int i = 0; i < N; i++) asm volatile("" : "+r"(r[i])::"memory");
}
__device__ __forceinline__ uint64_t mkdesc(uint32_t addr, uint32_t lbo, uint32_t sbo, uint32_t swz) {
  return (uint64_t)((addr & 0x3FFFF) >> 4) | ((uint64_t)(lbo >> 4) << 16) | ((uint64_t)(sbo >> 4) << 32) | ((uint64_t)swz << 62);
}
__device__ __forceinline__ float ex2(float x) { float y; asm("ex2.approx.ftz.f32 %0, %1;" : "=f"(y) : "f"(x)); return y; }
__device__ __forceinline__ float rcp(float x) { float y; asm("rcp.approx.ftz.f32 %0, %1;" : "=f"(y) : "f"(x)); return y; }
__device__ __forceinline__ float sqrt_ap(float x) { float y; asm("sqrt.approx.f32 %0, %1;" : "=f"(y) : "f"(x)); return y; }
__device__ __forceinline__ uint32_t packbf(float lo, float hi) { uint32_t d; asm("cvt.rn.bf16x2.f32 %0, %1, %2;" : "=r"(d) : "f"(hi), "f"(lo)); return d; }
__device__ __forceinline__ float bf_lo(uint32_t v) { return __uint_as_float(v << 16); }
__device__ __forceinline__ float bf_hi(uint32_t v) { return __uint_as_float(v & 0xFFFF0000u); }
__device__ __forceinline__ float bf_round(float x) { return bf_lo(packbf(x, 0.f)); }
__device__ __forceinline__ uint4 ldg_cg4(const void* p) { uint4 v; asm volatile("ld.global.cg.v4.b32 {%0,%1,%2,%3}, [%4];" : "=r"(v.x), "=r"(v.y), "=r"(v.z), "=r"(v.w) : "l"(p) : "memory"); return v; }
__device__ __forceinline__ void sts32(uint32_t a, uint32_t v) { asm volatile("st.shared.b32 [%0], %1;" ::"r"(a), "r"(v) : "memory"); }
__device__ __forceinline__ void stsm4(uint32_t a, uint32_t r0, uint32_t r1, uint32_t r2, uint32_t r3) {
  asm volatile("stmatrix.sync.aligned.m8n8.x4.shared.b16 [%0], {%1,%2,%3,%4};" ::"r"(a), "r"(r0), "r"(r1), "r"(r2), "r"(r3) : "memory");
}

__device__ __forceinline__ void stsm2(uint32_t a, uint32_t r0, uint32_t r1) {
  asm volatile("stmatrix.sync.aligned.m8n8.x2.shared.b16 [%0], {%1,%2};" ::"r"(a), "r"(r0), "r"(r1) : "memory");
}
__device__ __forceinline__ uint4 ldg_x(const void* p) {
  uint4 v;
  asm volatile("ld.global.nc.L1::no_allocate.L2::128B.v4.b32 {%0,%1,%2,%3}, [%4];" : "=r"(v.x), "=r"(v.y), "=r"(v.z), "=r"(v.w) : "l"(p));
  return v;
}
__device__ __forceinline__ float2 lds_f2(uint32_t a) { float2 v; asm volatile("ld.shared.v2.f32 {%0,%1}, [%2];" : "=f"(v.x), "=f"(v.y) : "r"(a) : "memory"); return v; }
__device__ __forceinline__ void bulk_s2g(void* dst, uint32_t src, uint32_t bytes) {
  asm volatile("cp.async.bulk.global.shared::cta.bulk_group [%0], [%1], %2;" ::"l"(dst), "r"(src), "r"(bytes) : "memory");
}

__device__ __forceinline__ void mma_n24_ss_tb(float (&d)[12], uint64_t adesc, uint64_t bdesc, int acc) {
  asm volatile("{\n.reg .pred p;\nsetp.ne.b32 p, %14, 0;\n"
      "wgmma.mma_async.sync.aligned.m64n24k16.f32.bf16.bf16 "
      "{%0,%1,%2,%3,%4,%5,%6,%7,%8,%9,%10,%11}, "
      "%12, %13, p, 1, 1, 0, 1;\n}\n"
      : "+f"(d[0]), "+f"(d[1]), "+f"(d[2]), "+f"(d[3]), "+f"(d[4]), "+f"(d[5]), "+f"(d[6]), "+f"(d[7]),
        "+f"(d[8]), "+f"(d[9]), "+f"(d[10]), "+f"(d[11])
      : "l"(adesc), "l"(bdesc), "r"(acc));
}
__device__ __forceinline__ void mma_n192_rs_tb(float (&d)[96], uint32_t a0, uint32_t a1, uint32_t a2, uint32_t a3, uint64_t bdesc, int acc) {
  asm volatile("{\n.reg .pred p;\nsetp.ne.b32 p, %101, 0;\n"
      "wgmma.mma_async.sync.aligned.m64n192k16.f32.bf16.bf16 "
      "{%0,%1,%2,%3,%4,%5,%6,%7,%8,%9,%10,%11,%12,%13,%14,%15,"
      "%16,%17,%18,%19,%20,%21,%22,%23,%24,%25,%26,%27,%28,%29,%30,%31,"
      "%32,%33,%34,%35,%36,%37,%38,%39,%40,%41,%42,%43,%44,%45,%46,%47,"
      "%48,%49,%50,%51,%52,%53,%54,%55,%56,%57,%58,%59,%60,%61,%62,%63,"
      "%64,%65,%66,%67,%68,%69,%70,%71,%72,%73,%74,%75,%76,%77,%78,%79,"
      "%80,%81,%82,%83,%84,%85,%86,%87,%88,%89,%90,%91,%92,%93,%94,%95}, "
      "{%96,%97,%98,%99}, %100, p, 1, 1, 1;\n}\n"
      : "+f"(d[0]), "+f"(d[1]), "+f"(d[2]), "+f"(d[3]), "+f"(d[4]), "+f"(d[5]), "+f"(d[6]), "+f"(d[7]),
        "+f"(d[8]), "+f"(d[9]), "+f"(d[10]), "+f"(d[11]), "+f"(d[12]), "+f"(d[13]), "+f"(d[14]), "+f"(d[15]),
        "+f"(d[16]), "+f"(d[17]), "+f"(d[18]), "+f"(d[19]), "+f"(d[20]), "+f"(d[21]), "+f"(d[22]), "+f"(d[23]),
        "+f"(d[24]), "+f"(d[25]), "+f"(d[26]), "+f"(d[27]), "+f"(d[28]), "+f"(d[29]), "+f"(d[30]), "+f"(d[31]),
        "+f"(d[32]), "+f"(d[33]), "+f"(d[34]), "+f"(d[35]), "+f"(d[36]), "+f"(d[37]), "+f"(d[38]), "+f"(d[39]),
        "+f"(d[40]), "+f"(d[41]), "+f"(d[42]), "+f"(d[43]), "+f"(d[44]), "+f"(d[45]), "+f"(d[46]), "+f"(d[47]),
        "+f"(d[48]), "+f"(d[49]), "+f"(d[50]), "+f"(d[51]), "+f"(d[52]), "+f"(d[53]), "+f"(d[54]), "+f"(d[55]),
        "+f"(d[56]), "+f"(d[57]), "+f"(d[58]), "+f"(d[59]), "+f"(d[60]), "+f"(d[61]), "+f"(d[62]), "+f"(d[63]),
        "+f"(d[64]), "+f"(d[65]), "+f"(d[66]), "+f"(d[67]), "+f"(d[68]), "+f"(d[69]), "+f"(d[70]), "+f"(d[71]),
        "+f"(d[72]), "+f"(d[73]), "+f"(d[74]), "+f"(d[75]), "+f"(d[76]), "+f"(d[77]), "+f"(d[78]), "+f"(d[79]),
        "+f"(d[80]), "+f"(d[81]), "+f"(d[82]), "+f"(d[83]), "+f"(d[84]), "+f"(d[85]), "+f"(d[86]), "+f"(d[87]),
        "+f"(d[88]), "+f"(d[89]), "+f"(d[90]), "+f"(d[91]), "+f"(d[92]), "+f"(d[93]), "+f"(d[94]), "+f"(d[95])
      : "r"(a0), "r"(a1), "r"(a2), "r"(a3), "l"(bdesc), "r"(acc));
}
__device__ __forceinline__ void mma_n48_rs_tb(float (&d)[24], uint32_t a0, uint32_t a1, uint32_t a2, uint32_t a3, uint64_t bdesc, int acc) {
  asm volatile("{\n.reg .pred p;\nsetp.ne.b32 p, %29, 0;\n"
      "wgmma.mma_async.sync.aligned.m64n48k16.f32.bf16.bf16 "
      "{%0,%1,%2,%3,%4,%5,%6,%7,%8,%9,%10,%11,%12,%13,%14,%15,"
      "%16,%17,%18,%19,%20,%21,%22,%23}, "
      "{%24,%25,%26,%27}, %28, p, 1, 1, 1;\n}\n"
      : "+f"(d[0]), "+f"(d[1]), "+f"(d[2]), "+f"(d[3]), "+f"(d[4]), "+f"(d[5]), "+f"(d[6]), "+f"(d[7]),
        "+f"(d[8]), "+f"(d[9]), "+f"(d[10]), "+f"(d[11]), "+f"(d[12]), "+f"(d[13]), "+f"(d[14]), "+f"(d[15]),
        "+f"(d[16]), "+f"(d[17]), "+f"(d[18]), "+f"(d[19]), "+f"(d[20]), "+f"(d[21]), "+f"(d[22]), "+f"(d[23])
      : "r"(a0), "r"(a1), "r"(a2), "r"(a3), "l"(bdesc), "r"(acc));
}
__device__ __forceinline__ void mma_n128_ss(float (&d)[64], uint64_t adesc, uint64_t bdesc, int acc) {
  asm volatile("{\n.reg .pred p;\nsetp.ne.b32 p, %66, 0;\n"
      "wgmma.mma_async.sync.aligned.m64n128k16.f32.bf16.bf16 "
      "{%0,%1,%2,%3,%4,%5,%6,%7,%8,%9,%10,%11,%12,%13,%14,%15,"
      "%16,%17,%18,%19,%20,%21,%22,%23,%24,%25,%26,%27,%28,%29,%30,%31,"
      "%32,%33,%34,%35,%36,%37,%38,%39,%40,%41,%42,%43,%44,%45,%46,%47,"
      "%48,%49,%50,%51,%52,%53,%54,%55,%56,%57,%58,%59,%60,%61,%62,%63}, "
      "%64, %65, p, 1, 1, 0, 0;\n}\n"
      : "+f"(d[0]), "+f"(d[1]), "+f"(d[2]), "+f"(d[3]), "+f"(d[4]), "+f"(d[5]), "+f"(d[6]), "+f"(d[7]),
        "+f"(d[8]), "+f"(d[9]), "+f"(d[10]), "+f"(d[11]), "+f"(d[12]), "+f"(d[13]), "+f"(d[14]), "+f"(d[15]),
        "+f"(d[16]), "+f"(d[17]), "+f"(d[18]), "+f"(d[19]), "+f"(d[20]), "+f"(d[21]), "+f"(d[22]), "+f"(d[23]),
        "+f"(d[24]), "+f"(d[25]), "+f"(d[26]), "+f"(d[27]), "+f"(d[28]), "+f"(d[29]), "+f"(d[30]), "+f"(d[31]),
        "+f"(d[32]), "+f"(d[33]), "+f"(d[34]), "+f"(d[35]), "+f"(d[36]), "+f"(d[37]), "+f"(d[38]), "+f"(d[39]),
        "+f"(d[40]), "+f"(d[41]), "+f"(d[42]), "+f"(d[43]), "+f"(d[44]), "+f"(d[45]), "+f"(d[46]), "+f"(d[47]),
        "+f"(d[48]), "+f"(d[49]), "+f"(d[50]), "+f"(d[51]), "+f"(d[52]), "+f"(d[53]), "+f"(d[54]), "+f"(d[55]),
        "+f"(d[56]), "+f"(d[57]), "+f"(d[58]), "+f"(d[59]), "+f"(d[60]), "+f"(d[61]), "+f"(d[62]), "+f"(d[63])
      : "l"(adesc), "l"(bdesc), "r"(acc));
}
__device__ __forceinline__ void mma_n160_ss_tb(float (&d)[80], uint64_t adesc, uint64_t bdesc, int acc) {
  asm volatile("{\n.reg .pred p;\nsetp.ne.b32 p, %82, 0;\n"
      "wgmma.mma_async.sync.aligned.m64n160k16.f32.bf16.bf16 "
      "{%0,%1,%2,%3,%4,%5,%6,%7,%8,%9,%10,%11,%12,%13,%14,%15,"
      "%16,%17,%18,%19,%20,%21,%22,%23,%24,%25,%26,%27,%28,%29,%30,%31,"
      "%32,%33,%34,%35,%36,%37,%38,%39,%40,%41,%42,%43,%44,%45,%46,%47,"
      "%48,%49,%50,%51,%52,%53,%54,%55,%56,%57,%58,%59,%60,%61,%62,%63,"
      "%64,%65,%66,%67,%68,%69,%70,%71,%72,%73,%74,%75,%76,%77,%78,%79}, "
      "%80, %81, p, 1, 1, 0, 1;\n}\n"
      : "+f"(d[0]), "+f"(d[1]), "+f"(d[2]), "+f"(d[3]), "+f"(d[4]), "+f"(d[5]), "+f"(d[6]), "+f"(d[7]),
        "+f"(d[8]), "+f"(d[9]), "+f"(d[10]), "+f"(d[11]), "+f"(d[12]), "+f"(d[13]), "+f"(d[14]), "+f"(d[15]),
        "+f"(d[16]), "+f"(d[17]), "+f"(d[18]), "+f"(d[19]), "+f"(d[20]), "+f"(d[21]), "+f"(d[22]), "+f"(d[23]),
        "+f"(d[24]), "+f"(d[25]), "+f"(d[26]), "+f"(d[27]), "+f"(d[28]), "+f"(d[29]), "+f"(d[30]), "+f"(d[31]),
        "+f"(d[32]), "+f"(d[33]), "+f"(d[34]), "+f"(d[35]), "+f"(d[36]), "+f"(d[37]), "+f"(d[38]), "+f"(d[39]),
        "+f"(d[40]), "+f"(d[41]), "+f"(d[42]), "+f"(d[43]), "+f"(d[44]), "+f"(d[45]), "+f"(d[46]), "+f"(d[47]),
        "+f"(d[48]), "+f"(d[49]), "+f"(d[50]), "+f"(d[51]), "+f"(d[52]), "+f"(d[53]), "+f"(d[54]), "+f"(d[55]),
        "+f"(d[56]), "+f"(d[57]), "+f"(d[58]), "+f"(d[59]), "+f"(d[60]), "+f"(d[61]), "+f"(d[62]), "+f"(d[63]),
        "+f"(d[64]), "+f"(d[65]), "+f"(d[66]), "+f"(d[67]), "+f"(d[68]), "+f"(d[69]), "+f"(d[70]), "+f"(d[71]),
        "+f"(d[72]), "+f"(d[73]), "+f"(d[74]), "+f"(d[75]), "+f"(d[76]), "+f"(d[77]), "+f"(d[78]), "+f"(d[79])
      : "l"(adesc), "l"(bdesc), "r"(acc));
}
__device__ __forceinline__ void mma_n24_rs_tb(float (&d)[12], uint32_t a0, uint32_t a1, uint32_t a2, uint32_t a3, uint64_t bdesc, int acc) {
  asm volatile("{\n.reg .pred p;\nsetp.ne.b32 p, %17, 0;\n"
      "wgmma.mma_async.sync.aligned.m64n24k16.f32.bf16.bf16 "
      "{%0,%1,%2,%3,%4,%5,%6,%7,%8,%9,%10,%11}, "
      "{%12,%13,%14,%15}, %16, p, 1, 1, 1;\n}\n"
      : "+f"(d[0]), "+f"(d[1]), "+f"(d[2]), "+f"(d[3]), "+f"(d[4]), "+f"(d[5]), "+f"(d[6]), "+f"(d[7]),
        "+f"(d[8]), "+f"(d[9]), "+f"(d[10]), "+f"(d[11])
      : "r"(a0), "r"(a1), "r"(a2), "r"(a3), "l"(bdesc), "r"(acc));
}
__device__ __forceinline__ void mma_n24_ss_tatb(float (&d)[12], uint64_t adesc, uint64_t bdesc, int acc) {
  asm volatile("{\n.reg .pred p;\nsetp.ne.b32 p, %14, 0;\n"
      "wgmma.mma_async.sync.aligned.m64n24k16.f32.bf16.bf16 "
      "{%0,%1,%2,%3,%4,%5,%6,%7,%8,%9,%10,%11}, "
      "%12, %13, p, 1, 1, 1, 1;\n}\n"
      : "+f"(d[0]), "+f"(d[1]), "+f"(d[2]), "+f"(d[3]), "+f"(d[4]), "+f"(d[5]), "+f"(d[6]), "+f"(d[7]),
        "+f"(d[8]), "+f"(d[9]), "+f"(d[10]), "+f"(d[11])
      : "l"(adesc), "l"(bdesc), "r"(acc));
}

constexpr int W_STAGE = 30720, W_NST = 5;
constexpr int KV_CHUNK = 24576;
constexpr int O_STAGE = 36864;
constexpr int OFF_AK = 3 * KV_CHUNK;
constexpr int OFF_PHK = 4 * KV_CHUNK;
constexpr int OFF_GATE = 112640;
constexpr int OFF_Q = W_NST * W_STAGE;
constexpr int OFF_V = OFF_Q + 24576;
constexpr int OFF_AQ = OFF_V + 24576;
constexpr int OFF_WPH = OFF_AQ + 24576;
constexpr int OFF_BAR = OFF_WPH + 4608;
constexpr int B_WF = 0, B_WE = 40, B_KF = 80, B_KE = 112, B_OF = 144, B_OE = 184, B_RF = 224;
constexpr int OFF_MISC = OFF_BAR + 240;
constexpr int SMEM_BYTES = OFF_MISC + 32 + 128;
__device__ __forceinline__ uint32_t o_stage(int s) { return s == 0 ? OFF_V : s == 1 ? OFF_Q - O_STAGE : (s - 2) * O_STAGE; }
constexpr int NB_STAGED = 1, NB_FREE = 2, NB_WG = 3, NB_PHIK = 5, NB_TAIL = 6, NB_GATE = 7, NB_KVB = 9, NB_READ = 11, NB_HELP = 13, NB_LAST = 14;

template <int SEC, int J, int HF>
__device__ __forceinline__ float2 grp(const float (&a1)[96], const float (&a2)[24]) {
  constexpr int S = SEC & 3, J1 = (SEC & 4) ? J - 2 : J, J2 = (SEC & 4) ? J : J - 8;
  if constexpr (J1 >= 0 && J1 < 8) return make_float2(a1[(8 * S + J1) * 4 + 2 * HF], a1[(8 * S + J1) * 4 + 2 * HF + 1]);
  else return make_float2(a2[(2 * S + J2) * 4 + 2 * HF], a2[(2 * S + J2) * 4 + 2 * HF + 1]);
}
__device__ __forceinline__ float sq2(float2 v) { return fmaf(v.x, v.x, v.y * v.y); }
__device__ __forceinline__ uint32_t pks(float2 v, float s) { return packbf(v.x * s, v.y * s); }

template <int SEC, int PR>
__device__ __forceinline__ void norms(const float (&a1)[96], const float (&a2)[24], int t, float (&n)[2][2]) {
  const float h0 = sq2(grp<SEC, 5 * PR + 2, 0>(a1, a2)), h1 = sq2(grp<SEC, 5 * PR + 2, 1>(a1, a2));
  n[0][0] = sq2(grp<SEC, 5 * PR, 0>(a1, a2)) + sq2(grp<SEC, 5 * PR + 1, 0>(a1, a2)) + (t < 2 ? h0 : 0.f);
  n[0][1] = sq2(grp<SEC, 5 * PR, 1>(a1, a2)) + sq2(grp<SEC, 5 * PR + 1, 1>(a1, a2)) + (t < 2 ? h1 : 0.f);
  n[1][0] = sq2(grp<SEC, 5 * PR + 3, 0>(a1, a2)) + sq2(grp<SEC, 5 * PR + 4, 0>(a1, a2)) + (t < 2 ? 0.f : h0);
  n[1][1] = sq2(grp<SEC, 5 * PR + 3, 1>(a1, a2)) + sq2(grp<SEC, 5 * PR + 4, 1>(a1, a2)) + (t < 2 ? 0.f : h1);
#pragma unroll
  for (int i = 0; i < 4; i++) n[i >> 1][i & 1] += __shfl_xor_sync(~0u, n[i >> 1][i & 1], 1);
#pragma unroll
  for (int i = 0; i < 4; i++) n[i >> 1][i & 1] += __shfl_xor_sync(~0u, n[i >> 1][i & 1], 2);
}

template <int SEC, int PR>
__device__ __forceinline__ void stage_pair(const float (&a1)[96], const float (&a2)[24], float sc0, float sc1, float sm, uint32_t xe0, uint32_t xe1,
                                           uint32_t xo0, uint32_t xo1, uint32_t ad01, uint32_t ad2, int t) {
  const uint32_t off = 2 * PR * 3072;
  stsm4(ad01 + off, pks(grp<SEC, 5 * PR, 0>(a1, a2), sc0), pks(grp<SEC, 5 * PR, 1>(a1, a2), sc1), pks(grp<SEC, 5 * PR + 1, 0>(a1, a2), sc0),
        pks(grp<SEC, 5 * PR + 1, 1>(a1, a2), sc1));
  stsm4(ad01 + off + 3072, pks(grp<SEC, 5 * PR + 3, 0>(a1, a2), sc0), pks(grp<SEC, 5 * PR + 3, 1>(a1, a2), sc1),
        pks(grp<SEC, 5 * PR + 4, 0>(a1, a2), sc0), pks(grp<SEC, 5 * PR + 4, 1>(a1, a2), sc1));
  const uint32_t m0 = pks(grp<SEC, 5 * PR + 2, 0>(a1, a2), sc0 * sm), m1 = pks(grp<SEC, 5 * PR + 2, 1>(a1, a2), sc1 * sm);
  const bool lo = t < 2;
  stsm4(ad2 + off, lo ? m0 : xe0, lo ? m1 : xe1, lo ? xo0 : m0, lo ? xo1 : m1);
}

__device__ __forceinline__ void hedgehog(const float (&p)[12], uint32_t (&f)[10], int t) {
  const bool lo = t < 2;
#pragma unroll
  for (int hf = 0; hf < 2; hf++) {
    const float v[6] = {p[2 * hf], p[2 * hf + 1], p[4 + 2 * hf], p[5 + 2 * hf], p[8 + 2 * hf], p[9 + 2 * hf]};
    float mx = fmaxf(fmaxf(fmaxf(v[0], v[1]), fmaxf(v[2], v[3])), fmaxf(v[4], v[5]));
    float mn = fminf(fminf(fminf(v[0], v[1]), fminf(v[2], v[3])), fminf(v[4], v[5]));
    mx = fmaxf(mx, __shfl_xor_sync(~0u, mx, 1)); mn = fminf(mn, __shfl_xor_sync(~0u, mn, 1));
    mx = fmaxf(mx, __shfl_xor_sync(~0u, mx, 2)); mn = fminf(mn, __shfl_xor_sync(~0u, mn, 2));
    const float bp = -mx * LOG2E, bn = mn * LOG2E;
    float ep[4], en[4];
#pragma unroll
    for (int i = 0; i < 4; i++) { ep[i] = ex2(fmaf(v[i], LOG2E, bp)); en[i] = ex2(fmaf(v[i], -LOG2E, bn)); }
    const float sg = lo ? LOG2E : -LOG2E, bm = lo ? bp : bn;
    const float m0 = ex2(fmaf(v[4], sg, bm)), m1 = ex2(fmaf(v[5], sg, bm)), ms = m0 + m1;
    float sp = (ep[0] + ep[1]) + (ep[2] + ep[3]) + (lo ? ms : 0.f);
    float sn = (en[0] + en[1]) + (en[2] + en[3]) + (lo ? 0.f : ms);
    sp += __shfl_xor_sync(~0u, sp, 1); sn += __shfl_xor_sync(~0u, sn, 1);
    sp += __shfl_xor_sync(~0u, sp, 2); sn += __shfl_xor_sync(~0u, sn, 2);
    const float rp = rcp(sp), rn = rcp(sn), rm = lo ? rp : rn;
    f[0 + hf] = packbf(ep[0] * rp, ep[1] * rp);
    f[2 + hf] = packbf(ep[2] * rp, ep[3] * rp);
    f[4 + hf] = packbf(m0 * rm, m1 * rm);
    f[6 + hf] = packbf(en[0] * rn, en[1] * rn);
    f[8 + hf] = packbf(en[2] * rn, en[3] * rn);
  }
}

template <int O>
__device__ __forceinline__ void epilogue0(const float (&a1)[96], const float (&a2)[24], int rg, int lane, uint32_t ad01, uint32_t ad2, uint32_t kmx) {
  const int t = lane & 3;
  const bool p0 = (POLY_MASK >> rg) & 1, p1 = (POLY_MASK >> (rg + 1)) & 1;
  const uint32_t kp = (t & 1) ? 0u : (BF_ONE | (BF_MAGIC << 16)), km = (t & 1) ? BF_MU_LO : (BF_ONE | (BF_MU_HI << 16));
  const uint32_t vp = (t & 1) ? 0u : (BF_ONE | 0x8000u), vm = (t & 1) ? 0u : BF_ONE;
  const uint32_t k0 = p0 ? kp : km, k1 = p1 ? kp : km, v0 = p0 ? vp : vm, v1 = p1 ? vp : vm;
  const float s0 = p0 ? -1.f : 1.f, s1 = p1 ? -1.f : 1.f;
  stage_pair<O + 0, 0>(a1, a2, 1.f, 1.f, 1.f, k0, k1, k0, k1, ad01 + OFF_Q, ad2 + OFF_Q, t);
  stage_pair<O + 0, 1>(a1, a2, 1.f, 1.f, 1.f, k0, k1, k0, k1, ad01 + OFF_Q, ad2 + OFF_Q, t);
  stage_pair<O + 1, 0>(a1, a2, s0, s1, 1.f, v0, v1, v0, v1, ad01 + OFF_V, ad2 + OFF_V, t);
  stage_pair<O + 1, 1>(a1, a2, s0, s1, 1.f, v0, v1, v0, v1, ad01 + OFF_V, ad2 + OFF_V, t);
  stage_pair<O + 2, 0>(a1, a2, 1.f, 1.f, 0.5f, 0u, 0u, 0u, 0u, ad01 + OFF_AQ, ad2 + OFF_AQ, t);
  stage_pair<O + 2, 1>(a1, a2, 1.f, 1.f, 0.5f, 0u, 0u, 0u, 0u, ad01 + OFF_AQ, ad2 + OFF_AQ, t);
  float n0[2][2], n1[2][2];
  norms<O + 0, 0>(a1, a2, t, n0);
  norms<O + 0, 1>(a1, a2, t, n1);
  const uint32_t m0 = __reduce_max_sync(~0u, __float_as_uint(fmaxf(n0[0][0], n0[0][1])));
  const uint32_t m1 = __reduce_max_sync(~0u, __float_as_uint(fmaxf(n0[1][0], n0[1][1])));
  const uint32_t m2 = __reduce_max_sync(~0u, __float_as_uint(fmaxf(n1[0][0], n1[0][1])));
  const uint32_t m3 = __reduce_max_sync(~0u, __float_as_uint(fmaxf(n1[1][0], n1[1][1])));
  if (lane < 4) sts32(kmx + lane * 4, lane == 0 ? m0 : lane == 1 ? m1 : lane == 2 ? m2 : m3);
}

template <int O>
__device__ __forceinline__ bool epilogue1(const float (&a1)[96], const float (&a2)[24], const uint8_t* smem, int wg, int t, uint32_t ad01, uint32_t ad2) {
  stage_pair<O + 0, 0>(a1, a2, 1.f, 1.f, 0.5f, 0u, 0u, 0u, 0u, ad01 + OFF_AK, ad2 + OFF_AK, t);
  stage_pair<O + 0, 1>(a1, a2, 1.f, 1.f, 0.5f, 0u, 0u, 0u, 0u, ad01 + OFF_AK, ad2 + OFF_AK, t);
  float n0[2][2], n1[2][2];
  norms<O + 2, 0>(a1, a2, t, n0);
  norms<O + 2, 1>(a1, a2, t, n1);
  const float4 km = *(const float4*)(smem + OFF_MISC);
  const float b[4][2] = {{sqrt_ap(n0[0][0]) * km.x, sqrt_ap(n0[0][1]) * km.x}, {sqrt_ap(n0[1][0]) * km.y, sqrt_ap(n0[1][1]) * km.y},
                         {sqrt_ap(n1[0][0]) * km.z, sqrt_ap(n1[0][1]) * km.z}, {sqrt_ap(n1[1][0]) * km.w, sqrt_ap(n1[1][1]) * km.w}};
  bool unsafe = false;
#pragma unroll
  for (int i = 0; i < 8; i++) unsafe |= !(b[i >> 1][i & 1] <= FAST_BOUND);
  fence_async_smem();
  uint32_t any;
  asm volatile("{\n.reg .pred p, q;\nsetp.ne.u32 p, %1, 0;\nbar.red.or.pred q, %2, 128, p;\nselp.u32 %0, 1, 0, q;\n}\n"
               : "=r"(any) : "r"((uint32_t)unsafe), "r"(NB_WG + wg) : "memory");
  const bool slow = __any_sync(~0u, any);
  uint32_t xq[4][2];
#pragma unroll
  for (int i = 0; i < 8; i++) xq[i >> 1][i & 1] = slow ? 0u : ((t & 1) ? 0x3F00u : packbf(-0.5f * b[i >> 1][i & 1], 0.5f));
  stage_pair<O + 2, 0>(a1, a2, QSCALE, QSCALE, 0.5f, xq[0][0], xq[0][1], xq[1][0], xq[1][1], ad01 + OFF_Q, ad2 + OFF_Q, t);
  stage_pair<O + 2, 1>(a1, a2, QSCALE, QSCALE, 0.5f, xq[2][0], xq[2][1], xq[3][0], xq[3][1], ad01 + OFF_Q, ad2 + OFF_Q, t);
  const uint32_t one = (t & 1) ? 0u : BF_ONE;
  stage_pair<O + 1, 0>(a1, a2, 1.f, 1.f, 1.f, one, one, one, one, ad01 + OFF_V, ad2 + OFF_V, t);
  stage_pair<O + 1, 1>(a1, a2, 1.f, 1.f, 1.f, one, one, one, one, ad01 + OFF_V, ad2 + OFF_V, t);
  return slow;
}

constexpr uint64_t NO_LBO = ~(0x3FFFull << 16);
__device__ __forceinline__ void issue_proj(float (&p)[12], uint32_t img, uint32_t wph) {
  const uint64_t ad = mkdesc(img, 128, 384, 0), wd = mkdesc(wph, 384, 128, 0);
  wg_fence();
  mma_n24_ss_tb(p, ad, wd, 0);
  mma_n24_ss_tb(p, (ad + 16) & NO_LBO, (wd + 48) & NO_LBO, 1);
  wg_commit();
}
__device__ __forceinline__ void phi_k_stage(const float (&p)[12], uint32_t a, int t) {
  uint32_t f[10];
  hedgehog(p, f, t);
  stsm4(a, f[0], f[1], f[2], f[3]);
  stsm4(a + 256, f[4], f[5], f[6], f[7]);
  stsm2(a + 512, f[8], f[9]);
}

__device__ __forceinline__ uint32_t exp2_bits(float y0, float y1, uint32_t cm, uint32_t neg1) {
  uint32_t w, m, r;
  asm("prmt.b32 %0, %1, %2, 0x6521;" : "=r"(w) : "f"(y0), "f"(y1));
  asm("lop3.b32 %0, %1, 0x007F007F, %2, 0xEA;" : "=r"(m) : "r"(w), "r"(cm));
  const uint32_t e = m * neg1 + w;
  asm("fma.rn.bf16x2 %0, %1, %2, %3;" : "=r"(r) : "r"(w), "r"(m), "r"(e));
  return r;
}
__device__ __forceinline__ void exp_tile(const float (&s)[64], uint32_t (&p)[32], uint32_t cm, uint32_t neg1) {
#pragma unroll
  for (int g = 0; g < 16; g++) {
    if ((POLY_MASK >> g) & 1) {
      p[2 * g] = exp2_bits(s[4 * g], s[4 * g + 1], cm, neg1);
      p[2 * g + 1] = exp2_bits(s[4 * g + 2], s[4 * g + 3], cm, neg1);
    } else {
      p[2 * g] = packbf(ex2(s[4 * g]), ex2(s[4 * g + 1]));
      p[2 * g + 1] = packbf(ex2(s[4 * g + 2]), ex2(s[4 * g + 3]));
    }
  }
}
__device__ __forceinline__ void issue_qk(float (&s)[64], uint64_t q, uint64_t q2, uint64_t k, uint64_t k2) {
  mma_n128_ss(s, q, k, 0);
  mma_n128_ss(s, q2, k2, 1);
}
__device__ __forceinline__ void issue_pv(float (&o)[12], const uint32_t (&p)[32], uint64_t vd, int acc) {
#pragma unroll
  for (int kk = 0; kk < 8; kk++) mma_n24_rs_tb(o, p[4 * kk], p[4 * kk + 1], p[4 * kk + 2], p[4 * kk + 3], vd + kk * 48, acc | kk);
}
struct AttnDesc { uint64_t q, q2, k, k2, v; };
__device__ __forceinline__ void attn_pair(float (&s0)[64], float (&s1)[64], uint32_t (&p0)[32], uint32_t (&p1)[32], float (&o)[12], const AttnDesc& d,
                                          uint32_t qo, uint32_t co, uint32_t qn, uint32_t cn, int acc, uint32_t full_next, uint32_t ph_next,
                                          uint32_t empty_prev, uint32_t release, uint32_t cm, uint32_t neg1) {
  wg_fence();
  issue_qk(s1, d.q + qo, d.q2 + qo, d.k + co + 384, d.k2 + co + 384);
  wg_commit();
  const uint32_t ready = mbar_test(full_next, ph_next);
  exp_tile(s0, p0, cm, neg1);
  wg_fence();
  issue_pv(o, p0, d.v + co, acc);
  wg_commit();
  wg_wait<1>();
  pin(s1); pin(p1);
  mbar_arrive_if(empty_prev, release);
  if (!__all_sync(~0u, ready)) mbar_wait_u(full_next, ph_next);
  wg_fence();
  issue_qk(s0, d.q + qn, d.q2 + qn, d.k + cn, d.k2 + cn);
  wg_commit();
  exp_tile(s1, p1, cm, neg1);
  wg_fence();
  issue_pv(o, p1, d.v + co + 384, 1);
  wg_commit();
}
__device__ __forceinline__ int bgroup(int G) {
  const int hg = G / 10, j = G % 10;
  return (hg >> 2) * 40 + (j / 5) * 20 + (hg & 3) * 5 + j % 5;
}
__device__ __forceinline__ void stage_o(const float (&o)[12], int odd, uint32_t pair, int w4, int lane, float eps, float s0, float s1) {
  const int src = (lane & ~3) | (odd ? 0 : 2);
  const float l0 = __shfl_sync(~0u, o[8], src) + eps, l1 = __shfl_sync(~0u, o[10], src) + eps;
  const float r0 = s0 * rcp(l0), r1 = s1 * rcp(l1);
  const uint32_t base = pair + w4 * 256;
  stsm4(base + (odd ? 3072 : 0) + (lane >> 4) * 1024 + (lane & 15) * 16, packbf(o[0] * r0, o[1] * r0), packbf(o[2] * r1, o[3] * r1),
        packbf(o[4] * r0, o[5] * r0), packbf(o[6] * r1, o[7] * r1));
  if (((lane & 3) < 2) != (odd != 0)) {
    sts32(base + 2048 + lane * 4, packbf(o[8] * r0, o[9] * r0));
    sts32(base + 2048 + 128 + lane * 4, packbf(o[10] * r1, o[11] * r1));
  }
}
__device__ __forceinline__ void readout_head(float (&p)[12], float (&pnext)[12], uint32_t kvs, int odd, uint32_t pair, int w4, int lane, float g0, float g1) {
  uint32_t f[10];
  hedgehog(p, f, lane & 3);
  pin(f);
  const uint64_t kvd = mkdesc(kvs, 384, 128, 0);
  wg_fence();
  mma_n24_rs_tb(p, f[0], f[1], f[2], f[3], kvd, 0);
  mma_n24_rs_tb(p, f[4], f[5], f[6], f[7], kvd + 48, 1);
  mma_n24_rs_tb(p, f[8], f[9], 0u, 0u, (kvd + 96) & NO_LBO, 1);
  wg_commit();
  wg_wait<0>();
  pin(p); pin(pnext); pin(f);
  stage_o(p, odd, pair, w4, lane, 1e-6f, g0, g1);
}

struct Maps { CUtensorMap a64, a16, b64, b16, out; };

__device__ __forceinline__ void w_load(const Maps& m, int it, uint32_t d, uint32_t b, int hg) {
  const int kb = (it % 10) * 2, c = hg * 80 + (hg & 1) * 16, c2 = hg * 80 + ((hg & 1) ? 0 : 64);
  const bool w0 = it < 10;
  const CUtensorMap *p64 = w0 ? &m.b64 : &m.a64, *q64 = w0 ? &m.a64 : &m.b64, *p16 = w0 ? &m.b16 : &m.a16, *q16 = w0 ? &m.a16 : &m.b16;
  mbar_expect(b, W_STAGE);
  tma5(d, p64, 640 + c, kb, b);
  tma5(d + 8192, p64, 1280 + c, kb, b);
  tma5(d + 16384, q64, c, kb, b);
  tma5(d + 24576, p16, 640 + c2, kb, b);
  tma5(d + 26624, p16, 1280 + c2, kb, b);
  tma5(d + 28672, q16, c2, kb, b);
}
__device__ __forceinline__ void x_load(uint4 (&v)[4], const uint8_t* p, int it) {
  const uint8_t* q = p + (it % 10) * 128;
  v[0] = ldg_x(q); v[1] = ldg_x(q + 8 * 1280); v[2] = ldg_x(q + 64); v[3] = ldg_x(q + 8 * 1280 + 64);
}
__device__ __forceinline__ void gemm_step(float (&a1)[96], float (&a2)[24], uint4 (&xv)[4], uint32_t (&f)[4][4], uint32_t (&fp)[4][4],
                                          const uint8_t* xp, int it, int acc, uint32_t sb, uint32_t bars, uint32_t lead) {
  const int s = it % W_NST;
  const uint32_t z = mbar_wait_z(bars + B_WF + 8 * s, (it / W_NST) & 1);
  f[0][0] = xv[0].x ^ z; f[0][1] = xv[1].x ^ z; f[0][2] = xv[0].y ^ z; f[0][3] = xv[1].y ^ z;
  f[1][0] = xv[0].z ^ z; f[1][1] = xv[1].z ^ z; f[1][2] = xv[0].w ^ z; f[1][3] = xv[1].w ^ z;
  f[2][0] = xv[2].x ^ z; f[2][1] = xv[3].x ^ z; f[2][2] = xv[2].y ^ z; f[2][3] = xv[3].y ^ z;
  f[3][0] = xv[2].z ^ z; f[3][1] = xv[3].z ^ z; f[3][2] = xv[2].w ^ z; f[3][3] = xv[3].w ^ z;
#pragma unroll
  for (int i = 0; i < 4; i++) pin(f[i]);
  x_load(xv, xp, it + 2);
  const uint64_t b1 = mkdesc(sb + s * W_STAGE, 8192, 1024, 1), b2 = mkdesc(sb + s * W_STAGE + 24576, 2048, 256, 3);
  wg_fence();
#pragma unroll
  for (int kk = 0; kk < 4; kk++) {
    mma_n192_rs_tb(a1, f[kk][0], f[kk][1], f[kk][2], f[kk][3], b1 + kk * 128, acc | kk);
    mma_n48_rs_tb(a2, f[kk][0], f[kk][1], f[kk][2], f[kk][3], b2 + kk * 32, acc | kk);
  }
  wg_commit();
  wg_wait<1>();
#pragma unroll
  for (int i = 0; i < 4; i++) pin(fp[i]);
  mbar_arrive_if(bars + B_WE + 8 * ((it + W_NST - 1) % W_NST), lead && acc);
}

__global__ void __cluster_dims__(2, 1, 1) __launch_bounds__(384, 1)
fused_block(const __grid_constant__ Maps maps, const __nv_bfloat16* __restrict__ x, const __nv_bfloat16* __restrict__ wphi,
            const __nv_bfloat16* __restrict__ gate_w, const uint8_t* __restrict__ woa, const uint8_t* __restrict__ wob, uint32_t cm, uint32_t neg1) {
  extern __shared__ __align__(1024) uint8_t smem[];
  const uint32_t sb = smem_u32(smem), bars = sb + OFF_BAR;
  const int warp = __shfl_sync(~0u, threadIdx.x >> 5, 0), lane = threadIdx.x & 31, wg = warp >> 2;
  const int bid = blockIdx.x;
  const int mt = (bid & 1) + 2 * (bid >> 4), hg = (bid >> 1) & 7;
  const int half = bid & 1, nt = (bid >> 1) & 3, mt3 = bid >> 3;
  PROF(threadIdx.x == 0, 0);
  const uint8_t* xp = (const uint8_t*)x + (size_t)(mt * 128 + (warp & 7) * 16 + (lane >> 2)) * 1280 + (lane & 3) * 16;
  uint4 xa[4], xb[4];
  if (wg < 2) { x_load(xa, xp, 0); x_load(xb, xp, 1); }
  if (warp == 8) {
    if (lane == 0) {
#pragma unroll
      for (int i = 0; i < W_NST; i++) { mbar_init(bars + B_WF + 8 * i, 1); mbar_init(bars + B_WE + 8 * i, 2); }
      fence_async_smem();
    }
    __syncwarp();
    bar_arrive(0, 288);
    if (lane == 0) { w_load(maps, 0, sb, bars + B_WF, hg); w_load(maps, 1, sb + W_STAGE, bars + B_WF + 8, hg); }
    __syncwarp();
  }

  if (wg == 2) {
    reg_dec<40>();
    if (warp == 8) {
      if (lane == 0) {
        for (int it = 2; it < 20; it++) {
          const int s = it % W_NST;
          if (it >= W_NST) mbar_wait(bars + B_WE + 8 * s, ((it / W_NST) - 1) & 1);
          PROF(it == 5, 1);
          w_load(maps, it, sb + s * W_STAGE, bars + B_WF + 8 * s, hg);
        }
      }
      __syncwarp();
      bar_sync(NB_HELP, 128);
      const uint32_t epoch = *(volatile uint32_t*)(smem + OFF_MISC + 16);
      if (lane == 0) {
        cnt_wait(C_KV + hg, 16 * epoch);
        for (int c = 0; c < 32; c++) {
          const int s = c & 3;
          const uint8_t* src = g_KV + (size_t)(hg * 4 + (c >> 3)) * IMG_HEAD + (c & 7) * 12288;
          mbar_wait(bars + B_KE + 8 * s, (c >> 2) & 1);
          mbar_expect(bars + B_KF + 8 * s, KV_CHUNK);
          bulk_g2s(sb + s * KV_CHUNK, src, 12288, bars + B_KF + 8 * s);
          bulk_g2s(sb + s * KV_CHUNK + 12288, src + (size_t)NH * IMG_HEAD, 12288, bars + B_KF + 8 * s);
        }
        cnt_wait(C_WO, NCTA * epoch);
        cnt_wait(C_OA + mt3, 8 * epoch);
        mbar_wait(bars + B_RF, 0);
        for (int it = 0; it < 10; it++) {
          const int s = it % 5, ks = (it < 5 ? 0 : 5) + half * 5 + it;
          if (it >= 5) mbar_wait(bars + B_OE + 8 * s, 0);
          else if (it >= 2) mbar_wait(bars + B_KE + 8 * (it - 1), 0);
          if (it == 7) { PROF(true, 28); cnt_wait(C_OB + mt3, 8 * epoch); PROF(true, 29); }
          const uint32_t d = sb + o_stage(s), b = bars + B_OF + 8 * s;
          const uint8_t* ga = g_OAB + (size_t)mt3 * 327680 + ks * 8192;
          mbar_expect(b, O_STAGE);
          bulk_g2s(d + 16384, g_WOI + (size_t)nt * 409600 + ks * 20480, 20480, b);
          bulk_g2s(d, ga, 8192, b);
          bulk_g2s(d + 8192, ga + 163840, 8192, b);
        }
      }
    } else if (warp == 9) {
      uint32_t epoch = 0;
      if (lane == 0) {
#pragma unroll
        for (int i = 0; i < 4; i++) { mbar_init(bars + B_KF + 8 * i, 1); mbar_init(bars + B_KE + 8 * i, 2); }
#pragma unroll
        for (int i = 0; i < 5; i++) { mbar_init(bars + B_OF + 8 * i, 1); mbar_init(bars + B_OE + 8 * i, 2); }
        mbar_init(bars + B_RF, 1);
        fence_async_smem();
        epoch = atomicAdd(g_CNT + C_START * 8, 1u) / NCTA + 1;
        *(volatile uint32_t*)(smem + OFF_MISC + 16) = epoch;
      }
      epoch = __shfl_sync(~0u, epoch, 0);
      bar_arrive(NB_HELP, 128);
#pragma unroll 1
      for (int e = lane; e < 96; e += 32) {
        const int i = e / 24, slot = e % 24;
        int d = -1;
        if (i & 1) { if (slot < 16) d = slot + 4; else if (slot >= 20) d = slot - 20; }
        else if (slot < 20) d = slot;
        uint2 v[5] = {};
        if (d >= 0) {
#pragma unroll
          for (int u = 0; u < 5; u++) v[u] = __ldg((const uint2*)(wphi + ((hg * 4 + i) * 20 + d) * 20) + u);
        }
        uint8_t* dst = smem + OFF_WPH + i * 1152 + (slot >> 3) * 384 + (slot & 7) * 16;
        *(uint4*)dst = make_uint4(v[0].x, v[0].y, v[1].x, v[1].y);
        *(uint4*)(dst + 128) = make_uint4(v[2].x, v[2].y, v[3].x, v[3].y);
        *(uint4*)(dst + 256) = make_uint4(v[4].x, v[4].y, v[4].x, v[4].y);
      }
      fence_async_smem();
      bar_sync(NB_STAGED, 288);
      {
        uint32_t m = *(volatile uint32_t*)(smem + OFF_MISC + 32 + lane * 4);
        m = max(m, __shfl_xor_sync(~0u, m, 4)); m = max(m, __shfl_xor_sync(~0u, m, 8)); m = max(m, __shfl_xor_sync(~0u, m, 16));
        if (lane < 4) *(volatile uint32_t*)(smem + OFF_MISC + lane * 4) = m;
        fence_async_smem();
        __syncwarp();
      }
      if (lane == 0) {
        bulk_s2g(g_KMAX + hg * 16 + mt, sb + OFF_MISC, 16);
#pragma unroll 1
        for (int i = 0; i < 16; i++) {
          bulk_s2g(g_KV + (size_t)((i >> 3) * NH + hg * 4 + (i & 3)) * IMG_HEAD + (mt * 2 + ((i >> 2) & 1)) * 3072, sb + OFF_Q + i * 3072, 3072);
          __nanosleep(150);
        }
        bulk_commit_wait();
        PROF(true, 22);
        cnt_add_done(C_KV + hg);
        cnt_wait(C_KV + hg, 16 * epoch);
      }
      __syncwarp();
      {
        uint4 v = ldg_cg4(g_KMAX + hg * 16 + (lane & 15));
        v.x = __reduce_max_sync(~0u, v.x); v.y = __reduce_max_sync(~0u, v.y); v.z = __reduce_max_sync(~0u, v.z); v.w = __reduce_max_sync(~0u, v.w);
        if (lane < 4) *(volatile float*)(smem + OFF_MISC + lane * 4) =
            sqrt_ap(__uint_as_float(lane == 0 ? v.x : lane == 1 ? v.y : lane == 2 ? v.z : v.w)) * (QSCALE * 1.02f);
      }
      PROF(lane == 0, 24);
      bar_arrive(NB_FREE, 288);
      bar_sync(NB_TAIL, 288);
      if (lane == 0) {
#pragma unroll 1
        for (int i = 0; i < 4; i++) bulk_s2g(g_KVP + (size_t)((hg * 4 + i) * 16 + mt) * 480, sb + OFF_PHK + i * 10240, 3840);
        bulk_commit_wait();
        cnt_add_done(C_KVP + hg);
        cnt_wait(C_GATE + mt, 8 * epoch);
      }
      __syncwarp();
      {
        const uint4 g0 = ldg_cg4(g_GATE + mt * 128 + lane * 2), g1 = ldg_cg4(g_GATE + mt * 128 + 64 + lane * 2);
        *(uint4*)(smem + OFF_GATE + lane * 16) = g0;
        *(uint4*)(smem + OFF_GATE + 512 + lane * 16) = g1;
      }
      bar_arrive(NB_GATE, 160);
      bar_arrive(NB_GATE + 1, 160);
      PROF(lane == 0, 21);
      if (lane == 0) cnt_wait(C_KVB + hg, 16 * epoch);
      __syncwarp();
#pragma unroll 1
      for (int e0 = 0; e0 < 480; e0 += 160) {
        uint4 v[5];
#pragma unroll
        for (int u = 0; u < 5; u++) v[u] = ldg_cg4(g_KVB + hg * 4 * 480 + (e0 + u * 32 + lane) * 4);
#pragma unroll
        for (int u = 0; u < 5; u++) *(uint4*)(smem + OFF_V + (e0 + u * 32 + lane) * 16) = v[u];
      }
      fence_async_smem();
      PROF(lane == 0, 25);
      bar_arrive(NB_KVB, 160);
      bar_arrive(NB_KVB + 1, 160);
      uint8_t* og = g_OAB + (size_t)mt * 327680;
#pragma unroll 1
      for (int w = 0; w < 2; w++) {
        bar_sync(NB_READ + w, 160);
        if (lane == 0) {
          bulk_s2g(og + w * 163840 + hg * 10240, sb + OFF_AQ + w * 12288, 10240);
          bulk_s2g(og + w * 163840 + (80 + bgroup(hg * 10)) * 1024, sb + OFF_Q + w * 12288, 5120);
        }
        __syncwarp();
      }
      if (lane == 0) { bulk_commit_wait(); mbar_arrive(bars + B_RF); cnt_add_done(C_OA + mt); }
      __syncwarp();
      bar_sync(NB_LAST, 288);
      if (lane == 0) {
        bulk_s2g(og + (80 + bgroup(hg * 10 + 5)) * 1024, sb + OFF_Q + 6144, 5120);
        bulk_s2g(og + 163840 + (80 + bgroup(hg * 10 + 5)) * 1024, sb + OFF_Q + 12288 + 6144, 5120);
        bulk_commit_wait();
        cnt_add_done(C_OB + mt);
        PROF(true, 27);
      }
    } else {
      const int ht = threadIdx.x - 320;
      bar_sync(NB_HELP, 128);
      const uint32_t epoch = *(volatile uint32_t*)(smem + OFF_MISC + 16);
      {
        const int row = mt * 128 + hg * 16 + (ht >> 2), q = ht & 3;
        float acc = 0.f;
#pragma unroll 1
        for (int i0 = 0; i0 < 20; i0 += 5) {
          uint4 xv[5];
#pragma unroll
          for (int i = 0; i < 5; i++) xv[i] = __ldg((const uint4*)(x + (size_t)row * DM + (i0 + i) * 32 + q * 8));
#pragma unroll
          for (int i = 0; i < 5; i++) {
            const uint4 gw = __ldg((const uint4*)(gate_w + (i0 + i) * 32 + q * 8));
            const uint32_t xr[4] = {xv[i].x, xv[i].y, xv[i].z, xv[i].w}, gr[4] = {gw.x, gw.y, gw.z, gw.w};
#pragma unroll
            for (int u = 0; u < 4; u++) {
              uint32_t p;
              asm("mul.rn.bf16x2 %0, %1, %2;" : "=r"(p) : "r"(xr[u]), "r"(gr[u]));
              acc += bf_lo(p) + bf_hi(p);
            }
          }
        }
        acc += __shfl_xor_sync(~0u, acc, 1);
        acc += __shfl_xor_sync(~0u, acc, 2);
        if (q == 0) {
          const float g = bf_round(__fdividef(1.f, 1.f + __expf(-bf_round(acc))));
          g_GATE[row] = make_float2(g, bf_round(1.f - g));
        }
      }
      bar_sync(NB_HELP, 64);
      if (ht == 0) { cnt_add(C_GATE + mt); PROF(true, 18); cnt_wait(C_KVP + hg, 16 * epoch); }
      bar_sync(NB_HELP, 64);
      if (ht < 60) {
        const int hd = hg * 4 + ht / 15, e = mt * 30 + (ht % 15) * 2;
        const float2* src = g_KVP + (size_t)hd * 16 * 480 + e;
        float4 s = make_float4(0.f, 0.f, 0.f, 0.f);
#pragma unroll 1
        for (int m0 = 0; m0 < 16; m0 += 4) {
          uint4 v[4];
#pragma unroll
          for (int m = 0; m < 4; m++) v[m] = ldg_cg4(src + (m0 + m) * 480);
#pragma unroll
          for (int m = 0; m < 4; m++) {
            s.x += __uint_as_float(v[m].x); s.y += __uint_as_float(v[m].y); s.z += __uint_as_float(v[m].z); s.w += __uint_as_float(v[m].w);
          }
        }
        *(uint2*)(g_KVB + hd * 480 + e) = make_uint2(packbf(s.x, s.y), packbf(s.z, s.w));
      }
      bar_sync(NB_HELP, 64);
      if (ht == 0) cnt_add(C_KVB + hg);
      PROF(ht == 0, 20);
#pragma unroll 1
      for (int kg = bid; kg < 160; kg += NCTA) {
        const uint8_t* src = (kg < 80 ? woa + (size_t)kg * 10240 : wob + (size_t)(kg - 80) * 10240) + (ht & 7) * 1280 + (ht >> 3) * 16;
        uint8_t* dst = g_WOI + (kg < 80 ? kg : 80 + bgroup(kg - 80)) * 2560 + (ht & 7) * 16;
#pragma unroll 1
        for (int c0 = 0; c0 < 80; c0 += 40) {
          uint4 v[5];
#pragma unroll
          for (int u = 0; u < 5; u++) v[u] = __ldg((const uint4*)(src + (c0 + u * 8) * 16));
#pragma unroll
          for (int u = 0; u < 5; u++) {
            const int c = c0 + u * 8 + (ht >> 3);
            *(uint4*)(dst + (size_t)(c / 20) * 409600 + (c % 20) * 128) = v[u];
          }
        }
      }
      bar_sync(NB_HELP, 64);
      if (ht == 0) cnt_add(C_WO);
      PROF(ht == 0, 19);
    }
  } else {
    reg_inc<232>();
    bar_sync(0, 288);
    const int w4 = warp & 3, t = lane & 3;
    const uint32_t lead = (threadIdx.x & 127) == 0;
    bool slow;
    {
      const int mi = lane >> 3;
      const uint32_t sbase = sb + wg * 12288 + (w4 * 2 + (mi & 1)) * 384 + (lane & 7) * 16;
      const uint32_t ad01 = sbase + (mi >> 1) * 128, ad2 = sbase + (mi >> 1) * 3072 + 256;
      float a1[96], a2[24];
      uint32_t fa[4][4] = {}, fb[4][4] = {};
#pragma unroll 1
      for (int tile = 0; tile < 2; tile++) {
#pragma unroll 1
        for (int ks = 0; ks < 10; ks += 2) {
          gemm_step(a1, a2, xa, fa, fb, xp, tile * 10 + ks, ks, sb, bars, lead);
          gemm_step(a1, a2, xb, fb, fa, xp, tile * 10 + ks + 1, 1, sb, bars, lead);
        }
        wg_wait<0>();
        pin(a1); pin(a2);
#pragma unroll
        for (int i = 0; i < 4; i++) pin(fb[i]);
        mbar_arrive_if(bars + B_WE + 8 * 4, lead);
        PROF(threadIdx.x == 0, 2 + 2 * tile);
        if (tile == 0) {
          if (hg & 1) epilogue0<4>(a1, a2, warp * 2, lane, ad01, ad2, sb + OFF_MISC + 32 + warp * 16);
          else epilogue0<0>(a1, a2, warp * 2, lane, ad01, ad2, sb + OFF_MISC + 32 + warp * 16);
          fence_async_smem();
          bar_arrive(NB_STAGED, 288);
          PROF(threadIdx.x == 0, 3);
        }
      }
      bar_sync(NB_FREE, 288);
#pragma unroll
      for (int s = 0; s < 3; s++) mbar_arrive_if(bars + B_KE + 8 * s, lead);
      mbar_wait_u(bars + B_WE + 8 * 4, 1);
      if (hg & 1) slow = epilogue1<4>(a1, a2, smem, wg, t, ad01, ad2);
      else slow = epilogue1<0>(a1, a2, smem, wg, t, ad01, ad2);
      PROF(threadIdx.x == 0, 15);
      const uint32_t ak = sb + OFF_AK + wg * 12288, wph = sb + OFF_WPH;
      const uint32_t pka = sb + OFF_PHK + (warp * 2 + (mi & 1)) * 640 + (mi >> 1) * 128 + (lane & 7) * 16;
      float pa[12], pb[12];
      issue_proj(pa, ak, wph);
      wg_wait<0>();
      pin(pa);
#pragma unroll 1
      for (int i = 0; i < 4; i += 2) {
        issue_proj(pb, ak + (i + 1) * 3072, wph + (i + 1) * 1152);
        phi_k_stage(pa, pka + i * 10240, t);
        wg_wait<0>();
        pin(pb);
        issue_proj(pa, ak + ((i + 2) & 3) * 3072, wph + ((i + 2) & 3) * 1152);
        phi_k_stage(pb, pka + (i + 1) * 10240, t);
        wg_wait<0>();
        pin(pa);
      }
      mbar_arrive_if(bars + B_KE + 8 * 3, lead);
      fence_async_smem();
      PROF(threadIdx.x == 0, 16);
      bar_sync(NB_PHIK, 256);
      wg_fence();
#pragma unroll
      for (int j = 0; j < 2; j++) {
        const uint64_t ad = mkdesc(sb + OFF_PHK + (wg * 2 + j) * 10240, 640, 128, 0), vd = mkdesc(sb + OFF_V + (wg * 2 + j) * 3072, 384, 128, 0);
#pragma unroll
        for (int ks = 0; ks < 8; ks++) mma_n24_ss_tatb(j ? pb : pa, ad + ks * 80, vd + (ks >> 2) * 768 + (ks & 3) * 48, ks);
      }
      wg_commit();
      wg_wait<0>();
      pin(pa); pin(pb);
      bar_sync(NB_WG + wg, 128);
      {
        float2* dst = (float2*)(smem + OFF_PHK + wg * 20480) + w4 * 192 + lane;
        if (w4 < 3) {
          dst[0] = make_float2(pa[0], pa[1]); dst[32] = make_float2(pa[4], pa[5]); dst[64] = make_float2(pa[8], pa[9]);
          dst[1280] = make_float2(pb[0], pb[1]); dst[1312] = make_float2(pb[4], pb[5]); dst[1344] = make_float2(pb[8], pb[9]);
        }
        if (w4 < 2) {
          dst[96] = make_float2(pa[2], pa[3]); dst[128] = make_float2(pa[6], pa[7]); dst[160] = make_float2(pa[10], pa[11]);
          dst[1376] = make_float2(pb[2], pb[3]); dst[1408] = make_float2(pb[6], pb[7]); dst[1440] = make_float2(pb[10], pb[11]);
        }
      }
      fence_async_smem();
      bar_arrive(NB_TAIL, 288);
      PROF(threadIdx.x == 0, 5);
    }
    {
      const uint32_t gate = sb + OFF_GATE + (warp * 16 + (lane >> 2)) * 8, qs = sb + OFF_Q + wg * 12288;
      AttnDesc d;
      d.q = mkdesc(qs, 128, 384, 0); d.q2 = mkdesc(qs + 256, 0, 384, 0);
      d.k = mkdesc(sb, 128, 384, 0); d.k2 = mkdesc(sb + 256, 0, 384, 0);
      d.v = mkdesc(sb + 12288, 384, 128, 0);
      float o[12], s0[64];
      mbar_wait_u(bars + B_KF, 0);
      wg_fence();
      issue_qk(s0, d.q, d.q2, d.k, d.k2);
      wg_commit();
      wg_wait<0>();
      pin(s0);
#pragma unroll 1
      for (int pass = 0; pass < 4; pass++) {
        const uint32_t qo = pass * 192;
        if (!slow) {
          float s1[64];
          uint32_t p0[32], p1[32] = {};
#pragma unroll 1
          for (int j = 0; j < 7; j++) {
            const int nx = (j + 1) & 3;
            attn_pair(s0, s1, p0, p1, o, d, qo, (j & 3) * 1536, qo, nx * 1536, j, bars + B_KF + 8 * nx, (j + 1) >> 2, bars + B_KE + 8 * ((j - 1) & 3),
                      lead && j, cm, neg1);
            wg_wait<1>();
            pin(s0); pin(p0);
          }
          const int last = pass == 3;
          attn_pair(s0, s1, p0, p1, o, d, qo, 3 * 1536, last ? qo : qo + 192, last ? 3 * 1536 : 0, 1, bars + B_KF + (last ? 24 : 0), last,
                    bars + B_KE + 16, lead, cm, neg1);
          wg_wait<0>();
          pin(s0); pin(o); pin(p0); pin(p1);
          mbar_arrive_if(bars + B_KE + 24, lead);
        } else {
          uint32_t p[32];
          float m0 = -INFINITY, m1 = -INFINITY;
#pragma unroll
          for (int i = 0; i < 12; i++) o[i] = 0.f;
#pragma unroll 1
          for (int j = 0; j < 16; j++) {
            const int slot = (j >> 1) & 3;
            const uint32_t co = slot * 1536 + (j & 1) * 384;
            mbar_wait_u(bars + B_KF + 8 * slot, j >> 3);
            wg_fence();
            issue_qk(s0, d.q + qo, d.q2 + qo, d.k + co, d.k2 + co);
            wg_commit();
            wg_wait<0>();
            pin(s0);
            float n0 = m0, n1 = m1;
#pragma unroll
            for (int g = 0; g < 16; g++) { n0 = fmaxf(n0, fmaxf(s0[4 * g], s0[4 * g + 1])); n1 = fmaxf(n1, fmaxf(s0[4 * g + 2], s0[4 * g + 3])); }
            n0 = fmaxf(n0, __shfl_xor_sync(~0u, n0, 1)); n1 = fmaxf(n1, __shfl_xor_sync(~0u, n1, 1));
            n0 = fmaxf(n0, __shfl_xor_sync(~0u, n0, 2)); n1 = fmaxf(n1, __shfl_xor_sync(~0u, n1, 2));
            const float c0 = ex2(m0 - n0), c1 = ex2(m1 - n1);
            m0 = n0; m1 = n1;
#pragma unroll
            for (int i = 0; i < 3; i++) { o[4 * i] *= c0; o[4 * i + 1] *= c0; o[4 * i + 2] *= c1; o[4 * i + 3] *= c1; }
#pragma unroll
            for (int g = 0; g < 16; g++) {
              const uint32_t sg = ((POLY_MASK >> g) & 1) ? 0x80008000u : 0u;
              p[2 * g] = packbf(ex2(s0[4 * g] - m0), ex2(s0[4 * g + 1] - m0)) ^ sg;
              p[2 * g + 1] = packbf(ex2(s0[4 * g + 2] - m1), ex2(s0[4 * g + 3] - m1)) ^ sg;
            }
            wg_fence();
            issue_pv(o, p, d.v + co, 1);
            wg_commit();
            wg_wait<0>();
            pin(o); pin(p);
            mbar_arrive_if(bars + B_KE + 8 * slot, lead && (j & 1));
          }
          bar_sync(NB_WG + wg, 128);
        }
        if (pass == 0) bar_sync(NB_GATE + wg, 160);
        stage_o(o, pass & 1, qs + (pass >> 1) * 6144, w4, lane, 0.f, lds_f2(gate).y, lds_f2(gate + 64).y);
        PROF(threadIdx.x == 0, 6 + pass);
        if (pass == 1 + wg) {
          const uint32_t aq = sb + OFF_AQ + wg * 12288, wph = sb + OFF_WPH;
          float pa[12], pb[12];
          issue_proj(pa, aq, wph);
          const float g0 = lds_f2(gate).x, g1 = lds_f2(gate + 64).x;
          bar_sync(NB_KVB + wg, 160);
          wg_wait<0>();
          pin(pa);
#pragma unroll 1
          for (int i = 0; i < 4; i += 2) {
            issue_proj(pb, aq + (i + 1) * 3072, wph + (i + 1) * 1152);
            readout_head(pa, pb, sb + OFF_V + i * 1920, 0, aq + i * 2560, w4, lane, g0, g1);
            issue_proj(pa, aq + (i ? 3 : 2) * 3072, wph + 2 * 1152);
            readout_head(pb, pa, sb + OFF_V + (i + 1) * 1920, 1, aq + i * 2560, w4, lane, g0, g1);
          }
          fence_async_smem();
          bar_arrive(NB_READ + wg, 160);
          PROF(threadIdx.x == 0, 17);
        }
      }
      fence_async_smem();
      bar_arrive(NB_LAST, 288);
    }
    {
      asm volatile("barrier.cluster.arrive.relaxed.aligned;" ::: "memory");
      float acc[80];
#pragma unroll 1
      for (int it = 0; it < 10; it++) {
        const int s = it % 5;
        mbar_wait_u(bars + B_OF + 8 * s, it / 5);
        PROF(threadIdx.x == 0 && (it == 0 || it == 7), 10 + it / 7);
        const uint32_t st = sb + o_stage(s);
        const uint64_t ad = mkdesc(st + wg * 8192, 1024, 128, 0), bd = mkdesc(st + 16384, 2560, 128, 0);
        wg_fence();
#pragma unroll
        for (int kk = 0; kk < 4; kk++) mma_n160_ss_tb(acc, ad + kk * 128, bd + kk * 320, it | kk);
        wg_commit();
        wg_wait<1>();
        mbar_arrive_if(bars + B_OE + 8 * ((it + 4) % 5), lead && it);
      }
      wg_wait<0>();
      pin(acc);
      PROF(threadIdx.x == 0, 12);
      asm volatile("barrier.cluster.wait.aligned;" ::: "memory");
      uint32_t remote;
      asm volatile("mapa.shared::cluster.u32 %0, %1, %2;" : "=r"(remote) : "r"(sb + OFF_Q + threadIdx.x * 16), "r"(half ^ 1));
#pragma unroll
      for (int j = 0; j < 5; j++) {
        uint32_t v[4];
#pragma unroll
        for (int u = 0; u < 4; u++) v[u] = half ? packbf(acc[8 * j + 2 * u], acc[8 * j + 2 * u + 1]) : packbf(acc[40 + 8 * j + 2 * u], acc[41 + 8 * j + 2 * u]);
        asm volatile("st.shared::cluster.v4.b32 [%0], {%1,%2,%3,%4};" ::"r"(remote + j * 4096), "r"(v[0]), "r"(v[1]), "r"(v[2]), "r"(v[3]) : "memory");
      }
      asm volatile("barrier.cluster.arrive.release.aligned;" ::: "memory");
      asm volatile("barrier.cluster.wait.acquire.aligned;" ::: "memory");
      PROF(threadIdx.x == 0, 13);
      const uint32_t ob = sb + wg * 10240;
      const uint32_t oa = ob + (w4 * 16 + (lane & 15)) * 160 + (lane >> 4) * 16;
      uint32_t pk[20];
#pragma unroll
      for (int j = 0; j < 5; j++) {
        const uint4 r = *(const uint4*)(smem + OFF_Q + j * 4096 + threadIdx.x * 16);
        const uint32_t rv[4] = {r.x, r.y, r.z, r.w};
#pragma unroll
        for (int u = 0; u < 4; u++) {
          const float v0 = half ? acc[40 + 8 * j + 2 * u] : acc[8 * j + 2 * u], v1 = half ? acc[41 + 8 * j + 2 * u] : acc[8 * j + 2 * u + 1];
          pk[4 * j + u] = packbf(v0 + bf_lo(rv[u]), v1 + bf_hi(rv[u]));
        }
      }
#pragma unroll
      for (int j = 0; j < 10; j += 2) stsm4(oa + j * 16, pk[2 * j], pk[2 * j + 1], pk[2 * j + 2], pk[2 * j + 3]);
      fence_async_smem();
      bar_sync(NB_WG + wg, 128);
      if (lead) {
        asm volatile("cp.async.bulk.tensor.2d.global.shared::cta.bulk_group [%0, {%2,%3}], [%1];" ::"l"(&maps.out), "r"(ob), "r"(nt * 160 + half * 80),
                     "r"(mt3 * 128 + wg * 64) : "memory");
        asm volatile("cp.async.bulk.commit_group;" ::: "memory");
        asm volatile("cp.async.bulk.wait_group.read 0;" ::: "memory");
      }
      PROF(threadIdx.x == 0, 14);
    }
  }
}

typedef CUresult (*EncodeFn)(CUtensorMap*, CUtensorMapDataType, cuuint32_t, void*, const cuuint64_t*, const cuuint64_t*, const cuuint32_t*,
                             const cuuint32_t*, CUtensorMapInterleave, CUtensorMapSwizzle, CUtensorMapL2promotion, CUtensorMapFloatOOBfill);

void encode(EncodeFn fn, CUtensorMap* m, const void* p, int rank, const cuuint64_t* dims, const cuuint64_t* strides, const cuuint32_t* box,
            CUtensorMapSwizzle sw) {
  const cuuint32_t es[5] = {1, 1, 1, 1, 1};
  fn(m, CU_TENSOR_MAP_DATA_TYPE_BFLOAT16, rank, const_cast<void*>(p), dims, strides, box, es, CU_TENSOR_MAP_INTERLEAVE_NONE, sw,
     CU_TENSOR_MAP_L2_PROMOTION_L2_128B, CU_TENSOR_MAP_FLOAT_OOB_FILL_NONE);
}

}

extern "C" void kernel_launch(void* const* d_in, const int* in_sizes, int n_in, void* d_out, int out_size) {
  (void)in_sizes; (void)n_in; (void)out_size;
  static EncodeFn enc = nullptr;
  if (!enc) {
    void* fn = nullptr;
    cudaDriverEntryPointQueryResult qr;
    cudaGetDriverEntryPoint("cuTensorMapEncodeTiled", &fn, cudaEnableDefault, &qr);
    enc = (EncodeFn)fn;
    cudaFuncSetAttribute(fused_block, cudaFuncAttributeMaxDynamicSharedMemorySize, SMEM_BYTES);
  }
  Maps maps;
  {
    const cuuint64_t dx[2] = {640, 2048}, sx[1] = {1280};
    const cuuint32_t bo[2] = {80, 64};
    encode(enc, &maps.out, d_out, 2, dx, sx, bo, CU_TENSOR_MAP_SWIZZLE_NONE);
    const cuuint64_t dw[5] = {1920, 2, 4, 4, 20}, sw[4] = {3840, 8 * 3840, 2 * 3840, 32 * 3840};
    const cuuint32_t b64[5] = {64, 2, 4, 4, 2}, b16[5] = {16, 2, 4, 4, 2};
    encode(enc, &maps.a64, d_in[1], 5, dw, sw, b64, CU_TENSOR_MAP_SWIZZLE_128B);
    encode(enc, &maps.a16, d_in[1], 5, dw, sw, b16, CU_TENSOR_MAP_SWIZZLE_32B);
    encode(enc, &maps.b64, d_in[5], 5, dw, sw, b64, CU_TENSOR_MAP_SWIZZLE_128B);
    encode(enc, &maps.b16, d_in[5], 5, dw, sw, b16, CU_TENSOR_MAP_SWIZZLE_32B);
  }
  fused_block<<<NCTA, 384, SMEM_BYTES, cudaStreamPerThread>>>(maps, (const __nv_bfloat16*)d_in[0], (const __nv_bfloat16*)d_in[2],
                                                               (const __nv_bfloat16*)d_in[7],
                                                               (const uint8_t*)d_in[3], (const uint8_t*)d_in[6], 0x1F801F80u, 0xFFFFFFFFu);
}
```

```cpp
#include <cuda_runtime.h>
#include <cuda_bf16.h>
#include <cuda.h>
#include <stdint.h>

#define STNS 150
#define POLLNS 40
namespace {

constexpr int SEQ = 2048, DM = 640, NH = 32, NCTA = 128;
constexpr int IMG_HEAD = SEQ * 48;
#define POLY_MASK 0x7777u
constexpr float LOG2E = 1.4426950408889634f;
constexpr float QSCALE = 0.22360679774997896f * 1.4426950408889634f;
constexpr uint32_t BF_ONE = 0x3F80u;
constexpr uint32_t BF_MAGIC = 0x43E0u;
constexpr uint32_t BF_MU_HI = 0x4025u;
constexpr uint32_t BF_MU_LO = 0x3B8Bu;
constexpr float FAST_BOUND = 40.0f;

__device__ __align__(1024) uint8_t g_KV[2 * NH * IMG_HEAD];
__device__ __align__(1024) float2 g_KVP[NH * 16 * 480];
__device__ __align__(1024) uint32_t g_KVB[NH * 480];
__device__ __align__(1024) float4 g_KMAX[8 * 16];
__device__ __align__(1024) float2 g_GATE[SEQ];
__device__ __align__(1024) uint8_t g_OAB[16 * 2 * 160 * 1024];
__device__ __align__(1024) uint8_t g_WOI[4 * 409600];
__device__ __align__(1024) uint32_t g_CNT[80 * 8];
constexpr int C_START = 0, C_WO = 1, C_KV = 2, C_KVP = 10, C_KVB = 18, C_GATE = 26, C_OA = 42, C_OB = 58;

#define SPIN_LIMIT (1ll << 29)
#define SPIN_FAIL(code) __trap()
#define PROF(cond, slot)
__device__ __forceinline__ uint32_t smem_u32(const void* p) { return (uint32_t)__cvta_generic_to_shared(p); }
__device__ __forceinline__ void mbar_init(uint32_t a, uint32_t c) { asm volatile("mbarrier.init.shared::cta.b64 [%0], %1;" ::"r"(a), "r"(c) : "memory"); }
__device__ __forceinline__ void mbar_expect(uint32_t a, uint32_t b) { asm volatile("mbarrier.arrive.expect_tx.shared::cta.b64 _, [%0], %1;" ::"r"(a), "r"(b) : "memory"); }
__device__ __forceinline__ void mbar_arrive(uint32_t a) { asm volatile("mbarrier.arrive.shared::cta.b64 _, [%0];" ::"r"(a) : "memory"); }
__device__ __forceinline__ uint32_t mbar_try(uint32_t a, uint32_t ph) {
  uint32_t ok;
  asm volatile("{\n.reg .pred p;\nmbarrier.try_wait.parity.shared::cta.b64 p, [%1], %2;\nselp.u32 %0, 1, 0, p;\n}\n" : "=r"(ok) : "r"(a), "r"(ph) : "memory");
  return ok;
}
__device__ __forceinline__ void mbar_wait(uint32_t a, uint32_t ph) {
  if (mbar_try(a, ph)) return;
  const long long t0 = clock64();
  while (!mbar_try(a, ph))
    if (clock64() - t0 > SPIN_LIMIT) { SPIN_FAIL(1000 + (a & 0x1FF) * 2 + ph); break; }
}
__device__ __forceinline__ void mbar_wait_u(uint32_t a, uint32_t ph) {
#pragma unroll 1
  for (int n = 0; n < (1 << 18); n++)
    if (__all_sync(~0u, mbar_try(a, ph))) break;
}
__device__ __forceinline__ uint32_t mbar_wait_z(uint32_t a, uint32_t ph) {
  uint32_t ok = 0;
#pragma unroll 1
  for (int n = 0; n < (1 << 18); n++) {
    ok = mbar_try(a, ph);
    if (__all_sync(~0u, ok)) break;
  }
  return ok - 1;
}
__device__ __forceinline__ uint32_t mbar_test(uint32_t a, uint32_t ph) {
  uint32_t ok;
  asm volatile("{\n.reg .pred p;\nmbarrier.test_wait.parity.shared::cta.b64 p, [%1], %2;\nselp.u32 %0, 1, 0, p;\n}\n" : "=r"(ok) : "r"(a), "r"(ph) : "memory");
  return ok;
}
__device__ __forceinline__ void mbar_arrive_if(uint32_t a, uint32_t flag) {
  asm volatile("{\n.reg .pred p;\nsetp.ne.u32 p, %1, 0;\n@p mbarrier.arrive.shared::cta.b64 _, [%0];\n}\n" ::"r"(a), "r"(flag) : "memory");
}
__device__ __forceinline__ void cnt_add_done(int slot) { asm volatile("red.relaxed.gpu.global.add.u32 [%0], 1;" ::"l"(g_CNT + slot * 8) : "memory"); }
__device__ __forceinline__ void cnt_add(int slot) {
  asm volatile("fence.acq_rel.gpu;" ::: "memory");
  cnt_add_done(slot);
}
__device__ __forceinline__ void cnt_wait(int slot, uint32_t target) {
  uint32_t v;
  long long t0 = 0;
  for (;;) {
    asm volatile("ld.relaxed.gpu.global.u32 %0, [%1];" : "=r"(v) : "l"(g_CNT + slot * 8) : "memory");
    if ((int32_t)(v - target) >= 0) break;
    __nanosleep(POLLNS);
    if (!t0) t0 = clock64();
    else if (clock64() - t0 > SPIN_LIMIT) { SPIN_FAIL(slot); break; }
  }
  asm volatile("ld.acquire.gpu.global.u32 %0, [%1];" : "=r"(v) : "l"(g_CNT + slot * 8) : "memory");
}
__device__ __forceinline__ void bulk_commit_wait() { asm volatile("cp.async.bulk.commit_group;\ncp.async.bulk.wait_group 0;" ::: "memory"); }
__device__ __forceinline__ void tma5(uint32_t dst, const CUtensorMap* m, int c0, int c4, uint32_t bar) {
  asm volatile("cp.async.bulk.tensor.5d.shared::cluster.global.mbarrier::complete_tx::bytes [%0], [%1, {%3,%5,%5,%5,%4}], [%2];" ::"r"(dst), "l"(m), "r"(bar), "r"(c0), "r"(c4), "r"(0) : "memory");
}
__device__ __forceinline__ void bulk_g2s(uint32_t dst, const void* src, uint32_t bytes, uint32_t bar) {
  asm volatile("cp.async.bulk.shared::cluster.global.mbarrier::complete_tx::bytes [%0], [%1], %2, [%3];" ::"r"(dst), "l"(src), "r"(bytes), "r"(bar) : "memory");
}
__device__ __forceinline__ void fence_async_smem() { asm volatile("fence.proxy.async.shared::cta;" ::: "memory"); }
__device__ __forceinline__ void bar_sync(int id, int n) { asm volatile("bar.sync %0, %1;" ::"r"(id), "r"(n) : "memory"); }
__device__ __forceinline__ void bar_arrive(int id, int n) { asm volatile("bar.arrive %0, %1;" ::"r"(id), "r"(n) : "memory"); }
__device__ __forceinline__ void wg_fence() { asm volatile("wgmma.fence.sync.aligned;" ::: "memory"); }
__device__ __forceinline__ void wg_commit() { asm volatile("wgmma.commit_group.sync.aligned;" ::: "memory"); }
template <int N> __device__ __forceinline__ void wg_wait() { asm volatile("wgmma.wait_group.sync.aligned %0;" ::"n"(N) : "memory"); }
template <int N> __device__ __forceinline__ void reg_inc() { asm volatile("setmaxnreg.inc.sync.aligned.u32 %0;" ::"n"(N)); }
template <int N> __device__ __forceinline__ void reg_dec() { asm volatile("setmaxnreg.dec.sync.aligned.u32 %0;" ::"n"(N)); }
template <int N> __device__ __forceinline__ void pin(float (&r)[N]) {
#pragma unroll
  for (int i = 0; i < N; i++) asm volatile("" : "+f"(r[i])::"memory");
}
template <int N> __device__ __forceinline__ void pin(uint32_t (&r)[N]) {
#pragma unroll
  for (int i = 0; i < N; i++) asm volatile("" : "+r"(r[i])::"memory");
}
__device__ __forceinline__ uint64_t mkdesc(uint32_t addr, uint32_t lbo, uint32_t sbo, uint32_t swz) {
  return (uint64_t)((addr & 0x3FFFF) >> 4) | ((uint64_t)(lbo >> 4) << 16) | ((uint64_t)(sbo >> 4) << 32) | ((uint64_t)swz << 62);
}
__device__ __forceinline__ float ex2(float x) { float y; asm("ex2.approx.ftz.f32 %0, %1;" : "=f"(y) : "f"(x)); return y; }
__device__ __forceinline__ float rcp(float x) { float y; asm("rcp.approx.ftz.f32 %0, %1;" : "=f"(y) : "f"(x)); return y; }
__device__ __forceinline__ float sqrt_ap(float x) { float y; asm("sqrt.approx.f32 %0, %1;" : "=f"(y) : "f"(x)); return y; }
__device__ __forceinline__ uint32_t packbf(float lo, float hi) { uint32_t d; asm("cvt.rn.bf16x2.f32 %0, %1, %2;" : "=r"(d) : "f"(hi), "f"(lo)); return d; }
__device__ __forceinline__ float bf_lo(uint32_t v) { return __uint_as_float(v << 16); }
__device__ __forceinline__ float bf_hi(uint32_t v) { return __uint_as_float(v & 0xFFFF0000u); }
__device__ __forceinline__ float bf_round(float x) { return bf_lo(packbf(x, 0.f)); }
__device__ __forceinline__ uint4 ldg_cg4(const void* p) { uint4 v; asm volatile("ld.global.cg.v4.b32 {%0,%1,%2,%3}, [%4];" : "=r"(v.x), "=r"(v.y), "=r"(v.z), "=r"(v.w) : "l"(p) : "memory"); return v; }
__device__ __forceinline__ void sts32(uint32_t a, uint32_t v) { asm volatile("st.shared.b32 [%0], %1;" ::"r"(a), "r"(v) : "memory"); }
__device__ __forceinline__ void stsm4(uint32_t a, uint32_t r0, uint32_t r1, uint32_t r2, uint32_t r3) {
  asm volatile("stmatrix.sync.aligned.m8n8.x4.shared.b16 [%0], {%1,%2,%3,%4};" ::"r"(a), "r"(r0), "r"(r1), "r"(r2), "r"(r3) : "memory");
}

__device__ __forceinline__ void stsm2(uint32_t a, uint32_t r0, uint32_t r1) {
  asm volatile("stmatrix.sync.aligned.m8n8.x2.shared.b16 [%0], {%1,%2};" ::"r"(a), "r"(r0), "r"(r1) : "memory");
}
__device__ __forceinline__ uint4 ldg_x(const void* p) {
  uint4 v;
  asm volatile("ld.global.nc.L1::no_allocate.L2::128B.v4.b32 {%0,%1,%2,%3}, [%4];" : "=r"(v.x), "=r"(v.y), "=r"(v.z), "=r"(v.w) : "l"(p));
  return v;
}
__device__ __forceinline__ float2 lds_f2(uint32_t a) { float2 v; asm volatile("ld.shared.v2.f32 {%0,%1}, [%2];" : "=f"(v.x), "=f"(v.y) : "r"(a) : "memory"); return v; }
__device__ __forceinline__ void bulk_s2g(void* dst, uint32_t src, uint32_t bytes) {
  asm volatile("cp.async.bulk.global.shared::cta.bulk_group [%0], [%1], %2;" ::"l"(dst), "r"(src), "r"(bytes) : "memory");
}

__device__ __forceinline__ void mma_n24_ss_tb(float (&d)[12], uint64_t adesc, uint64_t bdesc, int acc) {
  asm volatile("{\n.reg .pred p;\nsetp.ne.b32 p, %14, 0;\n"
      "wgmma.mma_async.sync.aligned.m64n24k16.f32.bf16.bf16 "
      "{%0,%1,%2,%3,%4,%5,%6,%7,%8,%9,%10,%11}, "
      "%12, %13, p, 1, 1, 0, 1;\n}\n"
      : "+f"(d[0]), "+f"(d[1]), "+f"(d[2]), "+f"(d[3]), "+f"(d[4]), "+f"(d[5]), "+f"(d[6]), "+f"(d[7]),
        "+f"(d[8]), "+f"(d[9]), "+f"(d[10]), "+f"(d[11])
      : "l"(adesc), "l"(bdesc), "r"(acc));
}
__device__ __forceinline__ void mma_n192_rs_tb(float (&d)[96], uint32_t a0, uint32_t a1, uint32_t a2, uint32_t a3, uint64_t bdesc, int acc) {
  asm volatile("{\n.reg .pred p;\nsetp.ne.b32 p, %101, 0;\n"
      "wgmma.mma_async.sync.aligned.m64n192k16.f32.bf16.bf16 "
      "{%0,%1,%2,%3,%4,%5,%6,%7,%8,%9,%10,%11,%12,%13,%14,%15,"
      "%16,%17,%18,%19,%20,%21,%22,%23,%24,%25,%26,%27,%28,%29,%30,%31,"
      "%32,%33,%34,%35,%36,%37,%38,%39,%40,%41,%42,%43,%44,%45,%46,%47,"
      "%48,%49,%50,%51,%52,%53,%54,%55,%56,%57,%58,%59,%60,%61,%62,%63,"
      "%64,%65,%66,%67,%68,%69,%70,%71,%72,%73,%74,%75,%76,%77,%78,%79,"
      "%80,%81,%82,%83,%84,%85,%86,%87,%88,%89,%90,%91,%92,%93,%94,%95}, "
      "{%96,%97,%98,%99}, %100, p, 1, 1, 1;\n}\n"
      : "+f"(d[0]), "+f"(d[1]), "+f"(d[2]), "+f"(d[3]), "+f"(d[4]), "+f"(d[5]), "+f"(d[6]), "+f"(d[7]),
        "+f"(d[8]), "+f"(d[9]), "+f"(d[10]), "+f"(d[11]), "+f"(d[12]), "+f"(d[13]), "+f"(d[14]), "+f"(d[15]),
        "+f"(d[16]), "+f"(d[17]), "+f"(d[18]), "+f"(d[19]), "+f"(d[20]), "+f"(d[21]), "+f"(d[22]), "+f"(d[23]),
        "+f"(d[24]), "+f"(d[25]), "+f"(d[26]), "+f"(d[27]), "+f"(d[28]), "+f"(d[29]), "+f"(d[30]), "+f"(d[31]),
        "+f"(d[32]), "+f"(d[33]), "+f"(d[34]), "+f"(d[35]), "+f"(d[36]), "+f"(d[37]), "+f"(d[38]), "+f"(d[39]),
        "+f"(d[40]), "+f"(d[41]), "+f"(d[42]), "+f"(d[43]), "+f"(d[44]), "+f"(d[45]), "+f"(d[46]), "+f"(d[47]),
        "+f"(d[48]), "+f"(d[49]), "+f"(d[50]), "+f"(d[51]), "+f"(d[52]), "+f"(d[53]), "+f"(d[54]), "+f"(d[55]),
        "+f"(d[56]), "+f"(d[57]), "+f"(d[58]), "+f"(d[59]), "+f"(d[60]), "+f"(d[61]), "+f"(d[62]), "+f"(d[63]),
        "+f"(d[64]), "+f"(d[65]), "+f"(d[66]), "+f"(d[67]), "+f"(d[68]), "+f"(d[69]), "+f"(d[70]), "+f"(d[71]),
        "+f"(d[72]), "+f"(d[73]), "+f"(d[74]), "+f"(d[75]), "+f"(d[76]), "+f"(d[77]), "+f"(d[78]), "+f"(d[79]),
        "+f"(d[80]), "+f"(d[81]), "+f"(d[82]), "+f"(d[83]), "+f"(d[84]), "+f"(d[85]), "+f"(d[86]), "+f"(d[87]),
        "+f"(d[88]), "+f"(d[89]), "+f"(d[90]), "+f"(d[91]), "+f"(d[92]), "+f"(d[93]), "+f"(d[94]), "+f"(d[95])
      : "r"(a0), "r"(a1), "r"(a2), "r"(a3), "l"(bdesc), "r"(acc));
}
__device__ __forceinline__ void mma_n48_rs_tb(float (&d)[24], uint32_t a0, uint32_t a1, uint32_t a2, uint32_t a3, uint64_t bdesc, int acc) {
  asm volatile("{\n.reg .pred p;\nsetp.ne.b32 p, %29, 0;\n"
      "wgmma.mma_async.sync.aligned.m64n48k16.f32.bf16.bf16 "
      "{%0,%1,%2,%3,%4,%5,%6,%7,%8,%9,%10,%11,%12,%13,%14,%15,"
      "%16,%17,%18,%19,%20,%21,%22,%23}, "
      "{%24,%25,%26,%27}, %28, p, 1, 1, 1;\n}\n"
      : "+f"(d[0]), "+f"(d[1]), "+f"(d[2]), "+f"(d[3]), "+f"(d[4]), "+f"(d[5]), "+f"(d[6]), "+f"(d[7]),
        "+f"(d[8]), "+f"(d[9]), "+f"(d[10]), "+f"(d[11]), "+f"(d[12]), "+f"(d[13]), "+f"(d[14]), "+f"(d[15]),
        "+f"(d[16]), "+f"(d[17]), "+f"(d[18]), "+f"(d[19]), "+f"(d[20]), "+f"(d[21]), "+f"(d[22]), "+f"(d[23])
      : "r"(a0), "r"(a1), "r"(a2), "r"(a3), "l"(bdesc), "r"(acc));
}
__device__ __forceinline__ void mma_n128_rs(float (&d)[64], uint32_t a0, uint32_t a1, uint32_t a2, uint32_t a3, uint64_t bdesc, int acc) {
  asm volatile("{\n.reg .pred p;\nsetp.ne.b32 p, %69, 0;\n"
      "wgmma.mma_async.sync.aligned.m64n128k16.f32.bf16.bf16 "
      "{%0,%1,%2,%3,%4,%5,%6,%7,%8,%9,%10,%11,%12,%13,%14,%15,"
      "%16,%17,%18,%19,%20,%21,%22,%23,%24,%25,%26,%27,%28,%29,%30,%31,"
      "%32,%33,%34,%35,%36,%37,%38,%39,%40,%41,%42,%43,%44,%45,%46,%47,"
      "%48,%49,%50,%51,%52,%53,%54,%55,%56,%57,%58,%59,%60,%61,%62,%63}, "
      "{%64,%65,%66,%67}, %68, p, 1, 1, 0;\n}\n"
      : "+f"(d[0]), "+f"(d[1]), "+f"(d[2]), "+f"(d[3]), "+f"(d[4]), "+f"(d[5]), "+f"(d[6]), "+f"(d[7]),
        "+f"(d[8]), "+f"(d[9]), "+f"(d[10]), "+f"(d[11]), "+f"(d[12]), "+f"(d[13]), "+f"(d[14]), "+f"(d[15]),
        "+f"(d[16]), "+f"(d[17]), "+f"(d[18]), "+f"(d[19]), "+f"(d[20]), "+f"(d[21]), "+f"(d[22]), "+f"(d[23]),
        "+f"(d[24]), "+f"(d[25]), "+f"(d[26]), "+f"(d[27]), "+f"(d[28]), "+f"(d[29]), "+f"(d[30]), "+f"(d[31]),
        "+f"(d[32]), "+f"(d[33]), "+f"(d[34]), "+f"(d[35]), "+f"(d[36]), "+f"(d[37]), "+f"(d[38]), "+f"(d[39]),
        "+f"(d[40]), "+f"(d[41]), "+f"(d[42]), "+f"(d[43]), "+f"(d[44]), "+f"(d[45]), "+f"(d[46]), "+f"(d[47]),
        "+f"(d[48]), "+f"(d[49]), "+f"(d[50]), "+f"(d[51]), "+f"(d[52]), "+f"(d[53]), "+f"(d[54]), "+f"(d[55]),
        "+f"(d[56]), "+f"(d[57]), "+f"(d[58]), "+f"(d[59]), "+f"(d[60]), "+f"(d[61]), "+f"(d[62]), "+f"(d[63])
      : "r"(a0), "r"(a1), "r"(a2), "r"(a3), "l"(bdesc), "r"(acc));
}
__device__ __forceinline__ void mma_n160_ss_tb(float (&d)[80], uint64_t adesc, uint64_t bdesc, int acc) {
  asm volatile("{\n.reg .pred p;\nsetp.ne.b32 p, %82, 0;\n"
      "wgmma.mma_async.sync.aligned.m64n160k16.f32.bf16.bf16 "
      "{%0,%1,%2,%3,%4,%5,%6,%7,%8,%9,%10,%11,%12,%13,%14,%15,"
      "%16,%17,%18,%19,%20,%21,%22,%23,%24,%25,%26,%27,%28,%29,%30,%31,"
      "%32,%33,%34,%35,%36,%37,%38,%39,%40,%41,%42,%43,%44,%45,%46,%47,"
      "%48,%49,%50,%51,%52,%53,%54,%55,%56,%57,%58,%59,%60,%61,%62,%63,"
      "%64,%65,%66,%67,%68,%69,%70,%71,%72,%73,%74,%75,%76,%77,%78,%79}, "
      "%80, %81, p, 1, 1, 0, 1;\n}\n"
      : "+f"(d[0]), "+f"(d[1]), "+f"(d[2]), "+f"(d[3]), "+f"(d[4]), "+f"(d[5]), "+f"(d[6]), "+f"(d[7]),
        "+f"(d[8]), "+f"(d[9]), "+f"(d[10]), "+f"(d[11]), "+f"(d[12]), "+f"(d[13]), "+f"(d[14]), "+f"(d[15]),
        "+f"(d[16]), "+f"(d[17]), "+f"(d[18]), "+f"(d[19]), "+f"(d[20]), "+f"(d[21]), "+f"(d[22]), "+f"(d[23]),
        "+f"(d[24]), "+f"(d[25]), "+f"(d[26]), "+f"(d[27]), "+f"(d[28]), "+f"(d[29]), "+f"(d[30]), "+f"(d[31]),
        "+f"(d[32]), "+f"(d[33]), "+f"(d[34]), "+f"(d[35]), "+f"(d[36]), "+f"(d[37]), "+f"(d[38]), "+f"(d[39]),
        "+f"(d[40]), "+f"(d[41]), "+f"(d[42]), "+f"(d[43]), "+f"(d[44]), "+f"(d[45]), "+f"(d[46]), "+f"(d[47]),
        "+f"(d[48]), "+f"(d[49]), "+f"(d[50]), "+f"(d[51]), "+f"(d[52]), "+f"(d[53]), "+f"(d[54]), "+f"(d[55]),
        "+f"(d[56]), "+f"(d[57]), "+f"(d[58]), "+f"(d[59]), "+f"(d[60]), "+f"(d[61]), "+f"(d[62]), "+f"(d[63]),
        "+f"(d[64]), "+f"(d[65]), "+f"(d[66]), "+f"(d[67]), "+f"(d[68]), "+f"(d[69]), "+f"(d[70]), "+f"(d[71]),
        "+f"(d[72]), "+f"(d[73]), "+f"(d[74]), "+f"(d[75]), "+f"(d[76]), "+f"(d[77]), "+f"(d[78]), "+f"(d[79])
      : "l"(adesc), "l"(bdesc), "r"(acc));
}
__device__ __forceinline__ void mma_n24_rs_tb(float (&d)[12], uint32_t a0, uint32_t a1, uint32_t a2, uint32_t a3, uint64_t bdesc, int acc) {
  asm volatile("{\n.reg .pred p;\nsetp.ne.b32 p, %17, 0;\n"
      "wgmma.mma_async.sync.aligned.m64n24k16.f32.bf16.bf16 "
      "{%0,%1,%2,%3,%4,%5,%6,%7,%8,%9,%10,%11}, "
      "{%12,%13,%14,%15}, %16, p, 1, 1, 1;\n}\n"
      : "+f"(d[0]), "+f"(d[1]), "+f"(d[2]), "+f"(d[3]), "+f"(d[4]), "+f"(d[5]), "+f"(d[6]), "+f"(d[7]),
        "+f"(d[8]), "+f"(d[9]), "+f"(d[10]), "+f"(d[11])
      : "r"(a0), "r"(a1), "r"(a2), "r"(a3), "l"(bdesc), "r"(acc));
}
__device__ __forceinline__ void mma_n24_ss_tatb(float (&d)[12], uint64_t adesc, uint64_t bdesc, int acc) {
  asm volatile("{\n.reg .pred p;\nsetp.ne.b32 p, %14, 0;\n"
      "wgmma.mma_async.sync.aligned.m64n24k16.f32.bf16.bf16 "
      "{%0,%1,%2,%3,%4,%5,%6,%7,%8,%9,%10,%11}, "
      "%12, %13, p, 1, 1, 1, 1;\n}\n"
      : "+f"(d[0]), "+f"(d[1]), "+f"(d[2]), "+f"(d[3]), "+f"(d[4]), "+f"(d[5]), "+f"(d[6]), "+f"(d[7]),
        "+f"(d[8]), "+f"(d[9]), "+f"(d[10]), "+f"(d[11])
      : "l"(adesc), "l"(bdesc), "r"(acc));
}

constexpr int W_STAGE = 30720, W_NST = 5;
constexpr int KV_CHUNK = 24576;
constexpr int O_STAGE = 36864;
constexpr int OFF_AK = 3 * KV_CHUNK;
constexpr int OFF_PHK = 4 * KV_CHUNK;
constexpr int OFF_GATE = 112640;
constexpr int OFF_Q = W_NST * W_STAGE;
constexpr int OFF_V = OFF_Q + 24576;
constexpr int OFF_AQ = OFF_V + 24576;
constexpr int OFF_WPH = OFF_AQ + 24576;
constexpr int OFF_BAR = OFF_WPH + 4608;
constexpr int B_WF = 0, B_WE = 40, B_KF = 80, B_KE = 112, B_OF = 144, B_OE = 184, B_RF = 224;
constexpr int OFF_MISC = OFF_BAR + 240;
constexpr int SMEM_BYTES = OFF_MISC + 32 + 128;
__device__ __forceinline__ uint32_t o_stage(int s) { return s == 0 ? OFF_V : s == 1 ? OFF_Q - O_STAGE : (s - 2) * O_STAGE; }
constexpr int NB_STAGED = 1, NB_FREE = 2, NB_WG = 3, NB_PHIK = 5, NB_TAIL = 6, NB_GATE = 7, NB_KVB = 9, NB_READ = 11, NB_HELP = 13, NB_LAST = 14;

template <int SEC, int J, int HF>
__device__ __forceinline__ float2 grp(const float (&a1)[96], const float (&a2)[24]) {
  constexpr int S = SEC & 3, J1 = (SEC & 4) ? J - 2 : J, J2 = (SEC & 4) ? J : J - 8;
  if constexpr (J1 >= 0 && J1 < 8) return make_float2(a1[(8 * S + J1) * 4 + 2 * HF], a1[(8 * S + J1) * 4 + 2 * HF + 1]);
  else return make_float2(a2[(2 * S + J2) * 4 + 2 * HF], a2[(2 * S + J2) * 4 + 2 * HF + 1]);
}
__device__ __forceinline__ float sq2(float2 v) { return fmaf(v.x, v.x, v.y * v.y); }
__device__ __forceinline__ uint32_t pks(float2 v, float s) { return packbf(v.x * s, v.y * s); }

template <int SEC, int PR>
__device__ __forceinline__ void norms(const float (&a1)[96], const float (&a2)[24], int t, float (&n)[2][2]) {
  const float h0 = sq2(grp<SEC, 5 * PR + 2, 0>(a1, a2)), h1 = sq2(grp<SEC, 5 * PR + 2, 1>(a1, a2));
  n[0][0] = sq2(grp<SEC, 5 * PR, 0>(a1, a2)) + sq2(grp<SEC, 5 * PR + 1, 0>(a1, a2)) + (t < 2 ? h0 : 0.f);
  n[0][1] = sq2(grp<SEC, 5 * PR, 1>(a1, a2)) + sq2(grp<SEC, 5 * PR + 1, 1>(a1, a2)) + (t < 2 ? h1 : 0.f);
  n[1][0] = sq2(grp<SEC, 5 * PR + 3, 0>(a1, a2)) + sq2(grp<SEC, 5 * PR + 4, 0>(a1, a2)) + (t < 2 ? 0.f : h0);
  n[1][1] = sq2(grp<SEC, 5 * PR + 3, 1>(a1, a2)) + sq2(grp<SEC, 5 * PR + 4, 1>(a1, a2)) + (t < 2 ? 0.f : h1);
#pragma unroll
  for (int i = 0; i < 4; i++) n[i >> 1][i & 1] += __shfl_xor_sync(~0u, n[i >> 1][i & 1], 1);
#pragma unroll
  for (int i = 0; i < 4; i++) n[i >> 1][i & 1] += __shfl_xor_sync(~0u, n[i >> 1][i & 1], 2);
}

template <int SEC, int PR>
__device__ __forceinline__ void stage_pair(const float (&a1)[96], const float (&a2)[24], float sc0, float sc1, float sm, uint32_t xe0, uint32_t xe1,
                                           uint32_t xo0, uint32_t xo1, uint32_t ad01, uint32_t ad2, int t) {
  const uint32_t off = 2 * PR * 3072;
  stsm4(ad01 + off, pks(grp<SEC, 5 * PR, 0>(a1, a2), sc0), pks(grp<SEC, 5 * PR, 1>(a1, a2), sc1), pks(grp<SEC, 5 * PR + 1, 0>(a1, a2), sc0),
        pks(grp<SEC, 5 * PR + 1, 1>(a1, a2), sc1));
  stsm4(ad01 + off + 3072, pks(grp<SEC, 5 * PR + 3, 0>(a1, a2), sc0), pks(grp<SEC, 5 * PR + 3, 1>(a1, a2), sc1),
        pks(grp<SEC, 5 * PR + 4, 0>(a1, a2), sc0), pks(grp<SEC, 5 * PR + 4, 1>(a1, a2), sc1));
  const uint32_t m0 = pks(grp<SEC, 5 * PR + 2, 0>(a1, a2), sc0 * sm), m1 = pks(grp<SEC, 5 * PR + 2, 1>(a1, a2), sc1 * sm);
  const bool lo = t < 2;
  stsm4(ad2 + off, lo ? m0 : xe0, lo ? m1 : xe1, lo ? xo0 : m0, lo ? xo1 : m1);
}

__device__ __forceinline__ void hedgehog(const float (&p)[12], uint32_t (&f)[10], int t) {
  const bool lo = t < 2;
#pragma unroll
  for (int hf = 0; hf < 2; hf++) {
    const float v[6] = {p[2 * hf], p[2 * hf + 1], p[4 + 2 * hf], p[5 + 2 * hf], p[8 + 2 * hf], p[9 + 2 * hf]};
    float mx = fmaxf(fmaxf(fmaxf(v[0], v[1]), fmaxf(v[2], v[3])), fmaxf(v[4], v[5]));
    float mn = fminf(fminf(fminf(v[0], v[1]), fminf(v[2], v[3])), fminf(v[4], v[5]));
    mx = fmaxf(mx, __shfl_xor_sync(~0u, mx, 1)); mn = fminf(mn, __shfl_xor_sync(~0u, mn, 1));
    mx = fmaxf(mx, __shfl_xor_sync(~0u, mx, 2)); mn = fminf(mn, __shfl_xor_sync(~0u, mn, 2));
    const float bp = -mx * LOG2E, bn = mn * LOG2E;
    float ep[4], en[4];
#pragma unroll
    for (int i = 0; i < 4; i++) { ep[i] = ex2(fmaf(v[i], LOG2E, bp)); en[i] = ex2(fmaf(v[i], -LOG2E, bn)); }
    const float sg = lo ? LOG2E : -LOG2E, bm = lo ? bp : bn;
    const float m0 = ex2(fmaf(v[4], sg, bm)), m1 = ex2(fmaf(v[5], sg, bm)), ms = m0 + m1;
    float sp = (ep[0] + ep[1]) + (ep[2] + ep[3]) + (lo ? ms : 0.f);
    float sn = (en[0] + en[1]) + (en[2] + en[3]) + (lo ? 0.f : ms);
    sp += __shfl_xor_sync(~0u, sp, 1); sn += __shfl_xor_sync(~0u, sn, 1);
    sp += __shfl_xor_sync(~0u, sp, 2); sn += __shfl_xor_sync(~0u, sn, 2);
    const float rp = rcp(sp), rn = rcp(sn), rm = lo ? rp : rn;
    f[0 + hf] = packbf(ep[0] * rp, ep[1] * rp);
    f[2 + hf] = packbf(ep[2] * rp, ep[3] * rp);
    f[4 + hf] = packbf(m0 * rm, m1 * rm);
    f[6 + hf] = packbf(en[0] * rn, en[1] * rn);
    f[8 + hf] = packbf(en[2] * rn, en[3] * rn);
  }
}

template <int O>
__device__ __forceinline__ void epilogue0(const float (&a1)[96], const float (&a2)[24], int rg, int lane, uint32_t ad01, uint32_t ad2, uint32_t kmx) {
  const int t = lane & 3;
  const bool p0 = (POLY_MASK >> rg) & 1, p1 = (POLY_MASK >> (rg + 1)) & 1;
  const uint32_t kp = (t & 1) ? 0u : (BF_ONE | (BF_MAGIC << 16)), km = (t & 1) ? BF_MU_LO : (BF_ONE | (BF_MU_HI << 16));
  const uint32_t vp = (t & 1) ? 0u : (BF_ONE | 0x8000u), vm = (t & 1) ? 0u : BF_ONE;
  const uint32_t k0 = p0 ? kp : km, k1 = p1 ? kp : km, v0 = p0 ? vp : vm, v1 = p1 ? vp : vm;
  const float s0 = p0 ? -1.f : 1.f, s1 = p1 ? -1.f : 1.f;
  stage_pair<O + 0, 0>(a1, a2, 1.f, 1.f, 1.f, k0, k1, k0, k1, ad01 + OFF_Q, ad2 + OFF_Q, t);
  stage_pair<O + 0, 1>(a1, a2, 1.f, 1.f, 1.f, k0, k1, k0, k1, ad01 + OFF_Q, ad2 + OFF_Q, t);
  stage_pair<O + 1, 0>(a1, a2, s0, s1, 1.f, v0, v1, v0, v1, ad01 + OFF_V, ad2 + OFF_V, t);
  stage_pair<O + 1, 1>(a1, a2, s0, s1, 1.f, v0, v1, v0, v1, ad01 + OFF_V, ad2 + OFF_V, t);
  stage_pair<O + 2, 0>(a1, a2, 1.f, 1.f, 0.5f, 0u, 0u, 0u, 0u, ad01 + OFF_AQ, ad2 + OFF_AQ, t);
  stage_pair<O + 2, 1>(a1, a2, 1.f, 1.f, 0.5f, 0u, 0u, 0u, 0u, ad01 + OFF_AQ, ad2 + OFF_AQ, t);
  float n0[2][2], n1[2][2];
  norms<O + 0, 0>(a1, a2, t, n0);
  norms<O + 0, 1>(a1, a2, t, n1);
  const uint32_t m0 = __reduce_max_sync(~0u, __float_as_uint(fmaxf(n0[0][0], n0[0][1])));
  const uint32_t m1 = __reduce_max_sync(~0u, __float_as_uint(fmaxf(n0[1][0], n0[1][1])));
  const uint32_t m2 = __reduce_max_sync(~0u, __float_as_uint(fmaxf(n1[0][0], n1[0][1])));
  const uint32_t m3 = __reduce_max_sync(~0u, __float_as_uint(fmaxf(n1[1][0], n1[1][1])));
  if (lane < 4) sts32(kmx + lane * 4, lane == 0 ? m0 : lane == 1 ? m1 : lane == 2 ? m2 : m3);
}

template <int O>
__device__ __forceinline__ bool epilogue1(const float (&a1)[96], const float (&a2)[24], const uint8_t* smem, int wg, int t, uint32_t ad01, uint32_t ad2) {
  stage_pair<O + 0, 0>(a1, a2, 1.f, 1.f, 0.5f, 0u, 0u, 0u, 0u, ad01 + OFF_AK, ad2 + OFF_AK, t);
  stage_pair<O + 0, 1>(a1, a2, 1.f, 1.f, 0.5f, 0u, 0u, 0u, 0u, ad01 + OFF_AK, ad2 + OFF_AK, t);
  float n0[2][2], n1[2][2];
  norms<O + 2, 0>(a1, a2, t, n0);
  norms<O + 2, 1>(a1, a2, t, n1);
  const float4 km = *(const float4*)(smem + OFF_MISC);
  const float b[4][2] = {{sqrt_ap(n0[0][0]) * km.x, sqrt_ap(n0[0][1]) * km.x}, {sqrt_ap(n0[1][0]) * km.y, sqrt_ap(n0[1][1]) * km.y},
                         {sqrt_ap(n1[0][0]) * km.z, sqrt_ap(n1[0][1]) * km.z}, {sqrt_ap(n1[1][0]) * km.w, sqrt_ap(n1[1][1]) * km.w}};
  bool unsafe = false;
#pragma unroll
  for (int i = 0; i < 8; i++) unsafe |= !(b[i >> 1][i & 1] <= FAST_BOUND);
  fence_async_smem();
  uint32_t any;
  asm volatile("{\n.reg .pred p, q;\nsetp.ne.u32 p, %1, 0;\nbar.red.or.pred q, %2, 128, p;\nselp.u32 %0, 1, 0, q;\n}\n"
               : "=r"(any) : "r"((uint32_t)unsafe), "r"(NB_WG + wg) : "memory");
  const bool slow = __any_sync(~0u, any);
  uint32_t xq[4][2];
#pragma unroll
  for (int i = 0; i < 8; i++) xq[i >> 1][i & 1] = slow ? 0u : ((t & 1) ? BF_ONE : packbf(-b[i >> 1][i & 1], 1.f));
  stage_pair<O + 2, 0>(a1, a2, QSCALE, QSCALE, 1.f, xq[0][0], xq[0][1], xq[1][0], xq[1][1], ad01 + OFF_Q, ad2 + OFF_Q, t);
  stage_pair<O + 2, 1>(a1, a2, QSCALE, QSCALE, 1.f, xq[2][0], xq[2][1], xq[3][0], xq[3][1], ad01 + OFF_Q, ad2 + OFF_Q, t);
  const uint32_t one = (t & 1) ? 0u : BF_ONE;
  stage_pair<O + 1, 0>(a1, a2, 1.f, 1.f, 1.f, one, one, one, one, ad01 + OFF_V, ad2 + OFF_V, t);
  stage_pair<O + 1, 1>(a1, a2, 1.f, 1.f, 1.f, one, one, one, one, ad01 + OFF_V, ad2 + OFF_V, t);
  return slow;
}

constexpr uint64_t NO_LBO = ~(0x3FFFull << 16);
__device__ __forceinline__ void issue_proj(float (&p)[2][12], uint32_t img, uint32_t wph) {
  const uint64_t ad = mkdesc(img, 128, 384, 0), wd = mkdesc(wph, 384, 128, 0);
#pragma unroll
  for (int u = 0; u < 2; u++) {
    mma_n24_ss_tb(p[u], ad + u * 192, wd + u * 72, 0);
    mma_n24_ss_tb(p[u], (ad + u * 192 + 16) & NO_LBO, (wd + u * 72 + 48) & NO_LBO, 1);
  }
}

__device__ __forceinline__ uint32_t exp2_bits(float y0, float y1, uint32_t cm, uint32_t neg1) {
  uint32_t w, m, r;
  asm("prmt.b32 %0, %1, %2, 0x6521;" : "=r"(w) : "f"(y0), "f"(y1));
  asm("lop3.b32 %0, %1, 0x007F007F, %2, 0xEA;" : "=r"(m) : "r"(w), "r"(cm));
  const uint32_t e = m * neg1 + w;
  asm("fma.rn.bf16x2 %0, %1, %2, %3;" : "=r"(r) : "r"(w), "r"(m), "r"(e));
  return r;
}
__device__ __forceinline__ void exp_tile(const float (&s)[64], uint32_t (&p)[32], uint32_t cm, uint32_t neg1) {
#pragma unroll
  for (int g = 0; g < 16; g++) {
    if ((POLY_MASK >> g) & 1) {
      p[2 * g] = exp2_bits(s[4 * g], s[4 * g + 1], cm, neg1);
      p[2 * g + 1] = exp2_bits(s[4 * g + 2], s[4 * g + 3], cm, neg1);
    } else {
      p[2 * g] = packbf(ex2(s[4 * g]), ex2(s[4 * g + 1]));
      p[2 * g + 1] = packbf(ex2(s[4 * g + 2]), ex2(s[4 * g + 3]));
    }
  }
}
__device__ __forceinline__ void issue_qk(float (&s)[64], const uint32_t (&q)[6], uint64_t k, uint64_t k2) {
  mma_n128_rs(s, q[0], q[1], q[2], q[3], k, 0);
  mma_n128_rs(s, q[4], q[5], 0u, 0u, k2, 1);
}
__device__ __forceinline__ void issue_pv(float (&o)[12], const uint32_t (&p)[32], uint64_t vd, int acc) {
#pragma unroll
  for (int kk = 0; kk < 8; kk++) mma_n24_rs_tb(o, p[4 * kk], p[4 * kk + 1], p[4 * kk + 2], p[4 * kk + 3], vd + kk * 48, acc | kk);
}
__device__ __forceinline__ void load_q(uint32_t (&q)[6], uint32_t a) {
#pragma unroll
  for (int i = 0; i < 6; i++) asm volatile("ld.shared.b32 %0, [%1];" : "=r"(q[i]) : "r"(a + (i >> 1) * 128 + (i & 1) * 384) : "memory");
}
struct AttnDesc { uint64_t k, k2, v; };
__device__ __forceinline__ void attn_pair(float (&s)[64], uint32_t (&p0)[32], uint32_t (&p1)[32], float (&o)[12], const uint32_t (&q)[6],
                                          const uint32_t (&qn)[6], const AttnDesc& d, uint32_t co, uint32_t cn, int acc, uint32_t full_next,
                                          uint32_t ph_next, uint32_t empty_prev, uint32_t release, uint32_t cm, uint32_t neg1) {
  exp_tile(s, p0, cm, neg1);
  wg_fence();
  issue_qk(s, q, d.k + co + 384, d.k2 + co + 384);
  wg_commit();
  issue_pv(o, p0, d.v + co, acc);
  wg_commit();
  wg_wait<1>();
  pin(s); pin(p1);
  mbar_arrive_if(empty_prev, release);
  const uint32_t ready = mbar_test(full_next, ph_next);
  exp_tile(s, p1, cm, neg1);
  pin(p1);
  if (!__all_sync(~0u, ready)) mbar_wait_u(full_next, ph_next);
  wg_fence();
  issue_qk(s, qn, d.k + cn, d.k2 + cn);
  wg_commit();
  issue_pv(o, p1, d.v + co + 384, 1);
  wg_commit();
}
__device__ __forceinline__ int bgroup(int G) {
  const int hg = G / 10, j = G % 10;
  return (hg >> 2) * 40 + (j / 5) * 20 + (hg & 3) * 5 + j % 5;
}
__device__ __forceinline__ void stage_o(const float (&o)[12], int odd, uint32_t pair, int w4, int lane, float eps, float s0, float s1) {
  const int src = (lane & ~3) | (odd ? 0 : 2);
  const float l0 = __shfl_sync(~0u, o[8], src) + eps, l1 = __shfl_sync(~0u, o[10], src) + eps;
  const float r0 = s0 * rcp(l0), r1 = s1 * rcp(l1);
  const uint32_t base = pair + w4 * 256;
  stsm4(base + (odd ? 3072 : 0) + (lane >> 4) * 1024 + (lane & 15) * 16, packbf(o[0] * r0, o[1] * r0), packbf(o[2] * r1, o[3] * r1),
        packbf(o[4] * r0, o[5] * r0), packbf(o[6] * r1, o[7] * r1));
  if (((lane & 3) < 2) != (odd != 0)) {
    sts32(base + 2048 + lane * 4, packbf(o[8] * r0, o[9] * r0));
    sts32(base + 2048 + 128 + lane * 4, packbf(o[10] * r1, o[11] * r1));
  }
}
struct Maps { CUtensorMap a64, a16, b64, b16, out; };

__device__ __forceinline__ void w_load(const Maps& m, int it, uint32_t d, uint32_t b, int hg) {
  const int kb = (it % 10) * 2, c = hg * 80 + (hg & 1) * 16, c2 = hg * 80 + ((hg & 1) ? 0 : 64);
  const bool w0 = it < 10;
  const CUtensorMap *p64 = w0 ? &m.b64 : &m.a64, *q64 = w0 ? &m.a64 : &m.b64, *p16 = w0 ? &m.b16 : &m.a16, *q16 = w0 ? &m.a16 : &m.b16;
  mbar_expect(b, W_STAGE);
  tma5(d, p64, 640 + c, kb, b);
  tma5(d + 8192, p64, 1280 + c, kb, b);
  tma5(d + 16384, q64, c, kb, b);
  tma5(d + 24576, p16, 640 + c2, kb, b);
  tma5(d + 26624, p16, 1280 + c2, kb, b);
  tma5(d + 28672, q16, c2, kb, b);
}
__device__ __forceinline__ void x_load(uint4 (&v)[4], const uint8_t* p, int it) {
  const uint8_t* q = p + (it % 10) * 128;
  v[0] = ldg_x(q); v[1] = ldg_x(q + 8 * 1280); v[2] = ldg_x(q + 64); v[3] = ldg_x(q + 8 * 1280 + 64);
}
__device__ __forceinline__ void gemm_step(float (&a1)[96], float (&a2)[24], uint4 (&xv)[4], uint32_t (&f)[4][4], uint32_t (&fp)[4][4],
                                          const uint8_t* xp, int it, int acc, uint32_t sb, uint32_t bars, uint32_t lead) {
  const int s = it % W_NST;
  const uint32_t z = mbar_wait_z(bars + B_WF + 8 * s, (it / W_NST) & 1);
  f[0][0] = xv[0].x ^ z; f[0][1] = xv[1].x ^ z; f[0][2] = xv[0].y ^ z; f[0][3] = xv[1].y ^ z;
  f[1][0] = xv[0].z ^ z; f[1][1] = xv[1].z ^ z; f[1][2] = xv[0].w ^ z; f[1][3] = xv[1].w ^ z;
  f[2][0] = xv[2].x ^ z; f[2][1] = xv[3].x ^ z; f[2][2] = xv[2].y ^ z; f[2][3] = xv[3].y ^ z;
  f[3][0] = xv[2].z ^ z; f[3][1] = xv[3].z ^ z; f[3][2] = xv[2].w ^ z; f[3][3] = xv[3].w ^ z;
#pragma unroll
  for (int i = 0; i < 4; i++) pin(f[i]);
  x_load(xv, xp, it + 2);
  const uint64_t b1 = mkdesc(sb + s * W_STAGE, 8192, 1024, 1), b2 = mkdesc(sb + s * W_STAGE + 24576, 2048, 256, 3);
  wg_fence();
#pragma unroll
  for (int kk = 0; kk < 4; kk++) {
    mma_n192_rs_tb(a1, f[kk][0], f[kk][1], f[kk][2], f[kk][3], b1 + kk * 128, acc | kk);
    mma_n48_rs_tb(a2, f[kk][0], f[kk][1], f[kk][2], f[kk][3], b2 + kk * 32, acc | kk);
  }
  wg_commit();
  wg_wait<1>();
#pragma unroll
  for (int i = 0; i < 4; i++) pin(fp[i]);
  mbar_arrive_if(bars + B_WE + 8 * ((it + W_NST - 1) % W_NST), lead && acc);
}

__global__ void __cluster_dims__(2, 1, 1) __launch_bounds__(384, 1)
fused_block(const __grid_constant__ Maps maps, const __nv_bfloat16* __restrict__ x, const __nv_bfloat16* __restrict__ wphi,
            const __nv_bfloat16* __restrict__ gate_w, const uint8_t* __restrict__ woa, const uint8_t* __restrict__ wob, uint32_t cm, uint32_t neg1) {
  extern __shared__ __align__(1024) uint8_t smem[];
  const uint32_t sb = smem_u32(smem), bars = sb + OFF_BAR;
  const int warp = __shfl_sync(~0u, threadIdx.x >> 5, 0), lane = threadIdx.x & 31, wg = warp >> 2;
  const int bid = blockIdx.x;
  const int mt = (bid & 1) + 2 * (bid >> 4), hg = (bid >> 1) & 7;
  const int half = bid & 1, nt = (bid >> 1) & 3, mt3 = bid >> 3;
  PROF(threadIdx.x == 0, 0);
  const uint8_t* xp = (const uint8_t*)x + (size_t)(mt * 128 + (warp & 7) * 16 + (lane >> 2)) * 1280 + (lane & 3) * 16;
  uint4 xa[4], xb[4];
  if (wg < 2) { x_load(xa, xp, 0); x_load(xb, xp, 1); }
  if (warp == 8) {
    if (lane == 0) {
#pragma unroll
      for (int i = 0; i < W_NST; i++) { mbar_init(bars + B_WF + 8 * i, 1); mbar_init(bars + B_WE + 8 * i, 2); }
      fence_async_smem();
    }
    __syncwarp();
    bar_arrive(0, 288);
    if (lane == 0) { w_load(maps, 0, sb, bars + B_WF, hg); w_load(maps, 1, sb + W_STAGE, bars + B_WF + 8, hg); }
    __syncwarp();
  }

  if (wg == 2) {
    reg_dec<40>();
    if (warp == 8) {
      if (lane == 0) {
        for (int it = 2; it < 20; it++) {
          const int s = it % W_NST;
          if (it >= W_NST) mbar_wait(bars + B_WE + 8 * s, ((it / W_NST) - 1) & 1);
          PROF(it == 5, 1);
          w_load(maps, it, sb + s * W_STAGE, bars + B_WF + 8 * s, hg);
        }
      }
      __syncwarp();
      bar_sync(NB_HELP, 128);
      const uint32_t epoch = *(volatile uint32_t*)(smem + OFF_MISC + 16);
      if (lane == 0) {
        cnt_wait(C_KV + hg, 16 * epoch);
        for (int c = 0; c < 32; c++) {
          const int s = c & 3;
          const uint8_t* src = g_KV + (size_t)(hg * 4 + (c >> 3)) * IMG_HEAD + (c & 7) * 12288;
          mbar_wait(bars + B_KE + 8 * s, (c >> 2) & 1);
          mbar_expect(bars + B_KF + 8 * s, KV_CHUNK);
          bulk_g2s(sb + s * KV_CHUNK, src, 12288, bars + B_KF + 8 * s);
          bulk_g2s(sb + s * KV_CHUNK + 12288, src + (size_t)NH * IMG_HEAD, 12288, bars + B_KF + 8 * s);
        }
        cnt_wait(C_WO, NCTA * epoch);
        cnt_wait(C_OA + mt3, 8 * epoch);
        mbar_wait(bars + B_RF, 0);
        for (int it = 0; it < 10; it++) {
          const int s = it % 5, ks = (it < 5 ? 0 : 5) + half * 5 + it;
          if (it >= 5) mbar_wait(bars + B_OE + 8 * s, 0);
          else if (it >= 2) mbar_wait(bars + B_KE + 8 * (it - 1), 0);
          if (it == 7) { PROF(true, 28); cnt_wait(C_OB + mt3, 8 * epoch); PROF(true, 29); }
          const uint32_t d = sb + o_stage(s), b = bars + B_OF + 8 * s;
          const uint8_t* ga = g_OAB + (size_t)mt3 * 327680 + ks * 8192;
          mbar_expect(b, O_STAGE);
          bulk_g2s(d + 16384, g_WOI + (size_t)nt * 409600 + ks * 20480, 20480, b);
          bulk_g2s(d, ga, 8192, b);
          bulk_g2s(d + 8192, ga + 163840, 8192, b);
        }
      }
    } else if (warp == 9) {
      uint32_t epoch = 0;
      if (lane == 0) {
#pragma unroll
        for (int i = 0; i < 4; i++) { mbar_init(bars + B_KF + 8 * i, 1); mbar_init(bars + B_KE + 8 * i, 2); }
#pragma unroll
        for (int i = 0; i < 5; i++) { mbar_init(bars + B_OF + 8 * i, 1); mbar_init(bars + B_OE + 8 * i, 2); }
        mbar_init(bars + B_RF, 1);
        fence_async_smem();
        epoch = atomicAdd(g_CNT + C_START * 8, 1u) / NCTA + 1;
        *(volatile uint32_t*)(smem + OFF_MISC + 16) = epoch;
      }
      epoch = __shfl_sync(~0u, epoch, 0);
      bar_arrive(NB_HELP, 128);
#pragma unroll 1
      for (int e = lane; e < 96; e += 32) {
        const int i = e / 24, slot = e % 24;
        int d = -1;
        if (i & 1) { if (slot < 16) d = slot + 4; else if (slot >= 20) d = slot - 20; }
        else if (slot < 20) d = slot;
        uint2 v[5] = {};
        if (d >= 0) {
#pragma unroll
          for (int u = 0; u < 5; u++) v[u] = __ldg((const uint2*)(wphi + ((hg * 4 + i) * 20 + d) * 20) + u);
        }
        uint8_t* dst = smem + OFF_WPH + i * 1152 + (slot >> 3) * 384 + (slot & 7) * 16;
        *(uint4*)dst = make_uint4(v[0].x, v[0].y, v[1].x, v[1].y);
        *(uint4*)(dst + 128) = make_uint4(v[2].x, v[2].y, v[3].x, v[3].y);
        *(uint4*)(dst + 256) = make_uint4(v[4].x, v[4].y, v[4].x, v[4].y);
      }
      fence_async_smem();
      bar_sync(NB_STAGED, 288);
      {
        uint32_t m = *(volatile uint32_t*)(smem + OFF_MISC + 32 + lane * 4);
        m = max(m, __shfl_xor_sync(~0u, m, 4)); m = max(m, __shfl_xor_sync(~0u, m, 8)); m = max(m, __shfl_xor_sync(~0u, m, 16));
        if (lane < 4) *(volatile uint32_t*)(smem + OFF_MISC + lane * 4) = m;
        fence_async_smem();
        __syncwarp();
      }
      if (lane == 0) {
        bulk_s2g(g_KMAX + hg * 16 + mt, sb + OFF_MISC, 16);
#pragma unroll 1
        for (int i = 0; i < 16; i++) {
          bulk_s2g(g_KV + (size_t)((i >> 3) * NH + hg * 4 + (i & 3)) * IMG_HEAD + (mt * 2 + ((i >> 2) & 1)) * 3072, sb + OFF_Q + i * 3072, 3072);
          __nanosleep(STNS);
        }
        bulk_commit_wait();
        PROF(true, 22);
        cnt_add_done(C_KV + hg);
        cnt_wait(C_KV + hg, 16 * epoch);
      }
      __syncwarp();
      {
        uint4 v = ldg_cg4(g_KMAX + hg * 16 + (lane & 15));
        v.x = __reduce_max_sync(~0u, v.x); v.y = __reduce_max_sync(~0u, v.y); v.z = __reduce_max_sync(~0u, v.z); v.w = __reduce_max_sync(~0u, v.w);
        if (lane < 4) *(volatile float*)(smem + OFF_MISC + lane * 4) =
            sqrt_ap(__uint_as_float(lane == 0 ? v.x : lane == 1 ? v.y : lane == 2 ? v.z : v.w)) * (QSCALE * 1.02f);
      }
      PROF(lane == 0, 24);
      bar_arrive(NB_FREE, 288);
      bar_sync(NB_TAIL, 288);
      if (lane == 0) {
#pragma unroll 1
        for (int i = 0; i < 4; i++) bulk_s2g(g_KVP + (size_t)((hg * 4 + i) * 16 + mt) * 480, sb + OFF_PHK + i * 10240, 3840);
        bulk_commit_wait();
        cnt_add_done(C_KVP + hg);
        cnt_wait(C_GATE + mt, 8 * epoch);
      }
      __syncwarp();
      {
        const uint4 g0 = ldg_cg4(g_GATE + mt * 128 + lane * 2), g1 = ldg_cg4(g_GATE + mt * 128 + 64 + lane * 2);
        *(uint4*)(smem + OFF_GATE + lane * 16) = g0;
        *(uint4*)(smem + OFF_GATE + 512 + lane * 16) = g1;
      }
      bar_arrive(NB_GATE, 160);
      bar_arrive(NB_GATE + 1, 160);
      PROF(lane == 0, 21);
      if (lane == 0) cnt_wait(C_KVB + hg, 16 * epoch);
      __syncwarp();
#pragma unroll 1
      for (int e0 = 0; e0 < 480; e0 += 160) {
        uint4 v[5];
#pragma unroll
        for (int u = 0; u < 5; u++) v[u] = ldg_cg4(g_KVB + hg * 4 * 480 + (e0 + u * 32 + lane) * 4);
#pragma unroll
        for (int u = 0; u < 5; u++) *(uint4*)(smem + OFF_V + (e0 + u * 32 + lane) * 16) = v[u];
      }
      fence_async_smem();
      PROF(lane == 0, 25);
      bar_arrive(NB_KVB, 160);
      bar_arrive(NB_KVB + 1, 160);
      uint8_t* og = g_OAB + (size_t)mt * 327680;
#pragma unroll 1
      for (int w = 0; w < 2; w++) {
        bar_sync(NB_READ + w, 160);
        if (lane == 0) {
          bulk_s2g(og + w * 163840 + hg * 10240, sb + OFF_AQ + w * 12288, 10240);
          bulk_s2g(og + w * 163840 + (80 + bgroup(hg * 10)) * 1024, sb + OFF_Q + w * 12288, 5120);
        }
        __syncwarp();
      }
      if (lane == 0) { bulk_commit_wait(); mbar_arrive(bars + B_RF); cnt_add_done(C_OA + mt); }
      __syncwarp();
      bar_sync(NB_LAST, 288);
      if (lane == 0) {
        bulk_s2g(og + (80 + bgroup(hg * 10 + 5)) * 1024, sb + OFF_Q + 6144, 5120);
        bulk_s2g(og + 163840 + (80 + bgroup(hg * 10 + 5)) * 1024, sb + OFF_Q + 12288 + 6144, 5120);
        bulk_commit_wait();
        cnt_add_done(C_OB + mt);
        PROF(true, 27);
      }
    } else {
      const int ht = threadIdx.x - 320;
      bar_sync(NB_HELP, 128);
      const uint32_t epoch = *(volatile uint32_t*)(smem + OFF_MISC + 16);
      {
        const int row = mt * 128 + hg * 16 + (ht >> 2), q = ht & 3;
        float acc = 0.f;
#pragma unroll 1
        for (int i0 = 0; i0 < 20; i0 += 5) {
          uint4 xv[5];
#pragma unroll
          for (int i = 0; i < 5; i++) xv[i] = __ldg((const uint4*)(x + (size_t)row * DM + (i0 + i) * 32 + q * 8));
#pragma unroll
          for (int i = 0; i < 5; i++) {
            const uint4 gw = __ldg((const uint4*)(gate_w + (i0 + i) * 32 + q * 8));
            const uint32_t xr[4] = {xv[i].x, xv[i].y, xv[i].z, xv[i].w}, gr[4] = {gw.x, gw.y, gw.z, gw.w};
#pragma unroll
            for (int u = 0; u < 4; u++) {
              uint32_t p;
              asm("mul.rn.bf16x2 %0, %1, %2;" : "=r"(p) : "r"(xr[u]), "r"(gr[u]));
              acc += bf_lo(p) + bf_hi(p);
            }
          }
        }
        acc += __shfl_xor_sync(~0u, acc, 1);
        acc += __shfl_xor_sync(~0u, acc, 2);
        if (q == 0) {
          const float g = bf_round(__fdividef(1.f, 1.f + __expf(-bf_round(acc))));
          g_GATE[row] = make_float2(g, bf_round(1.f - g));
        }
      }
      bar_sync(NB_HELP, 64);
      if (ht == 0) { cnt_add(C_GATE + mt); PROF(true, 18); cnt_wait(C_KVP + hg, 16 * epoch); }
      bar_sync(NB_HELP, 64);
      if (ht < 60) {
        const int hd = hg * 4 + ht / 15, e = mt * 30 + (ht % 15) * 2;
        const float2* src = g_KVP + (size_t)hd * 16 * 480 + e;
        float4 s = make_float4(0.f, 0.f, 0.f, 0.f);
#pragma unroll 1
        for (int m0 = 0; m0 < 16; m0 += 4) {
          uint4 v[4];
#pragma unroll
          for (int m = 0; m < 4; m++) v[m] = ldg_cg4(src + (m0 + m) * 480);
#pragma unroll
          for (int m = 0; m < 4; m++) {
            s.x += __uint_as_float(v[m].x); s.y += __uint_as_float(v[m].y); s.z += __uint_as_float(v[m].z); s.w += __uint_as_float(v[m].w);
          }
        }
        *(uint2*)(g_KVB + hd * 480 + e) = make_uint2(packbf(s.x, s.y), packbf(s.z, s.w));
      }
      bar_sync(NB_HELP, 64);
      if (ht == 0) cnt_add(C_KVB + hg);
      PROF(ht == 0, 20);
#pragma unroll 1
      for (int kg = bid; kg < 160; kg += NCTA) {
        const uint8_t* src = (kg < 80 ? woa + (size_t)kg * 10240 : wob + (size_t)(kg - 80) * 10240) + (ht & 7) * 1280 + (ht >> 3) * 16;
        uint8_t* dst = g_WOI + (kg < 80 ? kg : 80 + bgroup(kg - 80)) * 2560 + (ht & 7) * 16;
#pragma unroll 1
        for (int c0 = 0; c0 < 80; c0 += 40) {
          uint4 v[5];
#pragma unroll
          for (int u = 0; u < 5; u++) v[u] = __ldg((const uint4*)(src + (c0 + u * 8) * 16));
#pragma unroll
          for (int u = 0; u < 5; u++) {
            const int c = c0 + u * 8 + (ht >> 3);
            *(uint4*)(dst + (size_t)(c / 20) * 409600 + (c % 20) * 128) = v[u];
          }
        }
      }
      bar_sync(NB_HELP, 64);
      if (ht == 0) cnt_add(C_WO);
      PROF(ht == 0, 19);
    }
  } else {
    reg_inc<232>();
    bar_sync(0, 288);
    const int w4 = warp & 3, t = lane & 3;
    const uint32_t lead = (threadIdx.x & 127) == 0;
    bool slow;
    {
      const int mi = lane >> 3;
      const uint32_t sbase = sb + wg * 12288 + (w4 * 2 + (mi & 1)) * 384 + (lane & 7) * 16;
      const uint32_t ad01 = sbase + (mi >> 1) * 128, ad2 = sbase + (mi >> 1) * 3072 + 256;
      float a1[96], a2[24];
      uint32_t fa[4][4] = {}, fb[4][4] = {};
#pragma unroll 1
      for (int tile = 0; tile < 2; tile++) {
#pragma unroll 1
        for (int ks = 0; ks < 10; ks += 2) {
          gemm_step(a1, a2, xa, fa, fb, xp, tile * 10 + ks, ks, sb, bars, lead);
          gemm_step(a1, a2, xb, fb, fa, xp, tile * 10 + ks + 1, 1, sb, bars, lead);
        }
        wg_wait<0>();
        pin(a1); pin(a2);
#pragma unroll
        for (int i = 0; i < 4; i++) pin(fb[i]);
        mbar_arrive_if(bars + B_WE + 8 * 4, lead);
        PROF(threadIdx.x == 0, 2 + 2 * tile);
        if (tile == 0) {
          if (hg & 1) epilogue0<4>(a1, a2, warp * 2, lane, ad01, ad2, sb + OFF_MISC + 32 + warp * 16);
          else epilogue0<0>(a1, a2, warp * 2, lane, ad01, ad2, sb + OFF_MISC + 32 + warp * 16);
          fence_async_smem();
          bar_arrive(NB_STAGED, 288);
          PROF(threadIdx.x == 0, 3);
        }
      }
      bar_sync(NB_FREE, 288);
#pragma unroll
      for (int s = 0; s < 3; s++) mbar_arrive_if(bars + B_KE + 8 * s, lead);
      mbar_wait_u(bars + B_WE + 8 * 4, 1);
      if (hg & 1) slow = epilogue1<4>(a1, a2, smem, wg, t, ad01, ad2);
      else slow = epilogue1<0>(a1, a2, smem, wg, t, ad01, ad2);
      PROF(threadIdx.x == 0, 15);
      const uint32_t ak = sb + OFF_AK + wg * 12288, wph = sb + OFF_WPH;
      const uint32_t pka = sb + OFF_PHK + (warp * 2 + (mi & 1)) * 640 + (mi >> 1) * 128 + (lane & 7) * 16;
      float pp[2][12];
#pragma unroll 1
      for (int i = 0; i < 4; i += 2) {
        wg_fence();
        issue_proj(pp, ak + i * 3072, wph + i * 1152);
        wg_commit();
        wg_wait<0>();
        pin(pp[0]); pin(pp[1]);
        uint32_t f[2][10];
        hedgehog(pp[0], f[0], t);
        hedgehog(pp[1], f[1], t);
#pragma unroll
        for (int u = 0; u < 2; u++) {
          stsm4(pka + (i + u) * 10240, f[u][0], f[u][1], f[u][2], f[u][3]);
          stsm4(pka + (i + u) * 10240 + 256, f[u][4], f[u][5], f[u][6], f[u][7]);
          stsm2(pka + (i + u) * 10240 + 512, f[u][8], f[u][9]);
        }
      }
      float (&pa)[12] = pp[0], (&pb)[12] = pp[1];
      mbar_arrive_if(bars + B_KE + 8 * 3, lead);
      fence_async_smem();
      PROF(threadIdx.x == 0, 16);
      bar_sync(NB_PHIK, 256);
      wg_fence();
#pragma unroll
      for (int j = 0; j < 2; j++) {
        const uint64_t ad = mkdesc(sb + OFF_PHK + (wg * 2 + j) * 10240, 640, 128, 0), vd = mkdesc(sb + OFF_V + (wg * 2 + j) * 3072, 384, 128, 0);
#pragma unroll
        for (int ks = 0; ks < 8; ks++) mma_n24_ss_tatb(j ? pb : pa, ad + ks * 80, vd + (ks >> 2) * 768 + (ks & 3) * 48, ks);
      }
      wg_commit();
      wg_wait<0>();
      pin(pa); pin(pb);
      bar_sync(NB_WG + wg, 128);
      {
        float2* dst = (float2*)(smem + OFF_PHK + wg * 20480) + w4 * 192 + lane;
        if (w4 < 3) {
          dst[0] = make_float2(pa[0], pa[1]); dst[32] = make_float2(pa[4], pa[5]); dst[64] = make_float2(pa[8], pa[9]);
          dst[1280] = make_float2(pb[0], pb[1]); dst[1312] = make_float2(pb[4], pb[5]); dst[1344] = make_float2(pb[8], pb[9]);
        }
        if (w4 < 2) {
          dst[96] = make_float2(pa[2], pa[3]); dst[128] = make_float2(pa[6], pa[7]); dst[160] = make_float2(pa[10], pa[11]);
          dst[1376] = make_float2(pb[2], pb[3]); dst[1408] = make_float2(pb[6], pb[7]); dst[1440] = make_float2(pb[10], pb[11]);
        }
      }
      fence_async_smem();
      bar_arrive(NB_TAIL, 288);
      PROF(threadIdx.x == 0, 5);
    }
    {
      const uint32_t gate = sb + OFF_GATE + (warp * 16 + (lane >> 2)) * 8, qs = sb + OFF_Q + wg * 12288;
      AttnDesc d;
      d.k = mkdesc(sb, 128, 384, 0); d.k2 = mkdesc(sb + 256, 0, 384, 0);
      d.v = mkdesc(sb + 12288, 384, 128, 0);
      const uint32_t qa = qs + w4 * 768 + lane * 4;
      float o[12], s0[64];
      uint32_t q[6];
      load_q(q, qa);
      mbar_wait_u(bars + B_KF, 0);
      wg_fence();
      issue_qk(s0, q, d.k, d.k2);
      wg_commit();
      wg_wait<0>();
      pin(s0); pin(q);
#pragma unroll 1
      for (int pass = 0; pass < 4; pass++) {
        if (!slow) {
          uint32_t p0[32], p1[32] = {};
#pragma unroll 1
          for (int j = 0; j < 7; j++) {
            const int nx = (j + 1) & 3;
            attn_pair(s0, p0, p1, o, q, q, d, (j & 3) * 1536, nx * 1536, j, bars + B_KF + 8 * nx, (j + 1) >> 2, bars + B_KE + 8 * ((j - 1) & 3),
                      lead && j, cm, neg1);
            wg_wait<1>();
            pin(s0); pin(p0);
          }
          const int last = pass == 3;
          uint32_t qn[6];
          load_q(qn, qa + ((pass + 1) & 3) * 3072);
          attn_pair(s0, p0, p1, o, q, qn, d, 3 * 1536, last ? 3 * 1536 : 0, 1, bars + B_KF + (last ? 24 : 0), last, bars + B_KE + 16, lead, cm, neg1);
          wg_wait<0>();
          pin(s0); pin(o); pin(p0); pin(p1); pin(qn);
#pragma unroll
          for (int i = 0; i < 6; i++) q[i] = qn[i];
          mbar_arrive_if(bars + B_KE + 24, lead);
        } else {
          uint32_t p[32];
          float m0 = -INFINITY, m1 = -INFINITY;
          load_q(q, qa + pass * 3072);
#pragma unroll
          for (int i = 0; i < 12; i++) o[i] = 0.f;
#pragma unroll 1
          for (int j = 0; j < 16; j++) {
            const int slot = (j >> 1) & 3;
            const uint32_t co = slot * 1536 + (j & 1) * 384;
            mbar_wait_u(bars + B_KF + 8 * slot, j >> 3);
            wg_fence();
            issue_qk(s0, q, d.k + co, d.k2 + co);
            wg_commit();
            wg_wait<0>();
            pin(s0);
            float n0 = m0, n1 = m1;
#pragma unroll
            for (int g = 0; g < 16; g++) { n0 = fmaxf(n0, fmaxf(s0[4 * g], s0[4 * g + 1])); n1 = fmaxf(n1, fmaxf(s0[4 * g + 2], s0[4 * g + 3])); }
            n0 = fmaxf(n0, __shfl_xor_sync(~0u, n0, 1)); n1 = fmaxf(n1, __shfl_xor_sync(~0u, n1, 1));
            n0 = fmaxf(n0, __shfl_xor_sync(~0u, n0, 2)); n1 = fmaxf(n1, __shfl_xor_sync(~0u, n1, 2));
            const float c0 = ex2(m0 - n0), c1 = ex2(m1 - n1);
            m0 = n0; m1 = n1;
#pragma unroll
            for (int i = 0; i < 3; i++) { o[4 * i] *= c0; o[4 * i + 1] *= c0; o[4 * i + 2] *= c1; o[4 * i + 3] *= c1; }
#pragma unroll
            for (int g = 0; g < 16; g++) {
              const uint32_t sg = ((POLY_MASK >> g) & 1) ? 0x80008000u : 0u;
              p[2 * g] = packbf(ex2(s0[4 * g] - m0), ex2(s0[4 * g + 1] - m0)) ^ sg;
              p[2 * g + 1] = packbf(ex2(s0[4 * g + 2] - m1), ex2(s0[4 * g + 3] - m1)) ^ sg;
            }
            wg_fence();
            issue_pv(o, p, d.v + co, 1);
            wg_commit();
            wg_wait<0>();
            pin(o); pin(p);
            mbar_arrive_if(bars + B_KE + 8 * slot, lead && (j & 1));
          }
        }
        if (pass == 0) bar_sync(NB_GATE + wg, 160);
        stage_o(o, pass & 1, qs + (pass >> 1) * 6144, w4, lane, 0.f, lds_f2(gate).y, lds_f2(gate + 64).y);
        PROF(threadIdx.x == 0, 6 + pass);
        if (pass == 1 + wg) {
          const uint32_t aq = sb + OFF_AQ + wg * 12288, wph = sb + OFF_WPH;
          float pp[2][12], oa[2][12];
          wg_fence();
          issue_proj(pp, aq, wph);
          wg_commit();
          const float g0 = lds_f2(gate).x, g1 = lds_f2(gate + 64).x;
          bar_sync(NB_KVB + wg, 160);
          wg_wait<0>();
          pin(pp[0]); pin(pp[1]);
#pragma unroll 1
          for (int i = 0; i < 4; i += 2) {
            uint32_t f[2][10];
            hedgehog(pp[0], f[0], t);
            hedgehog(pp[1], f[1], t);
            pin(f[0]); pin(f[1]);
            wg_fence();
#pragma unroll
            for (int u = 0; u < 2; u++) {
              const uint64_t kvd = mkdesc(sb + OFF_V + (i + u) * 1920, 384, 128, 0);
              mma_n24_rs_tb(oa[u], f[u][0], f[u][1], f[u][2], f[u][3], kvd, 0);
              mma_n24_rs_tb(oa[u], f[u][4], f[u][5], f[u][6], f[u][7], kvd + 48, 1);
              mma_n24_rs_tb(oa[u], f[u][8], f[u][9], 0u, 0u, (kvd + 96) & NO_LBO, 1);
            }
            issue_proj(pp, aq + 2 * 3072, wph + 2 * 1152);
            wg_commit();
            wg_wait<0>();
            pin(pp[0]); pin(pp[1]); pin(oa[0]); pin(oa[1]); pin(f[0]); pin(f[1]);
            stage_o(oa[0], 0, aq + i * 2560, w4, lane, 1e-6f, g0, g1);
            stage_o(oa[1], 1, aq + i * 2560, w4, lane, 1e-6f, g0, g1);
          }
          fence_async_smem();
          bar_arrive(NB_READ + wg, 160);
          PROF(threadIdx.x == 0, 17);
        }
      }
      fence_async_smem();
      bar_arrive(NB_LAST, 288);
    }
    {
      asm volatile("barrier.cluster.arrive.relaxed.aligned;" ::: "memory");
      float acc[80];
#pragma unroll 1
      for (int it = 0; it < 10; it++) {
        const int s = it % 5;
        mbar_wait_u(bars + B_OF + 8 * s, it / 5);
        PROF(threadIdx.x == 0 && (it == 0 || it == 7), 10 + it / 7);
        const uint32_t st = sb + o_stage(s);
        const uint64_t ad = mkdesc(st + wg * 8192, 1024, 128, 0), bd = mkdesc(st + 16384, 2560, 128, 0);
        wg_fence();
#pragma unroll
        for (int kk = 0; kk < 4; kk++) mma_n160_ss_tb(acc, ad + kk * 128, bd + kk * 320, it | kk);
        wg_commit();
        wg_wait<1>();
        mbar_arrive_if(bars + B_OE + 8 * ((it + 4) % 5), lead && it);
      }
      wg_wait<0>();
      pin(acc);
      PROF(threadIdx.x == 0, 12);
      asm volatile("barrier.cluster.wait.aligned;" ::: "memory");
      uint32_t remote;
      asm volatile("mapa.shared::cluster.u32 %0, %1, %2;" : "=r"(remote) : "r"(sb + OFF_Q + threadIdx.x * 16), "r"(half ^ 1));
#pragma unroll
      for (int j = 0; j < 5; j++) {
        uint32_t v[4];
#pragma unroll
        for (int u = 0; u < 4; u++) v[u] = half ? packbf(acc[8 * j + 2 * u], acc[8 * j + 2 * u + 1]) : packbf(acc[40 + 8 * j + 2 * u], acc[41 + 8 * j + 2 * u]);
        asm volatile("st.shared::cluster.v4.b32 [%0], {%1,%2,%3,%4};" ::"r"(remote + j * 4096), "r"(v[0]), "r"(v[1]), "r"(v[2]), "r"(v[3]) : "memory");
      }
      asm volatile("barrier.cluster.arrive.release.aligned;" ::: "memory");
      asm volatile("barrier.cluster.wait.acquire.aligned;" ::: "memory");
      PROF(threadIdx.x == 0, 13);
      const uint32_t ob = sb + wg * 10240;
      const uint32_t oa = ob + (w4 * 16 + (lane & 15)) * 160 + (lane >> 4) * 16;
      uint32_t pk[20];
#pragma unroll
      for (int j = 0; j < 5; j++) {
        const uint4 r = *(const uint4*)(smem + OFF_Q + j * 4096 + threadIdx.x * 16);
        const uint32_t rv[4] = {r.x, r.y, r.z, r.w};
#pragma unroll
        for (int u = 0; u < 4; u++) {
          const float v0 = half ? acc[40 + 8 * j + 2 * u] : acc[8 * j + 2 * u], v1 = half ? acc[41 + 8 * j + 2 * u] : acc[8 * j + 2 * u + 1];
          pk[4 * j + u] = packbf(v0 + bf_lo(rv[u]), v1 + bf_hi(rv[u]));
        }
      }
#pragma unroll
      for (int j = 0; j < 10; j += 2) stsm4(oa + j * 16, pk[2 * j], pk[2 * j + 1], pk[2 * j + 2], pk[2 * j + 3]);
      fence_async_smem();
      bar_sync(NB_WG + wg, 128);
      if (lead) {
        asm volatile("cp.async.bulk.tensor.2d.global.shared::cta.bulk_group [%0, {%2,%3}], [%1];" ::"l"(&maps.out), "r"(ob), "r"(nt * 160 + half * 80),
                     "r"(mt3 * 128 + wg * 64) : "memory");
        asm volatile("cp.async.bulk.commit_group;" ::: "memory");
        asm volatile("cp.async.bulk.wait_group.read 0;" ::: "memory");
      }
      PROF(threadIdx.x == 0, 14);
    }
  }
}

typedef CUresult (*EncodeFn)(CUtensorMap*, CUtensorMapDataType, cuuint32_t, void*, const cuuint64_t*, const cuuint64_t*, const cuuint32_t*,
                             const cuuint32_t*, CUtensorMapInterleave, CUtensorMapSwizzle, CUtensorMapL2promotion, CUtensorMapFloatOOBfill);

void encode(EncodeFn fn, CUtensorMap* m, const void* p, int rank, const cuuint64_t* dims, const cuuint64_t* strides, const cuuint32_t* box,
            CUtensorMapSwizzle sw) {
  const cuuint32_t es[5] = {1, 1, 1, 1, 1};
  fn(m, CU_TENSOR_MAP_DATA_TYPE_BFLOAT16, rank, const_cast<void*>(p), dims, strides, box, es, CU_TENSOR_MAP_INTERLEAVE_NONE, sw,
     CU_TENSOR_MAP_L2_PROMOTION_L2_128B, CU_TENSOR_MAP_FLOAT_OOB_FILL_NONE);
}

}

extern "C" void kernel_launch(void* const* d_in, const int* in_sizes, int n_in, void* d_out, int out_size) {
  (void)in_sizes; (void)n_in; (void)out_size;
  static EncodeFn enc = nullptr;
  if (!enc) {
    void* fn = nullptr;
    cudaDriverEntryPointQueryResult qr;
    cudaGetDriverEntryPoint("cuTensorMapEncodeTiled", &fn, cudaEnableDefault, &qr);
    enc = (EncodeFn)fn;
    cudaFuncSetAttribute(fused_block, cudaFuncAttributeMaxDynamicSharedMemorySize, SMEM_BYTES);
  }
  Maps maps;
  {
    const cuuint64_t dx[2] = {640, 2048}, sx[1] = {1280};
    const cuuint32_t bo[2] = {80, 64};
    encode(enc, &maps.out, d_out, 2, dx, sx, bo, CU_TENSOR_MAP_SWIZZLE_NONE);
    const cuuint64_t dw[5] = {1920, 2, 4, 4, 20}, sw[4] = {3840, 8 * 3840, 2 * 3840, 32 * 3840};
    const cuuint32_t b64[5] = {64, 2, 4, 4, 2}, b16[5] = {16, 2, 4, 4, 2};
    encode(enc, &maps.a64, d_in[1], 5, dw, sw, b64, CU_TENSOR_MAP_SWIZZLE_128B);
    encode(enc, &maps.a16, d_in[1], 5, dw, sw, b16, CU_TENSOR_MAP_SWIZZLE_32B);
    encode(enc, &maps.b64, d_in[5], 5, dw, sw, b64, CU_TENSOR_MAP_SWIZZLE_128B);
    encode(enc, &maps.b16, d_in[5], 5, dw, sw, b16, CU_TENSOR_MAP_SWIZZLE_32B);
  }
  fused_block<<<NCTA, 384, SMEM_BYTES, cudaStreamPerThread>>>(maps, (const __nv_bfloat16*)d_in[0], (const __nv_bfloat16*)d_in[2],
                                                               (const __nv_bfloat16*)d_in[7],
                                                               (const uint8_t*)d_in[3], (const uint8_t*)d_in[6], 0x1F801F80u, 0xFFFFFFFFu);
}
```

```cpp
#include <cuda_runtime.h>
#include <cuda_bf16.h>
#include <cuda.h>
#include <stdint.h>

#define STNS 100
#define POLLNS 40
#define BGNS 2500
#define XNOKV 0
#define XNOST 0
#define XDELAY 0
namespace {

constexpr int SEQ = 2048, DM = 640, NH = 32, NCTA = 128;
constexpr int IMG_HEAD = SEQ * 48;
#define POLY_MASK 0x6D6Du
constexpr float LOG2E = 1.4426950408889634f;
constexpr float QSCALE = 0.22360679774997896f * 1.4426950408889634f;
constexpr uint32_t BF_ONE = 0x3F80u;
constexpr uint32_t BF_MAGIC = 0x43E0u;
constexpr uint32_t BF_MU_HI = 0x4025u;
constexpr uint32_t BF_MU_LO = 0x3B8Bu;
constexpr float FAST_BOUND = 40.0f;

__device__ __align__(1024) uint8_t g_KV[2 * NH * IMG_HEAD];
__device__ __align__(1024) float2 g_KVP[NH * 16 * 480];
__device__ __align__(1024) uint32_t g_KVB[NH * 480];
__device__ __align__(1024) float4 g_KMAX[8 * 16];
__device__ __align__(1024) float2 g_GATE[SEQ];
__device__ __align__(1024) uint8_t g_OAB[16 * 2 * 160 * 1024];
__device__ __align__(1024) uint8_t g_WOI[4 * 409600];
__device__ __align__(1024) uint32_t g_CNT[82 * 8];
constexpr int C_START = 0, C_WO = 1, C_KV = 2, C_KVP = 10, C_KVB = 18, C_GATE = 26, C_OA = 42, C_OB = 58, C_KM = 74;

#define SPIN_LIMIT (1ll << 29)
#define SPIN_FAIL(code) __trap()
#define PROF(cond, slot)
__device__ __forceinline__ uint32_t smem_u32(const void* p) { return (uint32_t)__cvta_generic_to_shared(p); }
__device__ __forceinline__ void mbar_init(uint32_t a, uint32_t c) { asm volatile("mbarrier.init.shared::cta.b64 [%0], %1;" ::"r"(a), "r"(c) : "memory"); }
__device__ __forceinline__ void mbar_expect(uint32_t a, uint32_t b) { asm volatile("mbarrier.arrive.expect_tx.shared::cta.b64 _, [%0], %1;" ::"r"(a), "r"(b) : "memory"); }
__device__ __forceinline__ void mbar_arrive(uint32_t a) { asm volatile("mbarrier.arrive.shared::cta.b64 _, [%0];" ::"r"(a) : "memory"); }
__device__ __forceinline__ uint32_t mbar_try(uint32_t a, uint32_t ph) {
  uint32_t ok;
  asm volatile("{\n.reg .pred p;\nmbarrier.try_wait.parity.shared::cta.b64 p, [%1], %2;\nselp.u32 %0, 1, 0, p;\n}\n" : "=r"(ok) : "r"(a), "r"(ph) : "memory");
  return ok;
}
__device__ __forceinline__ void mbar_wait(uint32_t a, uint32_t ph) {
  if (mbar_try(a, ph)) return;
  const long long t0 = clock64();
  while (!mbar_try(a, ph))
    if (clock64() - t0 > SPIN_LIMIT) { SPIN_FAIL(1000 + (a & 0x1FF) * 2 + ph); break; }
}
__device__ __forceinline__ void mbar_wait_u(uint32_t a, uint32_t ph) {
#pragma unroll 1
  for (int n = 0; n < (1 << 18); n++)
    if (__all_sync(~0u, mbar_try(a, ph))) break;
}
__device__ __forceinline__ uint32_t mbar_test(uint32_t a, uint32_t ph) {
  uint32_t ok;
  asm volatile("{\n.reg .pred p;\nmbarrier.test_wait.parity.shared::cta.b64 p, [%1], %2;\nselp.u32 %0, 1, 0, p;\n}\n" : "=r"(ok) : "r"(a), "r"(ph) : "memory");
  return ok;
}
__device__ __forceinline__ void mbar_arrive_if(uint32_t a, uint32_t flag) {
  asm volatile("{\n.reg .pred p;\nsetp.ne.u32 p, %1, 0;\n@p mbarrier.arrive.shared::cta.b64 _, [%0];\n}\n" ::"r"(a), "r"(flag) : "memory");
}
__device__ __forceinline__ void cnt_add_done(int slot) { asm volatile("red.relaxed.gpu.global.add.u32 [%0], 1;" ::"l"(g_CNT + slot * 8) : "memory"); }
__device__ __forceinline__ void cnt_add(int slot) {
  asm volatile("fence.acq_rel.gpu;" ::: "memory");
  cnt_add_done(slot);
}
__device__ __forceinline__ void cnt_wait(int slot, uint32_t target) {
  uint32_t v;
  long long t0 = 0;
  for (;;) {
    asm volatile("ld.relaxed.gpu.global.u32 %0, [%1];" : "=r"(v) : "l"(g_CNT + slot * 8) : "memory");
    if ((int32_t)(v - target) >= 0) break;
    __nanosleep(POLLNS);
    if (!t0) t0 = clock64();
    else if (clock64() - t0 > SPIN_LIMIT) { SPIN_FAIL(slot); break; }
  }
  asm volatile("ld.acquire.gpu.global.u32 %0, [%1];" : "=r"(v) : "l"(g_CNT + slot * 8) : "memory");
}
__device__ __forceinline__ void bulk_commit_wait() { asm volatile("cp.async.bulk.commit_group;\ncp.async.bulk.wait_group 0;" ::: "memory"); }
__device__ __forceinline__ void tma5_pair(uint32_t dst, const CUtensorMap* m, int c0, int c4, uint32_t bar) {
  asm volatile("cp.async.bulk.tensor.5d.shared::cluster.global.mbarrier::complete_tx::bytes.multicast::cluster [%0], [%1, {%3,%5,%5,%5,%4}], [%2], %6;"
               ::"r"(dst), "l"(m), "r"(bar), "r"(c0), "r"(c4), "r"(0), "h"((uint16_t)3) : "memory");
}
__device__ __forceinline__ void mbar_arrive_pair(uint32_t a, uint32_t flag) {
  asm volatile("{\n.reg .pred p;\n.reg .b32 r0, r1;\nsetp.ne.u32 p, %1, 0;\nmapa.shared::cluster.u32 r0, %0, 0;\nmapa.shared::cluster.u32 r1, %0, 1;\n"
               "@p mbarrier.arrive.relaxed.cluster.shared::cluster.b64 _, [r0];\n@p mbarrier.arrive.relaxed.cluster.shared::cluster.b64 _, [r1];\n}\n" ::"r"(a), "r"(flag) : "memory");
}
__device__ __forceinline__ void bulk_g2s(uint32_t dst, const void* src, uint32_t bytes, uint32_t bar) {
  asm volatile("cp.async.bulk.shared::cluster.global.mbarrier::complete_tx::bytes [%0], [%1], %2, [%3];" ::"r"(dst), "l"(src), "r"(bytes), "r"(bar) : "memory");
}
__device__ __forceinline__ void fence_async_smem() { asm volatile("fence.proxy.async.shared::cta;" ::: "memory"); }
__device__ __forceinline__ void bar_sync(int id, int n) { asm volatile("bar.sync %0, %1;" ::"r"(id), "r"(n) : "memory"); }
__device__ __forceinline__ void bar_arrive(int id, int n) { asm volatile("bar.arrive %0, %1;" ::"r"(id), "r"(n) : "memory"); }
__device__ __forceinline__ void wg_fence() { asm volatile("wgmma.fence.sync.aligned;" ::: "memory"); }
__device__ __forceinline__ void wg_commit() { asm volatile("wgmma.commit_group.sync.aligned;" ::: "memory"); }
template <int N> __device__ __forceinline__ void wg_wait() { asm volatile("wgmma.wait_group.sync.aligned %0;" ::"n"(N) : "memory"); }
template <int N> __device__ __forceinline__ void reg_inc() { asm volatile("setmaxnreg.inc.sync.aligned.u32 %0;" ::"n"(N)); }
template <int N> __device__ __forceinline__ void reg_dec() { asm volatile("setmaxnreg.dec.sync.aligned.u32 %0;" ::"n"(N)); }
template <int N> __device__ __forceinline__ void pin(float (&r)[N]) {
#pragma unroll
  for (int i = 0; i < N; i++) asm volatile("" : "+f"(r[i])::"memory");
}
template <int N> __device__ __forceinline__ void pin(uint32_t (&r)[N]) {
#pragma unroll
  for (int i = 0; i < N; i++) asm volatile("" : "+r"(r[i])::"memory");
}
__device__ __forceinline__ uint64_t mkdesc(uint32_t addr, uint32_t lbo, uint32_t sbo, uint32_t swz) {
  return (uint64_t)((addr & 0x3FFFF) >> 4) | ((uint64_t)(lbo >> 4) << 16) | ((uint64_t)(sbo >> 4) << 32) | ((uint64_t)swz << 62);
}
__device__ __forceinline__ float ex2(float x) { float y; asm("ex2.approx.ftz.f32 %0, %1;" : "=f"(y) : "f"(x)); return y; }
__device__ __forceinline__ float rcp(float x) { float y; asm("rcp.approx.ftz.f32 %0, %1;" : "=f"(y) : "f"(x)); return y; }
__device__ __forceinline__ float sqrt_ap(float x) { float y; asm("sqrt.approx.f32 %0, %1;" : "=f"(y) : "f"(x)); return y; }
__device__ __forceinline__ uint32_t packbf(float lo, float hi) { uint32_t d; asm("cvt.rn.bf16x2.f32 %0, %1, %2;" : "=r"(d) : "f"(hi), "f"(lo)); return d; }
__device__ __forceinline__ float bf_lo(uint32_t v) { return __uint_as_float(v << 16); }
__device__ __forceinline__ float bf_hi(uint32_t v) { return __uint_as_float(v & 0xFFFF0000u); }
__device__ __forceinline__ float bf_round(float x) { return bf_lo(packbf(x, 0.f)); }
__device__ __forceinline__ uint4 ldg_cg4(const void* p) { uint4 v; asm volatile("ld.global.cg.v4.b32 {%0,%1,%2,%3}, [%4];" : "=r"(v.x), "=r"(v.y), "=r"(v.z), "=r"(v.w) : "l"(p) : "memory"); return v; }
__device__ __forceinline__ void sts32(uint32_t a, uint32_t v) { asm volatile("st.shared.b32 [%0], %1;" ::"r"(a), "r"(v) : "memory"); }
__device__ __forceinline__ void stsm4(uint32_t a, uint32_t r0, uint32_t r1, uint32_t r2, uint32_t r3) {
  asm volatile("stmatrix.sync.aligned.m8n8.x4.shared.b16 [%0], {%1,%2,%3,%4};" ::"r"(a), "r"(r0), "r"(r1), "r"(r2), "r"(r3) : "memory");
}

__device__ __forceinline__ void stsm2(uint32_t a, uint32_t r0, uint32_t r1) {
  asm volatile("stmatrix.sync.aligned.m8n8.x2.shared.b16 [%0], {%1,%2};" ::"r"(a), "r"(r0), "r"(r1) : "memory");
}
__device__ __forceinline__ uint4 ldg_x(const void* p) {
  uint4 v;
  asm volatile("ld.global.nc.L1::no_allocate.L2::128B.v4.b32 {%0,%1,%2,%3}, [%4];" : "=r"(v.x), "=r"(v.y), "=r"(v.z), "=r"(v.w) : "l"(p));
  return v;
}
__device__ __forceinline__ float2 lds_f2(uint32_t a) { float2 v; asm volatile("ld.shared.v2.f32 {%0,%1}, [%2];" : "=f"(v.x), "=f"(v.y) : "r"(a) : "memory"); return v; }
__device__ __forceinline__ void bulk_s2g(void* dst, uint32_t src, uint32_t bytes) {
  asm volatile("cp.async.bulk.global.shared::cta.bulk_group [%0], [%1], %2;" ::"l"(dst), "r"(src), "r"(bytes) : "memory");
}

__device__ __forceinline__ void mma_n24_ss_tb(float (&d)[12], uint64_t adesc, uint64_t bdesc, int acc) {
  asm volatile("{\n.reg .pred p;\nsetp.ne.b32 p, %14, 0;\n"
      "wgmma.mma_async.sync.aligned.m64n24k16.f32.bf16.bf16 "
      "{%0,%1,%2,%3,%4,%5,%6,%7,%8,%9,%10,%11}, "
      "%12, %13, p, 1, 1, 0, 1;\n}\n"
      : "+f"(d[0]), "+f"(d[1]), "+f"(d[2]), "+f"(d[3]), "+f"(d[4]), "+f"(d[5]), "+f"(d[6]), "+f"(d[7]),
        "+f"(d[8]), "+f"(d[9]), "+f"(d[10]), "+f"(d[11])
      : "l"(adesc), "l"(bdesc), "r"(acc));
}
__device__ __forceinline__ void mma_n192_rs_tb(float (&d)[96], uint32_t a0, uint32_t a1, uint32_t a2, uint32_t a3, uint64_t bdesc, int acc) {
  asm volatile("{\n.reg .pred p;\nsetp.ne.b32 p, %101, 0;\n"
      "wgmma.mma_async.sync.aligned.m64n192k16.f32.bf16.bf16 "
      "{%0,%1,%2,%3,%4,%5,%6,%7,%8,%9,%10,%11,%12,%13,%14,%15,"
      "%16,%17,%18,%19,%20,%21,%22,%23,%24,%25,%26,%27,%28,%29,%30,%31,"
      "%32,%33,%34,%35,%36,%37,%38,%39,%40,%41,%42,%43,%44,%45,%46,%47,"
      "%48,%49,%50,%51,%52,%53,%54,%55,%56,%57,%58,%59,%60,%61,%62,%63,"
      "%64,%65,%66,%67,%68,%69,%70,%71,%72,%73,%74,%75,%76,%77,%78,%79,"
      "%80,%81,%82,%83,%84,%85,%86,%87,%88,%89,%90,%91,%92,%93,%94,%95}, "
      "{%96,%97,%98,%99}, %100, p, 1, 1, 1;\n}\n"
      : "+f"(d[0]), "+f"(d[1]), "+f"(d[2]), "+f"(d[3]), "+f"(d[4]), "+f"(d[5]), "+f"(d[6]), "+f"(d[7]),
        "+f"(d[8]), "+f"(d[9]), "+f"(d[10]), "+f"(d[11]), "+f"(d[12]), "+f"(d[13]), "+f"(d[14]), "+f"(d[15]),
        "+f"(d[16]), "+f"(d[17]), "+f"(d[18]), "+f"(d[19]), "+f"(d[20]), "+f"(d[21]), "+f"(d[22]), "+f"(d[23]),
        "+f"(d[24]), "+f"(d[25]), "+f"(d[26]), "+f"(d[27]), "+f"(d[28]), "+f"(d[29]), "+f"(d[30]), "+f"(d[31]),
        "+f"(d[32]), "+f"(d[33]), "+f"(d[34]), "+f"(d[35]), "+f"(d[36]), "+f"(d[37]), "+f"(d[38]), "+f"(d[39]),
        "+f"(d[40]), "+f"(d[41]), "+f"(d[42]), "+f"(d[43]), "+f"(d[44]), "+f"(d[45]), "+f"(d[46]), "+f"(d[47]),
        "+f"(d[48]), "+f"(d[49]), "+f"(d[50]), "+f"(d[51]), "+f"(d[52]), "+f"(d[53]), "+f"(d[54]), "+f"(d[55]),
        "+f"(d[56]), "+f"(d[57]), "+f"(d[58]), "+f"(d[59]), "+f"(d[60]), "+f"(d[61]), "+f"(d[62]), "+f"(d[63]),
        "+f"(d[64]), "+f"(d[65]), "+f"(d[66]), "+f"(d[67]), "+f"(d[68]), "+f"(d[69]), "+f"(d[70]), "+f"(d[71]),
        "+f"(d[72]), "+f"(d[73]), "+f"(d[74]), "+f"(d[75]), "+f"(d[76]), "+f"(d[77]), "+f"(d[78]), "+f"(d[79]),
        "+f"(d[80]), "+f"(d[81]), "+f"(d[82]), "+f"(d[83]), "+f"(d[84]), "+f"(d[85]), "+f"(d[86]), "+f"(d[87]),
        "+f"(d[88]), "+f"(d[89]), "+f"(d[90]), "+f"(d[91]), "+f"(d[92]), "+f"(d[93]), "+f"(d[94]), "+f"(d[95])
      : "r"(a0), "r"(a1), "r"(a2), "r"(a3), "l"(bdesc), "r"(acc));
}
__device__ __forceinline__ void mma_n128_rs_tb(float (&d)[64], uint32_t a0, uint32_t a1, uint32_t a2, uint32_t a3, uint64_t bdesc, int acc) {
  asm volatile("{\n.reg .pred p;\nsetp.ne.b32 p, %69, 0;\n"
      "wgmma.mma_async.sync.aligned.m64n128k16.f32.bf16.bf16 "
      "{%0,%1,%2,%3,%4,%5,%6,%7,%8,%9,%10,%11,%12,%13,%14,%15,"
      "%16,%17,%18,%19,%20,%21,%22,%23,%24,%25,%26,%27,%28,%29,%30,%31,"
      "%32,%33,%34,%35,%36,%37,%38,%39,%40,%41,%42,%43,%44,%45,%46,%47,"
      "%48,%49,%50,%51,%52,%53,%54,%55,%56,%57,%58,%59,%60,%61,%62,%63}, "
      "{%64,%65,%66,%67}, %68, p, 1, 1, 1;\n}\n"
      : "+f"(d[0]), "+f"(d[1]), "+f"(d[2]), "+f"(d[3]), "+f"(d[4]), "+f"(d[5]), "+f"(d[6]), "+f"(d[7]),
        "+f"(d[8]), "+f"(d[9]), "+f"(d[10]), "+f"(d[11]), "+f"(d[12]), "+f"(d[13]), "+f"(d[14]), "+f"(d[15]),
        "+f"(d[16]), "+f"(d[17]), "+f"(d[18]), "+f"(d[19]), "+f"(d[20]), "+f"(d[21]), "+f"(d[22]), "+f"(d[23]),
        "+f"(d[24]), "+f"(d[25]), "+f"(d[26]), "+f"(d[27]), "+f"(d[28]), "+f"(d[29]), "+f"(d[30]), "+f"(d[31]),
        "+f"(d[32]), "+f"(d[33]), "+f"(d[34]), "+f"(d[35]), "+f"(d[36]), "+f"(d[37]), "+f"(d[38]), "+f"(d[39]),
        "+f"(d[40]), "+f"(d[41]), "+f"(d[42]), "+f"(d[43]), "+f"(d[44]), "+f"(d[45]), "+f"(d[46]), "+f"(d[47]),
        "+f"(d[48]), "+f"(d[49]), "+f"(d[50]), "+f"(d[51]), "+f"(d[52]), "+f"(d[53]), "+f"(d[54]), "+f"(d[55]),
        "+f"(d[56]), "+f"(d[57]), "+f"(d[58]), "+f"(d[59]), "+f"(d[60]), "+f"(d[61]), "+f"(d[62]), "+f"(d[63])
      : "r"(a0), "r"(a1), "r"(a2), "r"(a3), "l"(bdesc), "r"(acc));
}
__device__ __forceinline__ void mma_n64_rs_tb(float (&d)[32], uint32_t a0, uint32_t a1, uint32_t a2, uint32_t a3, uint64_t bdesc, int acc) {
  asm volatile("{\n.reg .pred p;\nsetp.ne.b32 p, %37, 0;\n"
      "wgmma.mma_async.sync.aligned.m64n64k16.f32.bf16.bf16 "
      "{%0,%1,%2,%3,%4,%5,%6,%7,%8,%9,%10,%11,%12,%13,%14,%15,"
      "%16,%17,%18,%19,%20,%21,%22,%23,%24,%25,%26,%27,%28,%29,%30,%31}, "
      "{%32,%33,%34,%35}, %36, p, 1, 1, 1;\n}\n"
      : "+f"(d[0]), "+f"(d[1]), "+f"(d[2]), "+f"(d[3]), "+f"(d[4]), "+f"(d[5]), "+f"(d[6]), "+f"(d[7]),
        "+f"(d[8]), "+f"(d[9]), "+f"(d[10]), "+f"(d[11]), "+f"(d[12]), "+f"(d[13]), "+f"(d[14]), "+f"(d[15]),
        "+f"(d[16]), "+f"(d[17]), "+f"(d[18]), "+f"(d[19]), "+f"(d[20]), "+f"(d[21]), "+f"(d[22]), "+f"(d[23]),
        "+f"(d[24]), "+f"(d[25]), "+f"(d[26]), "+f"(d[27]), "+f"(d[28]), "+f"(d[29]), "+f"(d[30]), "+f"(d[31])
      : "r"(a0), "r"(a1), "r"(a2), "r"(a3), "l"(bdesc), "r"(acc));
}
__device__ __forceinline__ void mma_n48_rs_tb(float (&d)[24], uint32_t a0, uint32_t a1, uint32_t a2, uint32_t a3, uint64_t bdesc, int acc) {
  asm volatile("{\n.reg .pred p;\nsetp.ne.b32 p, %29, 0;\n"
      "wgmma.mma_async.sync.aligned.m64n48k16.f32.bf16.bf16 "
      "{%0,%1,%2,%3,%4,%5,%6,%7,%8,%9,%10,%11,%12,%13,%14,%15,"
      "%16,%17,%18,%19,%20,%21,%22,%23}, "
      "{%24,%25,%26,%27}, %28, p, 1, 1, 1;\n}\n"
      : "+f"(d[0]), "+f"(d[1]), "+f"(d[2]), "+f"(d[3]), "+f"(d[4]), "+f"(d[5]), "+f"(d[6]), "+f"(d[7]),
        "+f"(d[8]), "+f"(d[9]), "+f"(d[10]), "+f"(d[11]), "+f"(d[12]), "+f"(d[13]), "+f"(d[14]), "+f"(d[15]),
        "+f"(d[16]), "+f"(d[17]), "+f"(d[18]), "+f"(d[19]), "+f"(d[20]), "+f"(d[21]), "+f"(d[22]), "+f"(d[23])
      : "r"(a0), "r"(a1), "r"(a2), "r"(a3), "l"(bdesc), "r"(acc));
}
__device__ __forceinline__ void mma_n128_rs(float (&d)[64], uint32_t a0, uint32_t a1, uint32_t a2, uint32_t a3, uint64_t bdesc, int acc) {
  asm volatile("{\n.reg .pred p;\nsetp.ne.b32 p, %69, 0;\n"
      "wgmma.mma_async.sync.aligned.m64n128k16.f32.bf16.bf16 "
      "{%0,%1,%2,%3,%4,%5,%6,%7,%8,%9,%10,%11,%12,%13,%14,%15,"
      "%16,%17,%18,%19,%20,%21,%22,%23,%24,%25,%26,%27,%28,%29,%30,%31,"
      "%32,%33,%34,%35,%36,%37,%38,%39,%40,%41,%42,%43,%44,%45,%46,%47,"
      "%48,%49,%50,%51,%52,%53,%54,%55,%56,%57,%58,%59,%60,%61,%62,%63}, "
      "{%64,%65,%66,%67}, %68, p, 1, 1, 0;\n}\n"
      : "+f"(d[0]), "+f"(d[1]), "+f"(d[2]), "+f"(d[3]), "+f"(d[4]), "+f"(d[5]), "+f"(d[6]), "+f"(d[7]),
        "+f"(d[8]), "+f"(d[9]), "+f"(d[10]), "+f"(d[11]), "+f"(d[12]), "+f"(d[13]), "+f"(d[14]), "+f"(d[15]),
        "+f"(d[16]), "+f"(d[17]), "+f"(d[18]), "+f"(d[19]), "+f"(d[20]), "+f"(d[21]), "+f"(d[22]), "+f"(d[23]),
        "+f"(d[24]), "+f"(d[25]), "+f"(d[26]), "+f"(d[27]), "+f"(d[28]), "+f"(d[29]), "+f"(d[30]), "+f"(d[31]),
        "+f"(d[32]), "+f"(d[33]), "+f"(d[34]), "+f"(d[35]), "+f"(d[36]), "+f"(d[37]), "+f"(d[38]), "+f"(d[39]),
        "+f"(d[40]), "+f"(d[41]), "+f"(d[42]), "+f"(d[43]), "+f"(d[44]), "+f"(d[45]), "+f"(d[46]), "+f"(d[47]),
        "+f"(d[48]), "+f"(d[49]), "+f"(d[50]), "+f"(d[51]), "+f"(d[52]), "+f"(d[53]), "+f"(d[54]), "+f"(d[55]),
        "+f"(d[56]), "+f"(d[57]), "+f"(d[58]), "+f"(d[59]), "+f"(d[60]), "+f"(d[61]), "+f"(d[62]), "+f"(d[63])
      : "r"(a0), "r"(a1), "r"(a2), "r"(a3), "l"(bdesc), "r"(acc));
}
__device__ __forceinline__ void mma_n64_rs(float (&d)[32], uint32_t a0, uint32_t a1, uint32_t a2, uint32_t a3, uint64_t bdesc, int acc) {
  asm volatile("{\n.reg .pred p;\nsetp.ne.b32 p, %37, 0;\n"
      "wgmma.mma_async.sync.aligned.m64n64k16.f32.bf16.bf16 "
      "{%0,%1,%2,%3,%4,%5,%6,%7,%8,%9,%10,%11,%12,%13,%14,%15,"
      "%16,%17,%18,%19,%20,%21,%22,%23,%24,%25,%26,%27,%28,%29,%30,%31}, "
      "{%32,%33,%34,%35}, %36, p, 1, 1, 0;\n}\n"
      : "+f"(d[0]), "+f"(d[1]), "+f"(d[2]), "+f"(d[3]), "+f"(d[4]), "+f"(d[5]), "+f"(d[6]), "+f"(d[7]),
        "+f"(d[8]), "+f"(d[9]), "+f"(d[10]), "+f"(d[11]), "+f"(d[12]), "+f"(d[13]), "+f"(d[14]), "+f"(d[15]),
        "+f"(d[16]), "+f"(d[17]), "+f"(d[18]), "+f"(d[19]), "+f"(d[20]), "+f"(d[21]), "+f"(d[22]), "+f"(d[23]),
        "+f"(d[24]), "+f"(d[25]), "+f"(d[26]), "+f"(d[27]), "+f"(d[28]), "+f"(d[29]), "+f"(d[30]), "+f"(d[31])
      : "r"(a0), "r"(a1), "r"(a2), "r"(a3), "l"(bdesc), "r"(acc));
}
__device__ __forceinline__ void mma_n128_ss(float (&d)[64], uint64_t adesc, uint64_t bdesc, int acc) {
  asm volatile("{\n.reg .pred p;\nsetp.ne.b32 p, %66, 0;\n"
      "wgmma.mma_async.sync.aligned.m64n128k16.f32.bf16.bf16 "
      "{%0,%1,%2,%3,%4,%5,%6,%7,%8,%9,%10,%11,%12,%13,%14,%15,"
      "%16,%17,%18,%19,%20,%21,%22,%23,%24,%25,%26,%27,%28,%29,%30,%31,"
      "%32,%33,%34,%35,%36,%37,%38,%39,%40,%41,%42,%43,%44,%45,%46,%47,"
      "%48,%49,%50,%51,%52,%53,%54,%55,%56,%57,%58,%59,%60,%61,%62,%63}, "
      "%64, %65, p, 1, 1, 0, 0;\n}\n"
      : "+f"(d[0]), "+f"(d[1]), "+f"(d[2]), "+f"(d[3]), "+f"(d[4]), "+f"(d[5]), "+f"(d[6]), "+f"(d[7]),
        "+f"(d[8]), "+f"(d[9]), "+f"(d[10]), "+f"(d[11]), "+f"(d[12]), "+f"(d[13]), "+f"(d[14]), "+f"(d[15]),
        "+f"(d[16]), "+f"(d[17]), "+f"(d[18]), "+f"(d[19]), "+f"(d[20]), "+f"(d[21]), "+f"(d[22]), "+f"(d[23]),
        "+f"(d[24]), "+f"(d[25]), "+f"(d[26]), "+f"(d[27]), "+f"(d[28]), "+f"(d[29]), "+f"(d[30]), "+f"(d[31]),
        "+f"(d[32]), "+f"(d[33]), "+f"(d[34]), "+f"(d[35]), "+f"(d[36]), "+f"(d[37]), "+f"(d[38]), "+f"(d[39]),
        "+f"(d[40]), "+f"(d[41]), "+f"(d[42]), "+f"(d[43]), "+f"(d[44]), "+f"(d[45]), "+f"(d[46]), "+f"(d[47]),
        "+f"(d[48]), "+f"(d[49]), "+f"(d[50]), "+f"(d[51]), "+f"(d[52]), "+f"(d[53]), "+f"(d[54]), "+f"(d[55]),
        "+f"(d[56]), "+f"(d[57]), "+f"(d[58]), "+f"(d[59]), "+f"(d[60]), "+f"(d[61]), "+f"(d[62]), "+f"(d[63])
      : "l"(adesc), "l"(bdesc), "r"(acc));
}
__device__ __forceinline__ void mma_n160_ss_tb(float (&d)[80], uint64_t adesc, uint64_t bdesc, int acc) {
  asm volatile("{\n.reg .pred p;\nsetp.ne.b32 p, %82, 0;\n"
      "wgmma.mma_async.sync.aligned.m64n160k16.f32.bf16.bf16 "
      "{%0,%1,%2,%3,%4,%5,%6,%7,%8,%9,%10,%11,%12,%13,%14,%15,"
      "%16,%17,%18,%19,%20,%21,%22,%23,%24,%25,%26,%27,%28,%29,%30,%31,"
      "%32,%33,%34,%35,%36,%37,%38,%39,%40,%41,%42,%43,%44,%45,%46,%47,"
      "%48,%49,%50,%51,%52,%53,%54,%55,%56,%57,%58,%59,%60,%61,%62,%63,"
      "%64,%65,%66,%67,%68,%69,%70,%71,%72,%73,%74,%75,%76,%77,%78,%79}, "
      "%80, %81, p, 1, 1, 0, 1;\n}\n"
      : "+f"(d[0]), "+f"(d[1]), "+f"(d[2]), "+f"(d[3]), "+f"(d[4]), "+f"(d[5]), "+f"(d[6]), "+f"(d[7]),
        "+f"(d[8]), "+f"(d[9]), "+f"(d[10]), "+f"(d[11]), "+f"(d[12]), "+f"(d[13]), "+f"(d[14]), "+f"(d[15]),
        "+f"(d[16]), "+f"(d[17]), "+f"(d[18]), "+f"(d[19]), "+f"(d[20]), "+f"(d[21]), "+f"(d[22]), "+f"(d[23]),
        "+f"(d[24]), "+f"(d[25]), "+f"(d[26]), "+f"(d[27]), "+f"(d[28]), "+f"(d[29]), "+f"(d[30]), "+f"(d[31]),
        "+f"(d[32]), "+f"(d[33]), "+f"(d[34]), "+f"(d[35]), "+f"(d[36]), "+f"(d[37]), "+f"(d[38]), "+f"(d[39]),
        "+f"(d[40]), "+f"(d[41]), "+f"(d[42]), "+f"(d[43]), "+f"(d[44]), "+f"(d[45]), "+f"(d[46]), "+f"(d[47]),
        "+f"(d[48]), "+f"(d[49]), "+f"(d[50]), "+f"(d[51]), "+f"(d[52]), "+f"(d[53]), "+f"(d[54]), "+f"(d[55]),
        "+f"(d[56]), "+f"(d[57]), "+f"(d[58]), "+f"(d[59]), "+f"(d[60]), "+f"(d[61]), "+f"(d[62]), "+f"(d[63]),
        "+f"(d[64]), "+f"(d[65]), "+f"(d[66]), "+f"(d[67]), "+f"(d[68]), "+f"(d[69]), "+f"(d[70]), "+f"(d[71]),
        "+f"(d[72]), "+f"(d[73]), "+f"(d[74]), "+f"(d[75]), "+f"(d[76]), "+f"(d[77]), "+f"(d[78]), "+f"(d[79])
      : "l"(adesc), "l"(bdesc), "r"(acc));
}
__device__ __forceinline__ void mma_n80_rs_tb(float (&d)[40], uint32_t a0, uint32_t a1, uint32_t a2, uint32_t a3, uint64_t bdesc, int acc) {
  asm volatile("{\n.reg .pred p;\nsetp.ne.b32 p, %45, 0;\n"
      "wgmma.mma_async.sync.aligned.m64n80k16.f32.bf16.bf16 "
      "{%0,%1,%2,%3,%4,%5,%6,%7,%8,%9,%10,%11,%12,%13,%14,%15,"
      "%16,%17,%18,%19,%20,%21,%22,%23,%24,%25,%26,%27,%28,%29,%30,%31,"
      "%32,%33,%34,%35,%36,%37,%38,%39}, "
      "{%40,%41,%42,%43}, %44, p, 1, 1, 1;\n}\n"
      : "+f"(d[0]), "+f"(d[1]), "+f"(d[2]), "+f"(d[3]), "+f"(d[4]), "+f"(d[5]), "+f"(d[6]), "+f"(d[7]),
        "+f"(d[8]), "+f"(d[9]), "+f"(d[10]), "+f"(d[11]), "+f"(d[12]), "+f"(d[13]), "+f"(d[14]), "+f"(d[15]),
        "+f"(d[16]), "+f"(d[17]), "+f"(d[18]), "+f"(d[19]), "+f"(d[20]), "+f"(d[21]), "+f"(d[22]), "+f"(d[23]),
        "+f"(d[24]), "+f"(d[25]), "+f"(d[26]), "+f"(d[27]), "+f"(d[28]), "+f"(d[29]), "+f"(d[30]), "+f"(d[31]),
        "+f"(d[32]), "+f"(d[33]), "+f"(d[34]), "+f"(d[35]), "+f"(d[36]), "+f"(d[37]), "+f"(d[38]), "+f"(d[39])
      : "r"(a0), "r"(a1), "r"(a2), "r"(a3), "l"(bdesc), "r"(acc));
}
__device__ __forceinline__ void mma_n24_rs_tb(float (&d)[12], uint32_t a0, uint32_t a1, uint32_t a2, uint32_t a3, uint64_t bdesc, int acc) {
  asm volatile("{\n.reg .pred p;\nsetp.ne.b32 p, %17, 0;\n"
      "wgmma.mma_async.sync.aligned.m64n24k16.f32.bf16.bf16 "
      "{%0,%1,%2,%3,%4,%5,%6,%7,%8,%9,%10,%11}, "
      "{%12,%13,%14,%15}, %16, p, 1, 1, 1;\n}\n"
      : "+f"(d[0]), "+f"(d[1]), "+f"(d[2]), "+f"(d[3]), "+f"(d[4]), "+f"(d[5]), "+f"(d[6]), "+f"(d[7]),
        "+f"(d[8]), "+f"(d[9]), "+f"(d[10]), "+f"(d[11])
      : "r"(a0), "r"(a1), "r"(a2), "r"(a3), "l"(bdesc), "r"(acc));
}
__device__ __forceinline__ void mma_n24_ss_tatb(float (&d)[12], uint64_t adesc, uint64_t bdesc, int acc) {
  asm volatile("{\n.reg .pred p;\nsetp.ne.b32 p, %14, 0;\n"
      "wgmma.mma_async.sync.aligned.m64n24k16.f32.bf16.bf16 "
      "{%0,%1,%2,%3,%4,%5,%6,%7,%8,%9,%10,%11}, "
      "%12, %13, p, 1, 1, 1, 1;\n}\n"
      : "+f"(d[0]), "+f"(d[1]), "+f"(d[2]), "+f"(d[3]), "+f"(d[4]), "+f"(d[5]), "+f"(d[6]), "+f"(d[7]),
        "+f"(d[8]), "+f"(d[9]), "+f"(d[10]), "+f"(d[11])
      : "l"(adesc), "l"(bdesc), "r"(acc));
}

constexpr int W_STAGE = 30720, W_NST = 5;
constexpr int KV_CHUNK = 24576;
constexpr int O_STAGE = 36864;
constexpr int OFF_AK = 3 * KV_CHUNK;
constexpr int OFF_PHK = 4 * KV_CHUNK;
constexpr int OFF_GATE = 112640;
constexpr int OFF_Q = W_NST * W_STAGE;
constexpr int OFF_V = OFF_Q + 24576;
constexpr int OFF_AQ = OFF_V + 24576;
constexpr int OFF_WPH = OFF_AQ + 24576;
constexpr int OFF_BAR = OFF_WPH + 4608;
constexpr int B_WF = 0, B_WE = 40, B_KF = 80, B_KE = 112, B_OF = 208, B_OE = 248, B_RF = 288, B_Z = 296, B_G = 304, B_X = 312;
constexpr int OFF_MISC = OFF_BAR + 320;
constexpr int SMEM_BYTES = OFF_MISC + 32 + 128;
__device__ __forceinline__ uint32_t o_stage(int s) { return s == 0 ? OFF_V : s == 1 ? OFF_Q - O_STAGE : (s - 2) * O_STAGE; }
constexpr int NB_STAGED = 1, NB_FREE = 2, NB_WG = 3, NB_BG = 7, NB_EPI = 15, NB_PHIK = 8, NB_TAIL = 9, NB_READ = 10, NB_LAST = 11, NB_HELP = 12;

template <int SEC, int J, int HF>
__device__ __forceinline__ float2 grp(const float (&a1)[2][64], const float (&a2)[24]) {
  constexpr int S = SEC & 3, J1 = (SEC & 4) ? J - 2 : J, J2 = (SEC & 4) ? J : J - 8;
  if constexpr (J1 >= 0 && J1 < 8) return make_float2(a1[S >> 1][(8 * (S & 1) + J1) * 4 + 2 * HF], a1[S >> 1][(8 * (S & 1) + J1) * 4 + 2 * HF + 1]);
  else return make_float2(a2[(2 * S + J2) * 4 + 2 * HF], a2[(2 * S + J2) * 4 + 2 * HF + 1]);
}
__device__ __forceinline__ float sq2(float2 v) { return fmaf(v.x, v.x, v.y * v.y); }
__device__ __forceinline__ uint32_t pks(float2 v, float s) { return packbf(v.x * s, v.y * s); }

template <int SEC, int PR>
__device__ __forceinline__ void norms(const float (&a1)[2][64], const float (&a2)[24], int t, float (&n)[2][2]) {
  const float h0 = sq2(grp<SEC, 5 * PR + 2, 0>(a1, a2)), h1 = sq2(grp<SEC, 5 * PR + 2, 1>(a1, a2));
  n[0][0] = sq2(grp<SEC, 5 * PR, 0>(a1, a2)) + sq2(grp<SEC, 5 * PR + 1, 0>(a1, a2)) + (t < 2 ? h0 : 0.f);
  n[0][1] = sq2(grp<SEC, 5 * PR, 1>(a1, a2)) + sq2(grp<SEC, 5 * PR + 1, 1>(a1, a2)) + (t < 2 ? h1 : 0.f);
  n[1][0] = sq2(grp<SEC, 5 * PR + 3, 0>(a1, a2)) + sq2(grp<SEC, 5 * PR + 4, 0>(a1, a2)) + (t < 2 ? 0.f : h0);
  n[1][1] = sq2(grp<SEC, 5 * PR + 3, 1>(a1, a2)) + sq2(grp<SEC, 5 * PR + 4, 1>(a1, a2)) + (t < 2 ? 0.f : h1);
#pragma unroll
  for (int i = 0; i < 4; i++) n[i >> 1][i & 1] += __shfl_xor_sync(~0u, n[i >> 1][i & 1], 1);
#pragma unroll
  for (int i = 0; i < 4; i++) n[i >> 1][i & 1] += __shfl_xor_sync(~0u, n[i >> 1][i & 1], 2);
}

template <int SEC, int PR>
__device__ __forceinline__ void stage_pair(const float (&a1)[2][64], const float (&a2)[24], float sc0, float sc1, float sm, uint32_t xe0, uint32_t xe1,
                                           uint32_t xo0, uint32_t xo1, uint32_t ad01, uint32_t ad2, int t) {
  const uint32_t off = 2 * PR * 3072;
  stsm4(ad01 + off, pks(grp<SEC, 5 * PR, 0>(a1, a2), sc0), pks(grp<SEC, 5 * PR, 1>(a1, a2), sc1), pks(grp<SEC, 5 * PR + 1, 0>(a1, a2), sc0),
        pks(grp<SEC, 5 * PR + 1, 1>(a1, a2), sc1));
  stsm4(ad01 + off + 3072, pks(grp<SEC, 5 * PR + 3, 0>(a1, a2), sc0), pks(grp<SEC, 5 * PR + 3, 1>(a1, a2), sc1),
        pks(grp<SEC, 5 * PR + 4, 0>(a1, a2), sc0), pks(grp<SEC, 5 * PR + 4, 1>(a1, a2), sc1));
  const uint32_t m0 = pks(grp<SEC, 5 * PR + 2, 0>(a1, a2), sc0 * sm), m1 = pks(grp<SEC, 5 * PR + 2, 1>(a1, a2), sc1 * sm);
  const bool lo = t < 2;
  stsm4(ad2 + off, lo ? m0 : xe0, lo ? m1 : xe1, lo ? xo0 : m0, lo ? xo1 : m1);
}

template <bool EXACT>
__device__ __forceinline__ void hedgehog(const float (&p)[12], uint32_t (&f)[10], int t) {
  const bool lo = t < 2;
#pragma unroll
  for (int hf = 0; hf < 2; hf++) {
    const float v[6] = {p[2 * hf], p[2 * hf + 1], p[4 + 2 * hf], p[5 + 2 * hf], p[8 + 2 * hf], p[9 + 2 * hf]};
    float bp = 0.f, bn = 0.f;
    if (EXACT) {
      float mx = fmaxf(fmaxf(fmaxf(v[0], v[1]), fmaxf(v[2], v[3])), fmaxf(v[4], v[5]));
      float mn = fminf(fminf(fminf(v[0], v[1]), fminf(v[2], v[3])), fminf(v[4], v[5]));
      mx = fmaxf(mx, __shfl_xor_sync(~0u, mx, 1)); mn = fminf(mn, __shfl_xor_sync(~0u, mn, 1));
      mx = fmaxf(mx, __shfl_xor_sync(~0u, mx, 2)); mn = fminf(mn, __shfl_xor_sync(~0u, mn, 2));
      bp = -mx * LOG2E; bn = mn * LOG2E;
    }
    float ep[4], en[4];
#pragma unroll
    for (int i = 0; i < 4; i++) { ep[i] = ex2(fmaf(v[i], LOG2E, bp)); en[i] = ex2(fmaf(v[i], -LOG2E, bn)); }
    const float sg = lo ? LOG2E : -LOG2E, bm = lo ? bp : bn;
    const float m0 = ex2(fmaf(v[4], sg, bm)), m1 = ex2(fmaf(v[5], sg, bm)), ms = m0 + m1;
    float sp = (ep[0] + ep[1]) + (ep[2] + ep[3]) + (lo ? ms : 0.f);
    float sn = (en[0] + en[1]) + (en[2] + en[3]) + (lo ? 0.f : ms);
    sp += __shfl_xor_sync(~0u, sp, 1); sn += __shfl_xor_sync(~0u, sn, 1);
    sp += __shfl_xor_sync(~0u, sp, 2); sn += __shfl_xor_sync(~0u, sn, 2);
    const float r = rcp(sp * sn), rp = r * sn, rn = r * sp, rm = lo ? rp : rn;
    f[0 + hf] = packbf(ep[0] * rp, ep[1] * rp);
    f[2 + hf] = packbf(ep[2] * rp, ep[3] * rp);
    f[4 + hf] = packbf(m0 * rm, m1 * rm);
    f[6 + hf] = packbf(en[0] * rn, en[1] * rn);
    f[8 + hf] = packbf(en[2] * rn, en[3] * rn);
  }
}
__device__ __forceinline__ void hedgehog1(const float (&p)[12], uint32_t (&f)[10], int t) {
  float m[2] = {fabsf(p[0]), fabsf(p[6])};
#pragma unroll
  for (int i = 1; i < 6; i++) { m[0] = fmaxf(m[0], fabsf(p[i])); m[1] = fmaxf(m[1], fabsf(p[6 + i])); }
  if (__all_sync(~0u, fmaxf(m[0], m[1]) <= 27.f)) hedgehog<false>(p, f, t);
  else hedgehog<true>(p, f, t);
}

template <int O>
__device__ __forceinline__ void epilogue0(const float (&a1)[2][64], const float (&a2)[24], int rg, int lane, uint32_t ad01, uint32_t ad2, uint32_t kmx) {
  const int t = lane & 3;
  const bool p0 = (POLY_MASK >> rg) & 1, p1 = (POLY_MASK >> (rg + 1)) & 1;
  const uint32_t kp = (t & 1) ? 0u : (BF_ONE | (BF_MAGIC << 16)), km = (t & 1) ? BF_MU_LO : (BF_ONE | (BF_MU_HI << 16));
  const uint32_t vp = (t & 1) ? 0u : (BF_ONE | 0x8000u), vm = (t & 1) ? 0u : BF_ONE;
  const uint32_t k0 = p0 ? kp : km, k1 = p1 ? kp : km, v0 = p0 ? vp : vm, v1 = p1 ? vp : vm;
  const float s0 = p0 ? -1.f : 1.f, s1 = p1 ? -1.f : 1.f;
  stage_pair<O + 0, 0>(a1, a2, 1.f, 1.f, 1.f, k0, k1, k0, k1, ad01 + OFF_Q, ad2 + OFF_Q, t);
  stage_pair<O + 0, 1>(a1, a2, 1.f, 1.f, 1.f, k0, k1, k0, k1, ad01 + OFF_Q, ad2 + OFF_Q, t);
  stage_pair<O + 1, 0>(a1, a2, s0, s1, 1.f, v0, v1, v0, v1, ad01 + OFF_V, ad2 + OFF_V, t);
  stage_pair<O + 1, 1>(a1, a2, s0, s1, 1.f, v0, v1, v0, v1, ad01 + OFF_V, ad2 + OFF_V, t);
  stage_pair<O + 2, 0>(a1, a2, 1.f, 1.f, 0.5f, 0u, 0u, 0u, 0u, ad01 + OFF_AQ, ad2 + OFF_AQ, t);
  stage_pair<O + 2, 1>(a1, a2, 1.f, 1.f, 0.5f, 0u, 0u, 0u, 0u, ad01 + OFF_AQ, ad2 + OFF_AQ, t);
  float n0[2][2], n1[2][2];
  norms<O + 0, 0>(a1, a2, t, n0);
  norms<O + 0, 1>(a1, a2, t, n1);
  const uint32_t m0 = __reduce_max_sync(~0u, __float_as_uint(fmaxf(n0[0][0], n0[0][1])));
  const uint32_t m1 = __reduce_max_sync(~0u, __float_as_uint(fmaxf(n0[1][0], n0[1][1])));
  const uint32_t m2 = __reduce_max_sync(~0u, __float_as_uint(fmaxf(n1[0][0], n1[0][1])));
  const uint32_t m3 = __reduce_max_sync(~0u, __float_as_uint(fmaxf(n1[1][0], n1[1][1])));
  if (lane < 4) asm volatile("red.shared.max.u32 [%0], %1;" ::"r"(kmx + lane * 4), "r"(lane == 0 ? m0 : lane == 1 ? m1 : lane == 2 ? m2 : m3) : "memory");
}

template <int O>
__device__ __forceinline__ bool epilogue1a(const float (&a1)[2][64], const float (&a2)[24], uint32_t (&xq)[4][2], const uint8_t* smem, int wg, int t,
                                           uint32_t ad01, uint32_t ad2) {
  stage_pair<O + 0, 0>(a1, a2, 1.f, 1.f, 0.5f, 0u, 0u, 0u, 0u, ad01 + OFF_AK, ad2 + OFF_AK, t);
  stage_pair<O + 0, 1>(a1, a2, 1.f, 1.f, 0.5f, 0u, 0u, 0u, 0u, ad01 + OFF_AK, ad2 + OFF_AK, t);
  float n0[2][2], n1[2][2];
  norms<O + 2, 0>(a1, a2, t, n0);
  norms<O + 2, 1>(a1, a2, t, n1);
  const float4 km = *(const float4*)(smem + OFF_MISC);
  const float b[4][2] = {{sqrt_ap(n0[0][0]) * km.x, sqrt_ap(n0[0][1]) * km.x}, {sqrt_ap(n0[1][0]) * km.y, sqrt_ap(n0[1][1]) * km.y},
                         {sqrt_ap(n1[0][0]) * km.z, sqrt_ap(n1[0][1]) * km.z}, {sqrt_ap(n1[1][0]) * km.w, sqrt_ap(n1[1][1]) * km.w}};
  bool unsafe = false;
#pragma unroll
  for (int i = 0; i < 8; i++) unsafe |= !(b[i >> 1][i & 1] <= FAST_BOUND);
  uint32_t any;
  asm volatile("{\n.reg .pred p, q;\nsetp.ne.u32 p, %1, 0;\nbar.red.or.pred q, %2, 128, p;\nselp.u32 %0, 1, 0, q;\n}\n"
               : "=r"(any) : "r"((uint32_t)unsafe), "r"(NB_WG + wg) : "memory");
  const bool slow = __any_sync(~0u, any);
#pragma unroll
  for (int i = 0; i < 8; i++) xq[i >> 1][i & 1] = slow ? 0u : ((t & 1) ? BF_ONE : packbf(-b[i >> 1][i & 1], 1.f));
  return slow;
}
template <int O>
__device__ __forceinline__ void epilogue1b(const float (&a1)[2][64], const float (&a2)[24], const uint32_t (&xq)[4][2], int t, uint32_t ad01, uint32_t ad2) {
  stage_pair<O + 2, 0>(a1, a2, QSCALE, QSCALE, 1.f, xq[0][0], xq[0][1], xq[1][0], xq[1][1], ad01 + OFF_Q, ad2 + OFF_Q, t);
  stage_pair<O + 2, 1>(a1, a2, QSCALE, QSCALE, 1.f, xq[2][0], xq[2][1], xq[3][0], xq[3][1], ad01 + OFF_Q, ad2 + OFF_Q, t);
  const uint32_t one = (t & 1) ? 0u : BF_ONE;
  stage_pair<O + 1, 0>(a1, a2, 1.f, 1.f, 1.f, one, one, one, one, ad01 + OFF_V, ad2 + OFF_V, t);
  stage_pair<O + 1, 1>(a1, a2, 1.f, 1.f, 1.f, one, one, one, one, ad01 + OFF_V, ad2 + OFF_V, t);
}

__device__ __forceinline__ void issue_proj(float (&p)[12], uint32_t img, uint32_t wph) {
  mma_n24_ss_tb(p, mkdesc(img, 128, 384, 0), mkdesc(wph, 384, 128, 0), 0);
  mma_n24_ss_tb(p, mkdesc(img + 256, 0, 384, 0), mkdesc(wph + 768, 0, 128, 0), 1);
}

__device__ __forceinline__ uint32_t exp2_bits(float y0, float y1, uint32_t cm, uint32_t neg1) {
  uint32_t w, m, r;
  asm("prmt.b32 %0, %1, %2, 0x6521;" : "=r"(w) : "f"(y0), "f"(y1));
  asm("lop3.b32 %0, %1, 0x007F007F, %2, 0xEA;" : "=r"(m) : "r"(w), "r"(cm));
  const uint32_t e = m * neg1 + w;
  asm("fma.rn.bf16x2 %0, %1, %2, %3;" : "=r"(r) : "r"(w), "r"(m), "r"(e));
  return r;
}
template <int HI>
__device__ __forceinline__ void exp_tile(const float (&s)[32], uint32_t (&p)[16], uint32_t cm, uint32_t neg1) {
#pragma unroll
  for (int g = 0; g < 8; g++) {
    if ((POLY_MASK >> (g + 8 * HI)) & 1) {
      p[2 * g] = exp2_bits(s[4 * g], s[4 * g + 1], cm, neg1);
      p[2 * g + 1] = exp2_bits(s[4 * g + 2], s[4 * g + 3], cm, neg1);
    } else {
      p[2 * g] = packbf(ex2(s[4 * g]), ex2(s[4 * g + 1]));
      p[2 * g + 1] = packbf(ex2(s[4 * g + 2]), ex2(s[4 * g + 3]));
    }
  }
}
struct AttnDesc { uint64_t k, k2, v; };
__device__ __forceinline__ void issue_qk(float (&s)[32], const uint32_t (&q)[6], const AttnDesc& d, uint32_t ko) {
  mma_n64_rs(s, q[0], q[1], q[2], q[3], d.k + ko, 0);
  mma_n64_rs(s, q[4], q[5], 0u, 0u, d.k2 + ko, 1);
}
__device__ __forceinline__ void issue_pv(float (&o)[12], const uint32_t (&p)[16], uint64_t vd, int acc) {
#pragma unroll
  for (int kk = 0; kk < 4; kk++) mma_n24_rs_tb(o, p[4 * kk], p[4 * kk + 1], p[4 * kk + 2], p[4 * kk + 3], vd + kk * 48, acc | kk);
}
__device__ __forceinline__ void load_q(uint32_t (&q)[6], uint32_t a) {
#pragma unroll
  for (int i = 0; i < 6; i++) asm volatile("ld.shared.b32 %0, [%1];" : "=r"(q[i]) : "r"(a + (i >> 1) * 128 + (i & 1) * 384) : "memory");
}
template <int SL>
__device__ __forceinline__ void attn_chunk(float (&s)[32], uint32_t (&p0)[16], uint32_t (&p1)[16], float (&o)[12], const uint32_t (&q)[6],
                                           const AttnDesc& d, int acc, uint32_t full_next, uint32_t ph_next,
                                           uint32_t bars, uint32_t release, uint32_t cm, uint32_t neg1) {
  exp_tile<0>(s, p0, cm, neg1);
  wg_fence();
  issue_qk(s, q, d, SL * 1536 + 192);
  wg_commit();
  issue_pv(o, p0, d.v + SL * 1536, acc);
  wg_commit();
  wg_wait<1>();
  pin(s); pin(p1);
  mbar_arrive_if(bars + B_KE + 8 * ((SL + 3) & 3), release);
  const uint32_t ready = mbar_test(full_next, ph_next);
  exp_tile<1>(s, p1, cm, neg1);
  pin(p1);
  if (!__all_sync(~0u, ready)) mbar_wait_u(full_next, ph_next);
  wg_fence();
  issue_qk(s, q, d, ((SL + 1) & 3) * 1536);
  wg_commit();
  issue_pv(o, p1, d.v + SL * 1536 + 192, 1);
  wg_commit();
  wg_wait<1>();
  pin(s); pin(p0);
}
__device__ __forceinline__ int bgroup(int G) {
  const int hg = G / 10, j = G % 10;
  return (hg >> 2) * 40 + (j / 5) * 20 + (hg & 3) * 5 + j % 5;
}
__device__ __forceinline__ void stage_o(const float (&o)[12], int odd, uint32_t pair, int w4, int lane, float eps, float s0, float s1) {
  const int src = (lane & ~3) | (odd ? 0 : 2);
  const float l0 = __shfl_sync(~0u, o[8], src) + eps, l1 = __shfl_sync(~0u, o[10], src) + eps;
  const float r0 = s0 * rcp(l0), r1 = s1 * rcp(l1);
  const uint32_t base = pair + w4 * 256;
  stsm4(base + (odd ? 3072 : 0) + (lane >> 4) * 1024 + (lane & 15) * 16, packbf(o[0] * r0, o[1] * r0), packbf(o[2] * r1, o[3] * r1),
        packbf(o[4] * r0, o[5] * r0), packbf(o[6] * r1, o[7] * r1));
  if (((lane & 3) < 2) != (odd != 0)) {
    sts32(base + 2048 + lane * 4, packbf(o[8] * r0, o[9] * r0));
    sts32(base + 2048 + 128 + lane * 4, packbf(o[10] * r1, o[11] * r1));
  }
}
struct Maps { CUtensorMap a64, a16, b64, b16, out; };

__device__ __forceinline__ void w_load(const Maps& m, int it, uint32_t d, uint32_t b, int hg, int rank) {
  const int kb = (it % 10) * 2 + rank, c = hg * 80 + (hg & 1) * 16, c2 = hg * 80 + ((hg & 1) ? 0 : 64);
  const bool w0 = it < 10;
  const CUtensorMap *p64 = w0 ? &m.b64 : &m.a64, *q64 = w0 ? &m.a64 : &m.b64, *p16 = w0 ? &m.b16 : &m.a16, *q16 = w0 ? &m.a16 : &m.b16;
  const uint32_t d1 = d + rank * 4096, d2 = d + 24576 + rank * 1024;
  mbar_expect(b, W_STAGE);
  tma5_pair(d1, p64, 640 + c, kb, b);
  tma5_pair(d1 + 8192, p64, 1280 + c, kb, b);
  tma5_pair(d1 + 16384, q64, c, kb, b);
  tma5_pair(d2, p16, 640 + c2, kb, b);
  tma5_pair(d2 + 2048, p16, 1280 + c2, kb, b);
  tma5_pair(d2 + 4096, q16, c2, kb, b);
}
__device__ __forceinline__ void x_load(uint4 (&v)[4], const uint8_t* p, int it) {
  const uint8_t* q = p + (it % 10) * 128;
  v[0] = ldg_x(q); v[1] = ldg_x(q + 8 * 1280); v[2] = ldg_x(q + 64); v[3] = ldg_x(q + 8 * 1280 + 64);
}
__device__ __forceinline__ void gemm_step(float (&a1)[2][64], float (&a2)[24], uint4 (&xv)[4], uint32_t (&f)[4][4], uint32_t (&fp)[4][4],
                                          const uint8_t* xp, int it, int acc, uint32_t sb, uint32_t bars, uint32_t lead) {
  const int s = it % W_NST;
  const uint32_t z = mbar_test(bars + B_Z, 1) - 1;
  f[0][0] = xv[0].x ^ z; f[0][1] = xv[1].x ^ z; f[0][2] = xv[0].y ^ z; f[0][3] = xv[1].y ^ z;
  f[1][0] = xv[0].z ^ z; f[1][1] = xv[1].z ^ z; f[1][2] = xv[0].w ^ z; f[1][3] = xv[1].w ^ z;
  f[2][0] = xv[2].x ^ z; f[2][1] = xv[3].x ^ z; f[2][2] = xv[2].y ^ z; f[2][3] = xv[3].y ^ z;
  f[3][0] = xv[2].z ^ z; f[3][1] = xv[3].z ^ z; f[3][2] = xv[2].w ^ z; f[3][3] = xv[3].w ^ z;
#pragma unroll
  for (int i = 0; i < 4; i++) pin(f[i]);
  x_load(xv, xp, it + 2);
  mbar_wait_u(bars + B_WF + 8 * s, (it / W_NST) & 1);
  const uint64_t b1 = mkdesc(sb + s * W_STAGE, 8192, 1024, 1), b2 = mkdesc(sb + s * W_STAGE + 24576, 2048, 256, 3);
  wg_fence();
#pragma unroll
  for (int kk = 0; kk < 4; kk++) {
    mma_n128_rs_tb(a1[0], f[kk][0], f[kk][1], f[kk][2], f[kk][3], b1 + kk * 128, acc | kk);
    mma_n64_rs_tb(*(float(*)[32])a1[1], f[kk][0], f[kk][1], f[kk][2], f[kk][3], b1 + 1024 + kk * 128, acc | kk);
    mma_n48_rs_tb(a2, f[kk][0], f[kk][1], f[kk][2], f[kk][3], b2 + kk * 32, acc | kk);
  }
  wg_commit();
  wg_wait<1>();
#pragma unroll
  for (int i = 0; i < 4; i++) pin(fp[i]);
  mbar_arrive_pair(bars + B_WE + 8 * ((it + W_NST - 1) % W_NST), lead && acc);
}

__device__ __forceinline__ void kv_stream(uint32_t sb, int hg, int u, uint32_t epoch) {
  const uint32_t bars = sb + OFF_BAR + u * 64;
  cnt_wait(C_KV + hg, 16 * epoch);
  for (int c = 0; c < 32; c++) {
    const int s = c & 3;
    const uint8_t* src = g_KV + (size_t)(hg * 4 + (c >> 4) * 2 + u) * IMG_HEAD + (c & 15) * 6144;
    mbar_wait(bars + B_KE + 8 * s, (c >> 2) & 1);
    mbar_expect(bars + B_KF + 8 * s, 12288);
    bulk_g2s(sb + s * KV_CHUNK + u * 12288, src, 6144, bars + B_KF + 8 * s);
    bulk_g2s(sb + s * KV_CHUNK + u * 12288 + 6144, src + (size_t)NH * IMG_HEAD, 6144, bars + B_KF + 8 * s);
  }
}

__device__ __forceinline__ void out_step(float (&acc)[80], uint32_t (&f)[4][4], uint32_t (&fp)[4][4], int it, int accum, uint32_t sb, uint32_t arow,
                                         uint32_t bars, uint32_t lead) {
  const int s = it % 5;
  mbar_wait_u(bars + B_OF + 8 * s, it / 5);
  const uint32_t st = sb + o_stage(s);
#pragma unroll
  for (int kk = 0; kk < 4; kk++)
    asm volatile("ldmatrix.sync.aligned.m8n8.x4.shared.b16 {%0,%1,%2,%3}, [%4];"
                 : "=r"(f[kk][0]), "=r"(f[kk][1]), "=r"(f[kk][2]), "=r"(f[kk][3]) : "r"(st + arow + kk * 2048) : "memory");
  const uint64_t bd = mkdesc(st + 16384, 2560, 128, 0);
  wg_fence();
#pragma unroll
  for (int kk = 0; kk < 4; kk++) {
    mma_n80_rs_tb(*(float(*)[40])acc, f[kk][0], f[kk][1], f[kk][2], f[kk][3], bd + kk * 320, accum | kk);
    mma_n80_rs_tb(*(float(*)[40])(acc + 40), f[kk][0], f[kk][1], f[kk][2], f[kk][3], bd + kk * 320 + 80, accum | kk);
  }
  wg_commit();
  wg_wait<1>();
#pragma unroll
  for (int i = 0; i < 4; i++) pin(fp[i]);
  mbar_arrive_if(bars + B_OE + 8 * ((it + 4) % 5), lead && accum);
}

__device__ __forceinline__ void middle(uint8_t* smem, int wg, int w4, int lane, uint32_t cm, uint32_t neg1) {
  const uint32_t sb = smem_u32(smem), bars = sb + OFF_BAR, lead = (threadIdx.x & 127) == 0;
  const int t = lane & 3, mi = lane >> 3, r = wg & 1, u = wg >> 1;
  PROF(threadIdx.x == 0, 15);
  const bool slow = __any_sync(~0u, *(volatile uint32_t*)(smem + OFF_MISC + 20 + r * 4));
  const uint32_t wph = sb + OFF_WPH + u * 2304;
  {
    const uint32_t ak = sb + OFF_AK + r * 12288 + u * 6144;
    const uint32_t pka = sb + OFF_PHK + u * 20480 + (r * 8 + w4 * 2 + (mi & 1)) * 640 + (mi >> 1) * 128 + (lane & 7) * 16;
    float pp[12];
#pragma unroll 1
    for (int i = 0; i < 2; i++) {
      wg_fence();
      issue_proj(pp, ak + i * 3072, wph + i * 1152);
      wg_commit();
      wg_wait<0>();
      pin(pp);
      uint32_t f[10];
      hedgehog1(pp, f, t);
      stsm4(pka + i * 10240, f[0], f[1], f[2], f[3]);
      stsm4(pka + i * 10240 + 256, f[4], f[5], f[6], f[7]);
      stsm2(pka + i * 10240 + 512, f[8], f[9]);
    }
    fence_async_smem();
    PROF(threadIdx.x == 0, 16);
    bar_sync(NB_PHIK, 512);
    mbar_arrive_if(bars + B_KE + u * 64 + 8 * 3, lead);
    const uint64_t ad = mkdesc(sb + OFF_PHK + wg * 10240, 640, 128, 0), vd = mkdesc(sb + OFF_V + wg * 3072, 384, 128, 0);
    wg_fence();
#pragma unroll
    for (int ks = 0; ks < 8; ks++) mma_n24_ss_tatb(pp, ad + ks * 80, vd + (ks >> 2) * 768 + (ks & 3) * 48, ks);
    wg_commit();
    wg_wait<0>();
    pin(pp);
    bar_sync(NB_WG + wg, 128);
    float2* dst = (float2*)(smem + OFF_PHK + wg * 10240) + w4 * 192 + lane;
    if (w4 < 3) { dst[0] = make_float2(pp[0], pp[1]); dst[32] = make_float2(pp[4], pp[5]); dst[64] = make_float2(pp[8], pp[9]); }
    if (w4 < 2) { dst[96] = make_float2(pp[2], pp[3]); dst[128] = make_float2(pp[6], pp[7]); dst[160] = make_float2(pp[10], pp[11]); }
    fence_async_smem();
    bar_arrive(NB_TAIL, 544);
    PROF(threadIdx.x == 0, 5);
  }
  {
    const uint32_t gate = sb + OFF_GATE + (r * 64 + w4 * 16 + (lane >> 2)) * 8, qs = sb + OFF_Q + r * 12288;
    const uint32_t kb = bars + u * 64;
    AttnDesc d0;
    d0.k = mkdesc(sb + u * 12288, 128, 384, 0); d0.k2 = mkdesc(sb + u * 12288 + 256, 0, 384, 0);
    d0.v = mkdesc(sb + u * 12288 + 6144, 384, 128, 0);
    const uint32_t qa = qs + u * 3072 + w4 * 768 + lane * 4;
#pragma unroll 1
    for (int pass = 0; pass < 2; pass++) {
      float o[12], s0[32];
      uint32_t q[6];
      load_q(q, qa + pass * 6144);
      if (!slow) {
        uint32_t p0[16], p1[16] = {};
        mbar_wait_u(kb + B_KF, 0);
        wg_fence();
        issue_qk(s0, q, d0, 0);
        wg_commit();
        wg_wait<0>();
        pin(s0);
#pragma unroll 1
        for (int turn = 0; turn < 4; turn++) {
          const int ph = turn & 1;
          AttnDesc d;
          asm volatile("mov.b64 %0, %3;\nmov.b64 %1, %4;\nmov.b64 %2, %5;" : "=l"(d.k), "=l"(d.k2), "=l"(d.v) : "l"(d0.k), "l"(d0.k2), "l"(d0.v));
          attn_chunk<0>(s0, p0, p1, o, q, d, turn, kb + B_KF + 8, ph, kb, lead && turn, cm, neg1);
          attn_chunk<1>(s0, p0, p1, o, q, d, 1, kb + B_KF + 16, ph, kb, lead, cm, neg1);
          attn_chunk<2>(s0, p0, p1, o, q, d, 1, kb + B_KF + 24, ph, kb, lead, cm, neg1);
          attn_chunk<3>(s0, p0, p1, o, q, d, 1, kb + B_KF + (turn == 3 ? 24 : 0), turn == 3 ? 1 : ph ^ 1, kb, lead, cm, neg1);
        }
        wg_wait<0>();
        pin(o); pin(p1); pin(q);
        mbar_arrive_if(kb + B_KE + 24, lead);
      } else {
        uint32_t p[16];
        float m0 = -INFINITY, m1 = -INFINITY;
#pragma unroll
        for (int i = 0; i < 12; i++) o[i] = 0.f;
#pragma unroll 1
        for (int j = 0; j < 32; j++) {
          const int slot = (j >> 1) & 3;
          const uint32_t co = slot * 1536 + (j & 1) * 192, neg = (POLY_MASK >> ((j & 1) * 8)) & 0xFF;
          mbar_wait_u(kb + B_KF + 8 * slot, (j >> 3) & 1);
          wg_fence();
          issue_qk(s0, q, d0, co);
          wg_commit();
          wg_wait<0>();
          pin(s0);
          float n0 = m0, n1 = m1;
#pragma unroll
          for (int g = 0; g < 8; g++) { n0 = fmaxf(n0, fmaxf(s0[4 * g], s0[4 * g + 1])); n1 = fmaxf(n1, fmaxf(s0[4 * g + 2], s0[4 * g + 3])); }
          n0 = fmaxf(n0, __shfl_xor_sync(~0u, n0, 1)); n1 = fmaxf(n1, __shfl_xor_sync(~0u, n1, 1));
          n0 = fmaxf(n0, __shfl_xor_sync(~0u, n0, 2)); n1 = fmaxf(n1, __shfl_xor_sync(~0u, n1, 2));
          const float c0 = ex2(m0 - n0), c1 = ex2(m1 - n1);
          m0 = n0; m1 = n1;
#pragma unroll
          for (int i = 0; i < 3; i++) { o[4 * i] *= c0; o[4 * i + 1] *= c0; o[4 * i + 2] *= c1; o[4 * i + 3] *= c1; }
#pragma unroll
          for (int g = 0; g < 8; g++) {
            const uint32_t sg = ((neg >> g) & 1) ? 0x80008000u : 0u;
            p[2 * g] = packbf(ex2(s0[4 * g] - m0), ex2(s0[4 * g + 1] - m0)) ^ sg;
            p[2 * g + 1] = packbf(ex2(s0[4 * g + 2] - m1), ex2(s0[4 * g + 3] - m1)) ^ sg;
          }
          wg_fence();
          issue_pv(o, p, d0.v + co, 1);
          wg_commit();
          wg_wait<0>();
          pin(o); pin(p);
          mbar_arrive_if(kb + B_KE + 8 * slot, lead && (j & 1));
        }
      }
      mbar_wait_u(bars + B_G, 0);
      stage_o(o, u, qs + pass * 6144, w4, lane, 0.f, lds_f2(gate).y, lds_f2(gate + 64).y);
      PROF(threadIdx.x == 0, 6 + pass);
      if (pass == 0) {
        const uint32_t aq = sb + OFF_AQ + r * 12288;
        const float g0 = lds_f2(gate).x, g1 = lds_f2(gate + 64).x;
        float pp[2][12];
        wg_fence();
        issue_proj(pp[0], aq + u * 6144, wph);
        issue_proj(pp[1], aq + u * 6144 + 3072, wph + 1152);
        wg_commit();
        wg_wait<0>();
        pin(pp[0]); pin(pp[1]);
        bar_sync(13 + r, 256);
#pragma unroll
        for (int i = 0; i < 2; i++) {
          uint32_t f[10];
          hedgehog1(pp[i], f, t);
          pin(f);
          const uint64_t kvd = mkdesc(sb + OFF_V + (2 * u + i) * 1920, 384, 128, 0), kvd2 = mkdesc(sb + OFF_V + (2 * u + i) * 1920 + 1536, 0, 128, 0);
          wg_fence();
          mma_n24_rs_tb(pp[i], f[0], f[1], f[2], f[3], kvd, 0);
          mma_n24_rs_tb(pp[i], f[4], f[5], f[6], f[7], kvd + 48, 1);
          mma_n24_rs_tb(pp[i], f[8], f[9], 0u, 0u, kvd2, 1);
          wg_commit();
          wg_wait<0>();
          pin(pp[i]); pin(f);
          stage_o(pp[i], i, aq + u * 5120, w4, lane, 1e-6f, g0, g1);
        }
        fence_async_smem();
        bar_arrive(NB_READ, 544);
        PROF(threadIdx.x == 0, 17);
      }
    }
    fence_async_smem();
    bar_arrive(NB_LAST, 544);
  }
}

__global__ void __cluster_dims__(2, 1, 1) __launch_bounds__(640, 1)
fused_block(const __grid_constant__ Maps maps, const __nv_bfloat16* __restrict__ x, const __nv_bfloat16* __restrict__ wphi,
            const __nv_bfloat16* __restrict__ gate_w, const uint8_t* __restrict__ woa, const uint8_t* __restrict__ wob, uint32_t cm, uint32_t neg1) {
  extern __shared__ __align__(1024) uint8_t smem[];
  const uint32_t sb = smem_u32(smem), bars = sb + OFF_BAR;
  const int warp = __shfl_sync(~0u, threadIdx.x >> 5, 0), lane = threadIdx.x & 31, wg = warp >> 2;
  const int bid = blockIdx.x;
  const int mt = (bid & 1) + 2 * (bid >> 4), hg = (bid >> 1) & 7;
  const int half = bid & 1, nt = (bid >> 1) & 3, mt3 = bid >> 3;
  PROF(threadIdx.x == 0, 0);
  if (warp == 16) {
    if (lane == 0) {
#pragma unroll
      for (int i = 0; i < W_NST; i++) { mbar_init(bars + B_WF + 8 * i, 1); mbar_init(bars + B_WE + 8 * i, 4); }
      mbar_init(bars + B_Z, 1);
      mbar_init(bars + B_X, 1);
      *(uint4*)(smem + OFF_MISC) = make_uint4(0u, 0u, 0u, 0u);
      asm volatile("fence.mbarrier_init.release.cluster;" ::: "memory");
    }
    __syncwarp();
  }
  PROF(threadIdx.x == 512, 8);
  asm volatile("barrier.cluster.arrive.relaxed.aligned;" ::: "memory");

  if (wg == 4) {
    reg_dec<32>();
    asm volatile("barrier.cluster.wait.aligned;" ::: "memory");
    if (warp == 16) {
      if (lane == 0) {
        PROF(true, 9);
        for (int it = 0; it < 20; it++) {
          const int s = it % W_NST;
          PROF(it == 1, 10);
          if (it >= W_NST) mbar_wait(bars + B_WE + 8 * s, ((it / W_NST) - 1) & 1);
          PROF(it == 5, 1);
          w_load(maps, it, sb + s * W_STAGE, bars + B_WF + 8 * s, hg, half);
        }
      }
      __syncwarp();
      bar_sync(NB_HELP, 128);
      const uint32_t epoch = *(volatile uint32_t*)(smem + OFF_MISC + 16);
      if (lane == 0) {
        kv_stream(sb, hg, 0, epoch);
        cnt_wait(C_WO, NCTA * epoch);
        cnt_wait(C_OA + mt3, 8 * epoch);
        mbar_wait(bars + B_RF, 0);
        for (int it = 0; it < 10; it++) {
          const int s = it % 5, ks = (it < 5 ? 0 : 5) + half * 5 + it;
          if (it >= 5) mbar_wait(bars + B_OE + 8 * s, 0);
          else if (it >= 2) { mbar_wait(bars + B_KE + 8 * (it - 1), 0); mbar_wait(bars + B_KE + 64 + 8 * (it - 1), 0); }
          if (it == 7) { PROF(true, 19); cnt_wait(C_OB + mt3, 8 * epoch); PROF(true, 21); }
          const uint32_t d = sb + o_stage(s), b = bars + B_OF + 8 * s;
          const uint8_t* ga = g_OAB + (size_t)mt3 * 327680 + ks * 8192;
          mbar_expect(b, O_STAGE);
          bulk_g2s(d + 16384, g_WOI + (size_t)nt * 409600 + ks * 20480, 20480, b);
          bulk_g2s(d, ga, 8192, b);
          bulk_g2s(d + 8192, ga + 163840, 8192, b);
        }
      }
    } else if (warp == 17) {
      uint32_t epoch = 0;
      if (lane == 0) {
#pragma unroll
        for (int i = 0; i < 8; i++) { mbar_init(bars + B_KF + (i >> 2) * 64 + 8 * (i & 3), 1); mbar_init(bars + B_KE + (i >> 2) * 64 + 8 * (i & 3), 2); }
#pragma unroll
        for (int i = 0; i < 5; i++) { mbar_init(bars + B_OF + 8 * i, 1); mbar_init(bars + B_OE + 8 * i, 2); }
        mbar_init(bars + B_RF, 1);
        mbar_init(bars + B_G, 1);
        fence_async_smem();
        epoch = atomicAdd(g_CNT + C_START * 8, 1u) / NCTA + 1;
        *(volatile uint32_t*)(smem + OFF_MISC + 16) = epoch;
      }
      epoch = __shfl_sync(~0u, epoch, 0);
      bar_arrive(NB_HELP, 128);
#pragma unroll 1
      for (int e = lane; e < 96; e += 32) {
        const int i = e / 24, slot = e % 24;
        int d = -1;
        if (i & 1) { if (slot < 16) d = slot + 4; else if (slot >= 20) d = slot - 20; }
        else if (slot < 20) d = slot;
        uint2 v[5] = {};
        if (d >= 0) {
#pragma unroll
          for (int u = 0; u < 5; u++) v[u] = __ldg((const uint2*)(wphi + ((hg * 4 + i) * 20 + d) * 20) + u);
        }
        uint8_t* dst = smem + OFF_WPH + i * 1152 + (slot >> 3) * 384 + (slot & 7) * 16;
        *(uint4*)dst = make_uint4(v[0].x, v[0].y, v[1].x, v[1].y);
        *(uint4*)(dst + 128) = make_uint4(v[2].x, v[2].y, v[3].x, v[3].y);
        *(uint4*)(dst + 256) = make_uint4(v[4].x, v[4].y, v[4].x, v[4].y);
      }
      fence_async_smem();
      bar_sync(NB_STAGED, 288);
      if (lane == 0) {
        bulk_s2g(g_KMAX + hg * 16 + mt, sb + OFF_MISC, 16);
        bulk_commit_wait();
        cnt_add_done(C_KM + hg);
#pragma unroll 1
        for (int i = 0; i < 16; i++) {
          if (!XNOST) bulk_s2g(g_KV + (size_t)((i >> 3) * NH + hg * 4 + (i & 3)) * IMG_HEAD + (mt * 2 + ((i >> 2) & 1)) * 3072, sb + OFF_Q + i * 3072, 3072);
          __nanosleep(STNS);
        }
        bulk_commit_wait();
        PROF(true, 22);
        cnt_add_done(C_KV + hg);
        cnt_wait(C_KM + hg, 16 * epoch);
      }
      __syncwarp();
      {
        uint4 v = ldg_cg4(g_KMAX + hg * 16 + (lane & 15));
        v.x = __reduce_max_sync(~0u, v.x); v.y = __reduce_max_sync(~0u, v.y); v.z = __reduce_max_sync(~0u, v.z); v.w = __reduce_max_sync(~0u, v.w);
        if (lane < 4) *(volatile float*)(smem + OFF_MISC + lane * 4) =
            sqrt_ap(__uint_as_float(lane == 0 ? v.x : lane == 1 ? v.y : lane == 2 ? v.z : v.w)) * (QSCALE * 1.02f);
      }
      bar_arrive(NB_FREE, 288);
      bar_sync(NB_TAIL, 544);
      if (lane == 0) {
#pragma unroll 1
        for (int i = 0; i < 4; i++) bulk_s2g(g_KVP + (size_t)((hg * 4 + i) * 16 + mt) * 480, sb + OFF_PHK + i * 10240, 3840);
        bulk_commit_wait();
        cnt_add_done(C_KVP + hg);
        cnt_wait(C_GATE + mt, 8 * epoch);
      }
      __syncwarp();
      {
        const uint4 g0 = ldg_cg4(g_GATE + mt * 128 + lane * 2), g1 = ldg_cg4(g_GATE + mt * 128 + 64 + lane * 2);
        *(uint4*)(smem + OFF_GATE + lane * 16) = g0;
        *(uint4*)(smem + OFF_GATE + 512 + lane * 16) = g1;
      }
      if (lane == 0) cnt_wait(C_KVB + hg, 16 * epoch);
      __syncwarp();
#pragma unroll 1
      for (int e0 = 0; e0 < 480; e0 += 160) {
        uint4 v[5];
#pragma unroll
        for (int u = 0; u < 5; u++) v[u] = ldg_cg4(g_KVB + hg * 4 * 480 + (e0 + u * 32 + lane) * 4);
#pragma unroll
        for (int u = 0; u < 5; u++) *(uint4*)(smem + OFF_V + (e0 + u * 32 + lane) * 16) = v[u];
      }
      fence_async_smem();
      __syncwarp();
      if (lane == 0) mbar_arrive(bars + B_G);
      uint8_t* og = g_OAB + (size_t)mt * 327680;
      bar_sync(NB_READ, 544);
      if (lane == 0) {
#pragma unroll 1
        for (int w = 0; w < 2; w++) {
          bulk_s2g(og + w * 163840 + hg * 10240, sb + OFF_AQ + w * 12288, 10240);
          bulk_s2g(og + w * 163840 + (80 + bgroup(hg * 10)) * 1024, sb + OFF_Q + w * 12288, 5120);
        }
        bulk_commit_wait();
        mbar_arrive(bars + B_RF);
        cnt_add_done(C_OA + mt);
      }
      __syncwarp();
      bar_sync(NB_LAST, 544);
      if (lane == 0) {
        bulk_s2g(og + (80 + bgroup(hg * 10 + 5)) * 1024, sb + OFF_Q + 6144, 5120);
        bulk_s2g(og + 163840 + (80 + bgroup(hg * 10 + 5)) * 1024, sb + OFF_Q + 12288 + 6144, 5120);
        bulk_commit_wait();
        cnt_add_done(C_OB + mt);
      }
    } else if (warp == 18) {
      bar_sync(NB_HELP, 128);
      if (lane == 0) kv_stream(sb, hg, 1, *(volatile uint32_t*)(smem + OFF_MISC + 16));
    } else {
      bar_sync(NB_HELP, 128);
      const uint32_t epoch = *(volatile uint32_t*)(smem + OFF_MISC + 16);
      if (lane == 0) cnt_wait(C_KVP + hg, 16 * epoch);
      __syncwarp();
#pragma unroll 1
      for (int e0 = lane; e0 < 60; e0 += 32) {
        const int hd = hg * 4 + e0 / 15, e = mt * 30 + (e0 % 15) * 2;
        const float2* src = g_KVP + (size_t)hd * 16 * 480 + e;
        float4 s = make_float4(0.f, 0.f, 0.f, 0.f);
#pragma unroll 1
        for (int m0 = 0; m0 < 16; m0 += 4) {
          uint4 v[4];
#pragma unroll
          for (int m = 0; m < 4; m++) v[m] = ldg_cg4(src + (m0 + m) * 480);
#pragma unroll
          for (int m = 0; m < 4; m++) {
            s.x += __uint_as_float(v[m].x); s.y += __uint_as_float(v[m].y); s.z += __uint_as_float(v[m].z); s.w += __uint_as_float(v[m].w);
          }
        }
        *(uint2*)(g_KVB + hd * 480 + e) = make_uint2(packbf(s.x, s.y), packbf(s.z, s.w));
      }
      __syncwarp();
      if (lane == 0) cnt_add(C_KVB + hg);
      PROF(lane == 0, 20);
    }
  } else {
    const int w4 = warp & 3;
    const uint32_t lead = (threadIdx.x & 127) == 0;
    if (wg >= 2) {
      reg_dec<24>();
      asm volatile("barrier.cluster.wait.aligned;" ::: "memory");
      const int ht = threadIdx.x - 256;
      __nanosleep(BGNS);
      {
        const int row = mt * 128 + hg * 16 + (ht >> 4);
        const uint4* xr = (const uint4*)(x + (size_t)row * DM) + (ht & 15);
        const uint4* gr = (const uint4*)gate_w + (ht & 15);
        float acc = 0.f;
#pragma unroll 1
        for (int i = 0; i < 5; i++) {
          const uint4 a = __ldg(xr + i * 16), g = __ldg(gr + i * 16);
          const uint32_t av[4] = {a.x, a.y, a.z, a.w}, gv[4] = {g.x, g.y, g.z, g.w};
#pragma unroll
          for (int j = 0; j < 4; j++) {
            uint32_t p;
            asm("mul.rn.bf16x2 %0, %1, %2;" : "=r"(p) : "r"(av[j]), "r"(gv[j]));
            acc += bf_lo(p) + bf_hi(p);
          }
        }
#pragma unroll
        for (int o = 8; o; o >>= 1) acc += __shfl_xor_sync(~0u, acc, o);
        if ((ht & 15) == 0) {
          const float g = bf_round(__fdividef(1.f, 1.f + __expf(-bf_round(acc))));
          g_GATE[row] = make_float2(g, bf_round(1.f - g));
        }
      }
#pragma unroll 1
      for (int e = ht; e < (bid < 32 ? 1280 : 640); e += 256) {
        const int kg = bid + (e >= 640 ? NCTA : 0), c = (e % 640) >> 3;
        const uint8_t* src = (kg < 80 ? woa + (size_t)kg * 10240 : wob + (size_t)(kg - 80) * 10240) + (e & 7) * 1280 + c * 16;
        *(uint4*)(g_WOI + (kg < 80 ? kg : 80 + bgroup(kg - 80)) * 2560 + (size_t)(c / 20) * 409600 + (c % 20) * 128 + (e & 7) * 16) = __ldg((const uint4*)src);
      }
      bar_sync(NB_BG, 256);
      if (ht == 0) { cnt_add(C_GATE + mt); cnt_add_done(C_WO); PROF(true, 18); }
      bar_sync(NB_EPI, 512);
      reg_inc<112>();
    } else {
    const uint8_t* xp = (const uint8_t*)x + (size_t)(mt * 128 + warp * 16 + (lane >> 2)) * 1280 + (lane & 3) * 16;
    uint4 xa[4], xb[4];
    x_load(xa, xp, 0);
    x_load(xb, xp, 1);
    reg_inc<200>();
    asm volatile("barrier.cluster.wait.aligned;" ::: "memory");
    const int t = lane & 3, mi = lane >> 3;
    {
      const uint32_t sbase = sb + wg * 12288 + (w4 * 2 + (mi & 1)) * 384 + (lane & 7) * 16;
      const uint32_t ad01 = sbase + (mi >> 1) * 128, ad2 = sbase + (mi >> 1) * 3072 + 256;
      float a1[2][64], a2[24];
      uint32_t fa[4][4] = {}, fb[4][4] = {};
#pragma unroll 1
      for (int tile = 0; tile < 2; tile++) {
#pragma unroll 1
        for (int ks = 0; ks < 10; ks += 2) {
          gemm_step(a1, a2, xa, fa, fb, xp, tile * 10 + ks, ks, sb, bars, lead);
          gemm_step(a1, a2, xb, fb, fa, xp, tile * 10 + ks + 1, 1, sb, bars, lead);
        }
        wg_wait<0>();
        pin(a1[0]); pin(*(float(*)[32])a1[1]); pin(a2);
#pragma unroll
        for (int i = 0; i < 4; i++) pin(fb[i]);
        mbar_arrive_pair(bars + B_WE + 8 * 4, lead);
        PROF(threadIdx.x == 0, 2 + 2 * tile);
        if (tile == 0) {
          if (hg & 1) epilogue0<4>(a1, a2, warp * 2, lane, ad01, ad2, sb + OFF_MISC);
          else epilogue0<0>(a1, a2, warp * 2, lane, ad01, ad2, sb + OFF_MISC);
          fence_async_smem();
          bar_arrive(NB_STAGED, 288);
          PROF(threadIdx.x == 0, 3);
        }
      }
      bar_sync(NB_FREE, 288);
#pragma unroll
      for (int s = 0; s < 3; s++) { mbar_arrive_if(bars + B_KE + 8 * s, lead); mbar_arrive_if(bars + B_KE + 64 + 8 * s, lead); }
      mbar_wait_u(bars + B_WE + 8 * 4, 1);
      PROF(threadIdx.x == 0, 23);
      uint32_t xq[4][2];
      bool unsafe;
      if (hg & 1) { unsafe = epilogue1a<4>(a1, a2, xq, smem, wg, t, ad01, ad2); epilogue1b<4>(a1, a2, xq, t, ad01, ad2); }
      else { unsafe = epilogue1a<0>(a1, a2, xq, smem, wg, t, ad01, ad2); epilogue1b<0>(a1, a2, xq, t, ad01, ad2); }
      if (lead) *(volatile uint32_t*)(smem + OFF_MISC + 20 + wg * 4) = unsafe;
      fence_async_smem();
      reg_dec<112>();
      bar_sync(NB_EPI, 512);
    }
    }
    middle(smem, wg, w4, lane, cm, neg1);
    if (wg >= 2) { reg_dec<24>(); return; }
    {
      asm volatile("barrier.cluster.arrive.relaxed.aligned;" ::: "memory");
      reg_inc<160>();
      float acc[80];
      uint32_t fa[4][4] = {}, fb[4][4] = {};
      const uint32_t arow = wg * 8192 + (lane >> 4) * 1024 + w4 * 256 + (lane & 15) * 16;
#pragma unroll 1
      for (int it = 0; it < 10; it += 2) {
        out_step(acc, fa, fb, it, it, sb, arow, bars, lead);
        out_step(acc, fb, fa, it + 1, 1, sb, arow, bars, lead);
      }
      wg_wait<0>();
      pin(acc);
#pragma unroll
      for (int i = 0; i < 4; i++) pin(fb[i]);
      PROF(threadIdx.x == 0, 12);
      asm volatile("barrier.cluster.wait.aligned;" ::: "memory");
      uint32_t remote, rbar;
      asm volatile("mapa.shared::cluster.u32 %0, %1, %2;" : "=r"(remote) : "r"(sb + OFF_Q + threadIdx.x * 16), "r"(half ^ 1));
      asm volatile("mapa.shared::cluster.u32 %0, %1, %2;" : "=r"(rbar) : "r"(bars + B_X), "r"(half ^ 1));
      if (threadIdx.x == 0) mbar_expect(bars + B_X, 20480);
#pragma unroll
      for (int j = 0; j < 5; j++) {
        uint32_t v[4];
#pragma unroll
        for (int u = 0; u < 4; u++) v[u] = half ? packbf(acc[8 * j + 2 * u], acc[8 * j + 2 * u + 1]) : packbf(acc[40 + 8 * j + 2 * u], acc[41 + 8 * j + 2 * u]);
        asm volatile("st.async.weak.shared::cluster.mbarrier::complete_tx::bytes.v4.b32 [%0], {%1,%2,%3,%4}, [%5];" ::"r"(remote + j * 4096), "r"(v[0]),
                     "r"(v[1]), "r"(v[2]), "r"(v[3]), "r"(rbar) : "memory");
      }
      bar_sync(NB_PHIK, 256);
      mbar_wait_u(bars + B_X, 0);
      PROF(threadIdx.x == 0, 13);
      const uint32_t ob = sb + wg * 10240;
      const uint32_t oa = ob + (w4 * 16 + (lane & 15)) * 160 + (lane >> 4) * 16;
      uint32_t pk[20];
#pragma unroll
      for (int j = 0; j < 5; j++) {
        const uint4 r = *(const uint4*)(smem + OFF_Q + j * 4096 + threadIdx.x * 16);
        const uint32_t rv[4] = {r.x, r.y, r.z, r.w};
#pragma unroll
        for (int u = 0; u < 4; u++) {
          const float v0 = half ? acc[40 + 8 * j + 2 * u] : acc[8 * j + 2 * u], v1 = half ? acc[41 + 8 * j + 2 * u] : acc[8 * j + 2 * u + 1];
          pk[4 * j + u] = packbf(v0 + bf_lo(rv[u]), v1 + bf_hi(rv[u]));
        }
      }
#pragma unroll
      for (int j = 0; j < 10; j += 2) stsm4(oa + j * 16, pk[2 * j], pk[2 * j + 1], pk[2 * j + 2], pk[2 * j + 3]);
      fence_async_smem();
      bar_sync(NB_WG + wg, 128);
      if (lead) {
        asm volatile("cp.async.bulk.tensor.2d.global.shared::cta.bulk_group [%0, {%2,%3}], [%1];" ::"l"(&maps.out), "r"(ob), "r"(nt * 160 + half * 80),
                     "r"(mt3 * 128 + wg * 64) : "memory");
        asm volatile("cp.async.bulk.commit_group;" ::: "memory");
        asm volatile("cp.async.bulk.wait_group.read 0;" ::: "memory");
      }
      PROF(threadIdx.x == 0, 14);
    }
  }
}

typedef CUresult (*EncodeFn)(CUtensorMap*, CUtensorMapDataType, cuuint32_t, void*, const cuuint64_t*, const cuuint64_t*, const cuuint32_t*,
                             const cuuint32_t*, CUtensorMapInterleave, CUtensorMapSwizzle, CUtensorMapL2promotion, CUtensorMapFloatOOBfill);

void encode(EncodeFn fn, CUtensorMap* m, const void* p, int rank, const cuuint64_t* dims, const cuuint64_t* strides, const cuuint32_t* box,
            CUtensorMapSwizzle sw) {
  const cuuint32_t es[5] = {1, 1, 1, 1, 1};
  fn(m, CU_TENSOR_MAP_DATA_TYPE_BFLOAT16, rank, const_cast<void*>(p), dims, strides, box, es, CU_TENSOR_MAP_INTERLEAVE_NONE, sw,
     CU_TENSOR_MAP_L2_PROMOTION_L2_128B, CU_TENSOR_MAP_FLOAT_OOB_FILL_NONE);
}

}

extern "C" void kernel_launch(void* const* d_in, const int* in_sizes, int n_in, void* d_out, int out_size) {
  (void)in_sizes; (void)n_in; (void)out_size;
  static EncodeFn enc = nullptr;
  if (!enc) {
    void* fn = nullptr;
    cudaDriverEntryPointQueryResult qr;
    cudaGetDriverEntryPoint("cuTensorMapEncodeTiled", &fn, cudaEnableDefault, &qr);
    enc = (EncodeFn)fn;
    cudaFuncSetAttribute(fused_block, cudaFuncAttributeMaxDynamicSharedMemorySize, SMEM_BYTES);
  }
  Maps maps;
  {
    const cuuint64_t dx[2] = {640, 2048}, sx[1] = {1280};
    const cuuint32_t bo[2] = {80, 64};
    encode(enc, &maps.out, d_out, 2, dx, sx, bo, CU_TENSOR_MAP_SWIZZLE_NONE);
    const cuuint64_t dw[5] = {1920, 2, 4, 4, 20}, sw[4] = {3840, 8 * 3840, 2 * 3840, 32 * 3840};
    const cuuint32_t b64[5] = {64, 2, 4, 4, 1}, b16[5] = {16, 2, 4, 4, 1};
    encode(enc, &maps.a64, d_in[1], 5, dw, sw, b64, CU_TENSOR_MAP_SWIZZLE_128B);
    encode(enc, &maps.a16, d_in[1], 5, dw, sw, b16, CU_TENSOR_MAP_SWIZZLE_32B);
    encode(enc, &maps.b64, d_in[5], 5, dw, sw, b64, CU_TENSOR_MAP_SWIZZLE_128B);
    encode(enc, &maps.b16, d_in[5], 5, dw, sw, b16, CU_TENSOR_MAP_SWIZZLE_32B);
  }
  fused_block<<<NCTA, 640, SMEM_BYTES, cudaStreamPerThread>>>(maps, (const __nv_bfloat16*)d_in[0], (const __nv_bfloat16*)d_in[2],
                                                               (const __nv_bfloat16*)d_in[7],
                                                               (const uint8_t*)d_in[3], (const uint8_t*)d_in[6], 0x1F801F80u, 0xFFFFFFFFu);
}
```

```cpp
#include <cuda_runtime.h>
#include <cuda_bf16.h>
#include <cuda.h>
#include <stdint.h>

#define STNS 100
#define POLLNS 40
#define BGNS 2500
#define XNOKV 0
#define TMPF 0
#define PFROWS 0
#define NOX 0
#define RDS 0
#define PAIRINV 1
#define O_DRAIN 1
#define P3RS 1
#define XNOST 0
#define XDELAY 0
namespace {

constexpr int SEQ = 2048, DM = 640, NH = 32, NCTA = 128;
constexpr int IMG_HEAD = SEQ * 48;
#define POLY_MASK 0x6D6Du
constexpr float LOG2E = 1.4426950408889634f;
constexpr float QSCALE = 0.22360679774997896f * 1.4426950408889634f;
constexpr uint32_t BF_ONE = 0x3F80u;
constexpr uint32_t BF_MAGIC = 0x43E0u;
constexpr uint32_t BF_MU_HI = 0x4025u;
constexpr uint32_t BF_MU_LO = 0x3B8Bu;
constexpr float FAST_BOUND = 40.0f;

__device__ __align__(1024) uint8_t g_KV[2 * NH * IMG_HEAD];
__device__ __align__(1024) float2 g_KVA[NH * 480];
__device__ __align__(1024) float4 g_KMAX[8 * 16];
__device__ __align__(1024) float2 g_GATE[SEQ];
__device__ __align__(1024) uint8_t g_OAB[16 * 2 * 160 * 1024];
__device__ __align__(1024) uint8_t g_WOI[4 * 409600];
__device__ __align__(1024) uint32_t g_CNT[82 * 8];
constexpr int C_START = 0, C_WO = 1, C_KV = 2, C_KVP = 10, C_GATE = 26, C_OA = 42, C_OB = 58, C_KM = 74;

#define SPIN_LIMIT (1ll << 29)
#define SPIN_FAIL(code) __trap()
#define PROF(cond, slot)
#define PROFNS(cond, slot)
__device__ __forceinline__ uint32_t smem_u32(const void* p) { return (uint32_t)__cvta_generic_to_shared(p); }
__device__ __forceinline__ void mbar_init(uint32_t a, uint32_t c) { asm volatile("mbarrier.init.shared::cta.b64 [%0], %1;" ::"r"(a), "r"(c) : "memory"); }
__device__ __forceinline__ void mbar_expect(uint32_t a, uint32_t b) { asm volatile("mbarrier.arrive.expect_tx.shared::cta.b64 _, [%0], %1;" ::"r"(a), "r"(b) : "memory"); }
__device__ __forceinline__ void mbar_arrive(uint32_t a) { asm volatile("mbarrier.arrive.shared::cta.b64 _, [%0];" ::"r"(a) : "memory"); }
__device__ __forceinline__ uint32_t mbar_try(uint32_t a, uint32_t ph) {
  uint32_t ok;
  asm volatile("{\n.reg .pred p;\nmbarrier.try_wait.parity.shared::cta.b64 p, [%1], %2;\nselp.u32 %0, 1, 0, p;\n}\n" : "=r"(ok) : "r"(a), "r"(ph) : "memory");
  return ok;
}
__device__ __forceinline__ void mbar_wait(uint32_t a, uint32_t ph) {
  if (mbar_try(a, ph)) return;
  const long long t0 = clock64();
  while (!mbar_try(a, ph))
    if (clock64() - t0 > SPIN_LIMIT) { SPIN_FAIL(1000 + (a & 0x1FF) * 2 + ph); break; }
}
__device__ __forceinline__ void mbar_wait_u(uint32_t a, uint32_t ph) {
#pragma unroll 1
  for (int n = 0; n < (1 << 18); n++)
    if (__all_sync(~0u, mbar_try(a, ph))) break;
}
__device__ __forceinline__ uint32_t mbar_test(uint32_t a, uint32_t ph) {
  uint32_t ok;
  asm volatile("{\n.reg .pred p;\nmbarrier.test_wait.parity.shared::cta.b64 p, [%1], %2;\nselp.u32 %0, 1, 0, p;\n}\n" : "=r"(ok) : "r"(a), "r"(ph) : "memory");
  return ok;
}
__device__ __forceinline__ void mbar_arrive_if(uint32_t a, uint32_t flag) {
  asm volatile("{\n.reg .pred p;\nsetp.ne.u32 p, %1, 0;\n@p mbarrier.arrive.shared::cta.b64 _, [%0];\n}\n" ::"r"(a), "r"(flag) : "memory");
}
__device__ __forceinline__ void cnt_add_done(int slot) { asm volatile("red.relaxed.gpu.global.add.u32 [%0], 1;" ::"l"(g_CNT + slot * 8) : "memory"); }
__device__ __forceinline__ void cnt_add(int slot) {
  asm volatile("fence.acq_rel.gpu;" ::: "memory");
  cnt_add_done(slot);
}
__device__ __forceinline__ void cnt_wait(int slot, uint32_t target) {
  uint32_t v;
  long long t0 = 0;
  for (;;) {
    asm volatile("ld.relaxed.gpu.global.u32 %0, [%1];" : "=r"(v) : "l"(g_CNT + slot * 8) : "memory");
    if ((int32_t)(v - target) >= 0) break;
    __nanosleep(POLLNS);
    if (!t0) t0 = clock64();
    else if (clock64() - t0 > SPIN_LIMIT) { SPIN_FAIL(slot); break; }
  }
  asm volatile("ld.acquire.gpu.global.u32 %0, [%1];" : "=r"(v) : "l"(g_CNT + slot * 8) : "memory");
}
__device__ __forceinline__ void bulk_commit_wait() { asm volatile("cp.async.bulk.commit_group;\ncp.async.bulk.wait_group 0;" ::: "memory"); }
template <bool MC>
__device__ __forceinline__ void tma5(uint32_t dst, const CUtensorMap* m, int c0, int c4, uint32_t bar) {
  if (MC)
    asm volatile("cp.async.bulk.tensor.5d.shared::cluster.global.mbarrier::complete_tx::bytes.multicast::cluster [%0], [%1, {%3,%5,%5,%5,%4}], [%2], %6;"
                 ::"r"(dst), "l"(m), "r"(bar), "r"(c0), "r"(c4), "r"(0), "h"((uint16_t)3) : "memory");
  else
    asm volatile("cp.async.bulk.tensor.5d.shared::cluster.global.mbarrier::complete_tx::bytes [%0], [%1, {%3,%5,%5,%5,%4}], [%2];"
                 ::"r"(dst), "l"(m), "r"(bar), "r"(c0), "r"(c4), "r"(0) : "memory");
}
__device__ __forceinline__ void mbar_arrive_pair(uint32_t a, uint32_t flag) {
  asm volatile("{\n.reg .pred p;\n.reg .b32 r0, r1;\nsetp.ne.u32 p, %1, 0;\nmapa.shared::cluster.u32 r0, %0, 0;\nmapa.shared::cluster.u32 r1, %0, 1;\n"
               "@p mbarrier.arrive.relaxed.cluster.shared::cluster.b64 _, [r0];\n@p mbarrier.arrive.relaxed.cluster.shared::cluster.b64 _, [r1];\n}\n" ::"r"(a), "r"(flag) : "memory");
}
__device__ __forceinline__ void bulk_g2s(uint32_t dst, const void* src, uint32_t bytes, uint32_t bar) {
  asm volatile("cp.async.bulk.shared::cluster.global.mbarrier::complete_tx::bytes [%0], [%1], %2, [%3];" ::"r"(dst), "l"(src), "r"(bytes), "r"(bar) : "memory");
}
__device__ __forceinline__ void fence_async_smem() { asm volatile("fence.proxy.async.shared::cta;" ::: "memory"); }
__device__ __forceinline__ void bar_sync(int id, int n) { asm volatile("bar.sync %0, %1;" ::"r"(id), "r"(n) : "memory"); }
__device__ __forceinline__ void bar_arrive(int id, int n) { asm volatile("bar.arrive %0, %1;" ::"r"(id), "r"(n) : "memory"); }
__device__ __forceinline__ void wg_fence() { asm volatile("wgmma.fence.sync.aligned;" ::: "memory"); }
__device__ __forceinline__ void wg_commit() { asm volatile("wgmma.commit_group.sync.aligned;" ::: "memory"); }
template <int N> __device__ __forceinline__ void wg_wait() { asm volatile("wgmma.wait_group.sync.aligned %0;" ::"n"(N) : "memory"); }
template <int N> __device__ __forceinline__ void reg_inc() { asm volatile("setmaxnreg.inc.sync.aligned.u32 %0;" ::"n"(N)); }
template <int N> __device__ __forceinline__ void reg_dec() { asm volatile("setmaxnreg.dec.sync.aligned.u32 %0;" ::"n"(N)); }
template <int N> __device__ __forceinline__ void pin(float (&r)[N]) {
#pragma unroll
  for (int i = 0; i < N; i++) asm volatile("" : "+f"(r[i])::"memory");
}
template <int N> __device__ __forceinline__ void pin(uint32_t (&r)[N]) {
#pragma unroll
  for (int i = 0; i < N; i++) asm volatile("" : "+r"(r[i])::"memory");
}
__device__ __forceinline__ uint64_t mkdesc(uint32_t addr, uint32_t lbo, uint32_t sbo, uint32_t swz) {
  return (uint64_t)((addr & 0x3FFFF) >> 4) | ((uint64_t)(lbo >> 4) << 16) | ((uint64_t)(sbo >> 4) << 32) | ((uint64_t)swz << 62);
}
__device__ __forceinline__ float ex2(float x) { float y; asm("ex2.approx.ftz.f32 %0, %1;" : "=f"(y) : "f"(x)); return y; }
__device__ __forceinline__ float rcp(float x) { float y; asm("rcp.approx.ftz.f32 %0, %1;" : "=f"(y) : "f"(x)); return y; }
__device__ __forceinline__ float sqrt_ap(float x) { float y; asm("sqrt.approx.f32 %0, %1;" : "=f"(y) : "f"(x)); return y; }
__device__ __forceinline__ uint32_t packbf(float lo, float hi) { uint32_t d; asm("cvt.rn.bf16x2.f32 %0, %1, %2;" : "=r"(d) : "f"(hi), "f"(lo)); return d; }
__device__ __forceinline__ float bf_lo(uint32_t v) { return __uint_as_float(v << 16); }
__device__ __forceinline__ float bf_hi(uint32_t v) { return __uint_as_float(v & 0xFFFF0000u); }
__device__ __forceinline__ float bf_round(float x) { return bf_lo(packbf(x, 0.f)); }
__device__ __forceinline__ uint4 ldg_cg4(const void* p) { uint4 v; asm volatile("ld.global.cg.v4.b32 {%0,%1,%2,%3}, [%4];" : "=r"(v.x), "=r"(v.y), "=r"(v.z), "=r"(v.w) : "l"(p) : "memory"); return v; }
__device__ __forceinline__ void sts32(uint32_t a, uint32_t v) { asm volatile("st.shared.b32 [%0], %1;" ::"r"(a), "r"(v) : "memory"); }
__device__ __forceinline__ void stsm4(uint32_t a, uint32_t r0, uint32_t r1, uint32_t r2, uint32_t r3) {
  asm volatile("stmatrix.sync.aligned.m8n8.x4.shared.b16 [%0], {%1,%2,%3,%4};" ::"r"(a), "r"(r0), "r"(r1), "r"(r2), "r"(r3) : "memory");
}

__device__ __forceinline__ void stsm2(uint32_t a, uint32_t r0, uint32_t r1) {
  asm volatile("stmatrix.sync.aligned.m8n8.x2.shared.b16 [%0], {%1,%2};" ::"r"(a), "r"(r0), "r"(r1) : "memory");
}
__device__ __forceinline__ uint4 ldg_x(const void* p) {
  uint4 v;
  asm volatile("ld.global.nc.L1::no_allocate.L2::128B.v4.b32 {%0,%1,%2,%3}, [%4];" : "=r"(v.x), "=r"(v.y), "=r"(v.z), "=r"(v.w) : "l"(p));
  return v;
}
__device__ __forceinline__ float2 lds_f2(uint32_t a) { float2 v; asm volatile("ld.shared.v2.f32 {%0,%1}, [%2];" : "=f"(v.x), "=f"(v.y) : "r"(a) : "memory"); return v; }
__device__ __forceinline__ void bulk_s2g(void* dst, uint32_t src, uint32_t bytes) {
  asm volatile("cp.async.bulk.global.shared::cta.bulk_group [%0], [%1], %2;" ::"l"(dst), "r"(src), "r"(bytes) : "memory");
}

__device__ __forceinline__ void mma_n24_ss_tb(float (&d)[12], uint64_t adesc, uint64_t bdesc, int acc) {
  asm volatile("{\n.reg .pred p;\nsetp.ne.b32 p, %14, 0;\n"
      "wgmma.mma_async.sync.aligned.m64n24k16.f32.bf16.bf16 "
      "{%0,%1,%2,%3,%4,%5,%6,%7,%8,%9,%10,%11}, "
      "%12, %13, p, 1, 1, 0, 1;\n}\n"
      : "+f"(d[0]), "+f"(d[1]), "+f"(d[2]), "+f"(d[3]), "+f"(d[4]), "+f"(d[5]), "+f"(d[6]), "+f"(d[7]),
        "+f"(d[8]), "+f"(d[9]), "+f"(d[10]), "+f"(d[11])
      : "l"(adesc), "l"(bdesc), "r"(acc));
}
__device__ __forceinline__ void mma_n192_rs_tb(float (&d)[96], uint32_t a0, uint32_t a1, uint32_t a2, uint32_t a3, uint64_t bdesc, int acc) {
  asm volatile("{\n.reg .pred p;\nsetp.ne.b32 p, %101, 0;\n"
      "wgmma.mma_async.sync.aligned.m64n192k16.f32.bf16.bf16 "
      "{%0,%1,%2,%3,%4,%5,%6,%7,%8,%9,%10,%11,%12,%13,%14,%15,"
      "%16,%17,%18,%19,%20,%21,%22,%23,%24,%25,%26,%27,%28,%29,%30,%31,"
      "%32,%33,%34,%35,%36,%37,%38,%39,%40,%41,%42,%43,%44,%45,%46,%47,"
      "%48,%49,%50,%51,%52,%53,%54,%55,%56,%57,%58,%59,%60,%61,%62,%63,"
      "%64,%65,%66,%67,%68,%69,%70,%71,%72,%73,%74,%75,%76,%77,%78,%79,"
      "%80,%81,%82,%83,%84,%85,%86,%87,%88,%89,%90,%91,%92,%93,%94,%95}, "
      "{%96,%97,%98,%99}, %100, p, 1, 1, 1;\n}\n"
      : "+f"(d[0]), "+f"(d[1]), "+f"(d[2]), "+f"(d[3]), "+f"(d[4]), "+f"(d[5]), "+f"(d[6]), "+f"(d[7]),
        "+f"(d[8]), "+f"(d[9]), "+f"(d[10]), "+f"(d[11]), "+f"(d[12]), "+f"(d[13]), "+f"(d[14]), "+f"(d[15]),
        "+f"(d[16]), "+f"(d[17]), "+f"(d[18]), "+f"(d[19]), "+f"(d[20]), "+f"(d[21]), "+f"(d[22]), "+f"(d[23]),
        "+f"(d[24]), "+f"(d[25]), "+f"(d[26]), "+f"(d[27]), "+f"(d[28]), "+f"(d[29]), "+f"(d[30]), "+f"(d[31]),
        "+f"(d[32]), "+f"(d[33]), "+f"(d[34]), "+f"(d[35]), "+f"(d[36]), "+f"(d[37]), "+f"(d[38]), "+f"(d[39]),
        "+f"(d[40]), "+f"(d[41]), "+f"(d[42]), "+f"(d[43]), "+f"(d[44]), "+f"(d[45]), "+f"(d[46]), "+f"(d[47]),
        "+f"(d[48]), "+f"(d[49]), "+f"(d[50]), "+f"(d[51]), "+f"(d[52]), "+f"(d[53]), "+f"(d[54]), "+f"(d[55]),
        "+f"(d[56]), "+f"(d[57]), "+f"(d[58]), "+f"(d[59]), "+f"(d[60]), "+f"(d[61]), "+f"(d[62]), "+f"(d[63]),
        "+f"(d[64]), "+f"(d[65]), "+f"(d[66]), "+f"(d[67]), "+f"(d[68]), "+f"(d[69]), "+f"(d[70]), "+f"(d[71]),
        "+f"(d[72]), "+f"(d[73]), "+f"(d[74]), "+f"(d[75]), "+f"(d[76]), "+f"(d[77]), "+f"(d[78]), "+f"(d[79]),
        "+f"(d[80]), "+f"(d[81]), "+f"(d[82]), "+f"(d[83]), "+f"(d[84]), "+f"(d[85]), "+f"(d[86]), "+f"(d[87]),
        "+f"(d[88]), "+f"(d[89]), "+f"(d[90]), "+f"(d[91]), "+f"(d[92]), "+f"(d[93]), "+f"(d[94]), "+f"(d[95])
      : "r"(a0), "r"(a1), "r"(a2), "r"(a3), "l"(bdesc), "r"(acc));
}
__device__ __forceinline__ void mma_n128_rs_tb(float (&d)[64], uint32_t a0, uint32_t a1, uint32_t a2, uint32_t a3, uint64_t bdesc, int acc) {
  asm volatile("{\n.reg .pred p;\nsetp.ne.b32 p, %69, 0;\n"
      "wgmma.mma_async.sync.aligned.m64n128k16.f32.bf16.bf16 "
      "{%0,%1,%2,%3,%4,%5,%6,%7,%8,%9,%10,%11,%12,%13,%14,%15,"
      "%16,%17,%18,%19,%20,%21,%22,%23,%24,%25,%26,%27,%28,%29,%30,%31,"
      "%32,%33,%34,%35,%36,%37,%38,%39,%40,%41,%42,%43,%44,%45,%46,%47,"
      "%48,%49,%50,%51,%52,%53,%54,%55,%56,%57,%58,%59,%60,%61,%62,%63}, "
      "{%64,%65,%66,%67}, %68, p, 1, 1, 1;\n}\n"
      : "+f"(d[0]), "+f"(d[1]), "+f"(d[2]), "+f"(d[3]), "+f"(d[4]), "+f"(d[5]), "+f"(d[6]), "+f"(d[7]),
        "+f"(d[8]), "+f"(d[9]), "+f"(d[10]), "+f"(d[11]), "+f"(d[12]), "+f"(d[13]), "+f"(d[14]), "+f"(d[15]),
        "+f"(d[16]), "+f"(d[17]), "+f"(d[18]), "+f"(d[19]), "+f"(d[20]), "+f"(d[21]), "+f"(d[22]), "+f"(d[23]),
        "+f"(d[24]), "+f"(d[25]), "+f"(d[26]), "+f"(d[27]), "+f"(d[28]), "+f"(d[29]), "+f"(d[30]), "+f"(d[31]),
        "+f"(d[32]), "+f"(d[33]), "+f"(d[34]), "+f"(d[35]), "+f"(d[36]), "+f"(d[37]), "+f"(d[38]), "+f"(d[39]),
        "+f"(d[40]), "+f"(d[41]), "+f"(d[42]), "+f"(d[43]), "+f"(d[44]), "+f"(d[45]), "+f"(d[46]), "+f"(d[47]),
        "+f"(d[48]), "+f"(d[49]), "+f"(d[50]), "+f"(d[51]), "+f"(d[52]), "+f"(d[53]), "+f"(d[54]), "+f"(d[55]),
        "+f"(d[56]), "+f"(d[57]), "+f"(d[58]), "+f"(d[59]), "+f"(d[60]), "+f"(d[61]), "+f"(d[62]), "+f"(d[63])
      : "r"(a0), "r"(a1), "r"(a2), "r"(a3), "l"(bdesc), "r"(acc));
}
__device__ __forceinline__ void mma_n64_rs_tb(float (&d)[32], uint32_t a0, uint32_t a1, uint32_t a2, uint32_t a3, uint64_t bdesc, int acc) {
  asm volatile("{\n.reg .pred p;\nsetp.ne.b32 p, %37, 0;\n"
      "wgmma.mma_async.sync.aligned.m64n64k16.f32.bf16.bf16 "
      "{%0,%1,%2,%3,%4,%5,%6,%7,%8,%9,%10,%11,%12,%13,%14,%15,"
      "%16,%17,%18,%19,%20,%21,%22,%23,%24,%25,%26,%27,%28,%29,%30,%31}, "
      "{%32,%33,%34,%35}, %36, p, 1, 1, 1;\n}\n"
      : "+f"(d[0]), "+f"(d[1]), "+f"(d[2]), "+f"(d[3]), "+f"(d[4]), "+f"(d[5]), "+f"(d[6]), "+f"(d[7]),
        "+f"(d[8]), "+f"(d[9]), "+f"(d[10]), "+f"(d[11]), "+f"(d[12]), "+f"(d[13]), "+f"(d[14]), "+f"(d[15]),
        "+f"(d[16]), "+f"(d[17]), "+f"(d[18]), "+f"(d[19]), "+f"(d[20]), "+f"(d[21]), "+f"(d[22]), "+f"(d[23]),
        "+f"(d[24]), "+f"(d[25]), "+f"(d[26]), "+f"(d[27]), "+f"(d[28]), "+f"(d[29]), "+f"(d[30]), "+f"(d[31])
      : "r"(a0), "r"(a1), "r"(a2), "r"(a3), "l"(bdesc), "r"(acc));
}
__device__ __forceinline__ void mma_n48_rs_tb(float (&d)[24], uint32_t a0, uint32_t a1, uint32_t a2, uint32_t a3, uint64_t bdesc, int acc) {
  asm volatile("{\n.reg .pred p;\nsetp.ne.b32 p, %29, 0;\n"
      "wgmma.mma_async.sync.aligned.m64n48k16.f32.bf16.bf16 "
      "{%0,%1,%2,%3,%4,%5,%6,%7,%8,%9,%10,%11,%12,%13,%14,%15,"
      "%16,%17,%18,%19,%20,%21,%22,%23}, "
      "{%24,%25,%26,%27}, %28, p, 1, 1, 1;\n}\n"
      : "+f"(d[0]), "+f"(d[1]), "+f"(d[2]), "+f"(d[3]), "+f"(d[4]), "+f"(d[5]), "+f"(d[6]), "+f"(d[7]),
        "+f"(d[8]), "+f"(d[9]), "+f"(d[10]), "+f"(d[11]), "+f"(d[12]), "+f"(d[13]), "+f"(d[14]), "+f"(d[15]),
        "+f"(d[16]), "+f"(d[17]), "+f"(d[18]), "+f"(d[19]), "+f"(d[20]), "+f"(d[21]), "+f"(d[22]), "+f"(d[23])
      : "r"(a0), "r"(a1), "r"(a2), "r"(a3), "l"(bdesc), "r"(acc));
}
__device__ __forceinline__ void mma_n128_rs(float (&d)[64], uint32_t a0, uint32_t a1, uint32_t a2, uint32_t a3, uint64_t bdesc, int acc) {
  asm volatile("{\n.reg .pred p;\nsetp.ne.b32 p, %69, 0;\n"
      "wgmma.mma_async.sync.aligned.m64n128k16.f32.bf16.bf16 "
      "{%0,%1,%2,%3,%4,%5,%6,%7,%8,%9,%10,%11,%12,%13,%14,%15,"
      "%16,%17,%18,%19,%20,%21,%22,%23,%24,%25,%26,%27,%28,%29,%30,%31,"
      "%32,%33,%34,%35,%36,%37,%38,%39,%40,%41,%42,%43,%44,%45,%46,%47,"
      "%48,%49,%50,%51,%52,%53,%54,%55,%56,%57,%58,%59,%60,%61,%62,%63}, "
      "{%64,%65,%66,%67}, %68, p, 1, 1, 0;\n}\n"
      : "+f"(d[0]), "+f"(d[1]), "+f"(d[2]), "+f"(d[3]), "+f"(d[4]), "+f"(d[5]), "+f"(d[6]), "+f"(d[7]),
        "+f"(d[8]), "+f"(d[9]), "+f"(d[10]), "+f"(d[11]), "+f"(d[12]), "+f"(d[13]), "+f"(d[14]), "+f"(d[15]),
        "+f"(d[16]), "+f"(d[17]), "+f"(d[18]), "+f"(d[19]), "+f"(d[20]), "+f"(d[21]), "+f"(d[22]), "+f"(d[23]),
        "+f"(d[24]), "+f"(d[25]), "+f"(d[26]), "+f"(d[27]), "+f"(d[28]), "+f"(d[29]), "+f"(d[30]), "+f"(d[31]),
        "+f"(d[32]), "+f"(d[33]), "+f"(d[34]), "+f"(d[35]), "+f"(d[36]), "+f"(d[37]), "+f"(d[38]), "+f"(d[39]),
        "+f"(d[40]), "+f"(d[41]), "+f"(d[42]), "+f"(d[43]), "+f"(d[44]), "+f"(d[45]), "+f"(d[46]), "+f"(d[47]),
        "+f"(d[48]), "+f"(d[49]), "+f"(d[50]), "+f"(d[51]), "+f"(d[52]), "+f"(d[53]), "+f"(d[54]), "+f"(d[55]),
        "+f"(d[56]), "+f"(d[57]), "+f"(d[58]), "+f"(d[59]), "+f"(d[60]), "+f"(d[61]), "+f"(d[62]), "+f"(d[63])
      : "r"(a0), "r"(a1), "r"(a2), "r"(a3), "l"(bdesc), "r"(acc));
}
__device__ __forceinline__ void mma_n64_rs(float (&d)[32], uint32_t a0, uint32_t a1, uint32_t a2, uint32_t a3, uint64_t bdesc, int acc) {
  asm volatile("{\n.reg .pred p;\nsetp.ne.b32 p, %37, 0;\n"
      "wgmma.mma_async.sync.aligned.m64n64k16.f32.bf16.bf16 "
      "{%0,%1,%2,%3,%4,%5,%6,%7,%8,%9,%10,%11,%12,%13,%14,%15,"
      "%16,%17,%18,%19,%20,%21,%22,%23,%24,%25,%26,%27,%28,%29,%30,%31}, "
      "{%32,%33,%34,%35}, %36, p, 1, 1, 0;\n}\n"
      : "+f"(d[0]), "+f"(d[1]), "+f"(d[2]), "+f"(d[3]), "+f"(d[4]), "+f"(d[5]), "+f"(d[6]), "+f"(d[7]),
        "+f"(d[8]), "+f"(d[9]), "+f"(d[10]), "+f"(d[11]), "+f"(d[12]), "+f"(d[13]), "+f"(d[14]), "+f"(d[15]),
        "+f"(d[16]), "+f"(d[17]), "+f"(d[18]), "+f"(d[19]), "+f"(d[20]), "+f"(d[21]), "+f"(d[22]), "+f"(d[23]),
        "+f"(d[24]), "+f"(d[25]), "+f"(d[26]), "+f"(d[27]), "+f"(d[28]), "+f"(d[29]), "+f"(d[30]), "+f"(d[31])
      : "r"(a0), "r"(a1), "r"(a2), "r"(a3), "l"(bdesc), "r"(acc));
}
__device__ __forceinline__ void mma_n128_ss(float (&d)[64], uint64_t adesc, uint64_t bdesc, int acc) {
  asm volatile("{\n.reg .pred p;\nsetp.ne.b32 p, %66, 0;\n"
      "wgmma.mma_async.sync.aligned.m64n128k16.f32.bf16.bf16 "
      "{%0,%1,%2,%3,%4,%5,%6,%7,%8,%9,%10,%11,%12,%13,%14,%15,"
      "%16,%17,%18,%19,%20,%21,%22,%23,%24,%25,%26,%27,%28,%29,%30,%31,"
      "%32,%33,%34,%35,%36,%37,%38,%39,%40,%41,%42,%43,%44,%45,%46,%47,"
      "%48,%49,%50,%51,%52,%53,%54,%55,%56,%57,%58,%59,%60,%61,%62,%63}, "
      "%64, %65, p, 1, 1, 0, 0;\n}\n"
      : "+f"(d[0]), "+f"(d[1]), "+f"(d[2]), "+f"(d[3]), "+f"(d[4]), "+f"(d[5]), "+f"(d[6]), "+f"(d[7]),
        "+f"(d[8]), "+f"(d[9]), "+f"(d[10]), "+f"(d[11]), "+f"(d[12]), "+f"(d[13]), "+f"(d[14]), "+f"(d[15]),
        "+f"(d[16]), "+f"(d[17]), "+f"(d[18]), "+f"(d[19]), "+f"(d[20]), "+f"(d[21]), "+f"(d[22]), "+f"(d[23]),
        "+f"(d[24]), "+f"(d[25]), "+f"(d[26]), "+f"(d[27]), "+f"(d[28]), "+f"(d[29]), "+f"(d[30]), "+f"(d[31]),
        "+f"(d[32]), "+f"(d[33]), "+f"(d[34]), "+f"(d[35]), "+f"(d[36]), "+f"(d[37]), "+f"(d[38]), "+f"(d[39]),
        "+f"(d[40]), "+f"(d[41]), "+f"(d[42]), "+f"(d[43]), "+f"(d[44]), "+f"(d[45]), "+f"(d[46]), "+f"(d[47]),
        "+f"(d[48]), "+f"(d[49]), "+f"(d[50]), "+f"(d[51]), "+f"(d[52]), "+f"(d[53]), "+f"(d[54]), "+f"(d[55]),
        "+f"(d[56]), "+f"(d[57]), "+f"(d[58]), "+f"(d[59]), "+f"(d[60]), "+f"(d[61]), "+f"(d[62]), "+f"(d[63])
      : "l"(adesc), "l"(bdesc), "r"(acc));
}
__device__ __forceinline__ void mma_n160_ss_tb(float (&d)[80], uint64_t adesc, uint64_t bdesc, int acc) {
  asm volatile("{\n.reg .pred p;\nsetp.ne.b32 p, %82, 0;\n"
      "wgmma.mma_async.sync.aligned.m64n160k16.f32.bf16.bf16 "
      "{%0,%1,%2,%3,%4,%5,%6,%7,%8,%9,%10,%11,%12,%13,%14,%15,"
      "%16,%17,%18,%19,%20,%21,%22,%23,%24,%25,%26,%27,%28,%29,%30,%31,"
      "%32,%33,%34,%35,%36,%37,%38,%39,%40,%41,%42,%43,%44,%45,%46,%47,"
      "%48,%49,%50,%51,%52,%53,%54,%55,%56,%57,%58,%59,%60,%61,%62,%63,"
      "%64,%65,%66,%67,%68,%69,%70,%71,%72,%73,%74,%75,%76,%77,%78,%79}, "
      "%80, %81, p, 1, 1, 0, 1;\n}\n"
      : "+f"(d[0]), "+f"(d[1]), "+f"(d[2]), "+f"(d[3]), "+f"(d[4]), "+f"(d[5]), "+f"(d[6]), "+f"(d[7]),
        "+f"(d[8]), "+f"(d[9]), "+f"(d[10]), "+f"(d[11]), "+f"(d[12]), "+f"(d[13]), "+f"(d[14]), "+f"(d[15]),
        "+f"(d[16]), "+f"(d[17]), "+f"(d[18]), "+f"(d[19]), "+f"(d[20]), "+f"(d[21]), "+f"(d[22]), "+f"(d[23]),
        "+f"(d[24]), "+f"(d[25]), "+f"(d[26]), "+f"(d[27]), "+f"(d[28]), "+f"(d[29]), "+f"(d[30]), "+f"(d[31]),
        "+f"(d[32]), "+f"(d[33]), "+f"(d[34]), "+f"(d[35]), "+f"(d[36]), "+f"(d[37]), "+f"(d[38]), "+f"(d[39]),
        "+f"(d[40]), "+f"(d[41]), "+f"(d[42]), "+f"(d[43]), "+f"(d[44]), "+f"(d[45]), "+f"(d[46]), "+f"(d[47]),
        "+f"(d[48]), "+f"(d[49]), "+f"(d[50]), "+f"(d[51]), "+f"(d[52]), "+f"(d[53]), "+f"(d[54]), "+f"(d[55]),
        "+f"(d[56]), "+f"(d[57]), "+f"(d[58]), "+f"(d[59]), "+f"(d[60]), "+f"(d[61]), "+f"(d[62]), "+f"(d[63]),
        "+f"(d[64]), "+f"(d[65]), "+f"(d[66]), "+f"(d[67]), "+f"(d[68]), "+f"(d[69]), "+f"(d[70]), "+f"(d[71]),
        "+f"(d[72]), "+f"(d[73]), "+f"(d[74]), "+f"(d[75]), "+f"(d[76]), "+f"(d[77]), "+f"(d[78]), "+f"(d[79])
      : "l"(adesc), "l"(bdesc), "r"(acc));
}
__device__ __forceinline__ void mma_n80_rs_tb(float (&d)[40], uint32_t a0, uint32_t a1, uint32_t a2, uint32_t a3, uint64_t bdesc, int acc) {
  asm volatile("{\n.reg .pred p;\nsetp.ne.b32 p, %45, 0;\n"
      "wgmma.mma_async.sync.aligned.m64n80k16.f32.bf16.bf16 "
      "{%0,%1,%2,%3,%4,%5,%6,%7,%8,%9,%10,%11,%12,%13,%14,%15,"
      "%16,%17,%18,%19,%20,%21,%22,%23,%24,%25,%26,%27,%28,%29,%30,%31,"
      "%32,%33,%34,%35,%36,%37,%38,%39}, "
      "{%40,%41,%42,%43}, %44, p, 1, 1, 1;\n}\n"
      : "+f"(d[0]), "+f"(d[1]), "+f"(d[2]), "+f"(d[3]), "+f"(d[4]), "+f"(d[5]), "+f"(d[6]), "+f"(d[7]),
        "+f"(d[8]), "+f"(d[9]), "+f"(d[10]), "+f"(d[11]), "+f"(d[12]), "+f"(d[13]), "+f"(d[14]), "+f"(d[15]),
        "+f"(d[16]), "+f"(d[17]), "+f"(d[18]), "+f"(d[19]), "+f"(d[20]), "+f"(d[21]), "+f"(d[22]), "+f"(d[23]),
        "+f"(d[24]), "+f"(d[25]), "+f"(d[26]), "+f"(d[27]), "+f"(d[28]), "+f"(d[29]), "+f"(d[30]), "+f"(d[31]),
        "+f"(d[32]), "+f"(d[33]), "+f"(d[34]), "+f"(d[35]), "+f"(d[36]), "+f"(d[37]), "+f"(d[38]), "+f"(d[39])
      : "r"(a0), "r"(a1), "r"(a2), "r"(a3), "l"(bdesc), "r"(acc));
}
__device__ __forceinline__ void mma_n80_ss_tb(float (&d)[40], uint64_t adesc, uint64_t bdesc, int acc) {
  asm volatile("{\n.reg .pred p;\nsetp.ne.b32 p, %42, 0;\n"
      "wgmma.mma_async.sync.aligned.m64n80k16.f32.bf16.bf16 "
      "{%0,%1,%2,%3,%4,%5,%6,%7,%8,%9,%10,%11,%12,%13,%14,%15,"
      "%16,%17,%18,%19,%20,%21,%22,%23,%24,%25,%26,%27,%28,%29,%30,%31,"
      "%32,%33,%34,%35,%36,%37,%38,%39}, "
      "%40, %41, p, 1, 1, 0, 1;\n}\n"
      : "+f"(d[0]), "+f"(d[1]), "+f"(d[2]), "+f"(d[3]), "+f"(d[4]), "+f"(d[5]), "+f"(d[6]), "+f"(d[7]),
        "+f"(d[8]), "+f"(d[9]), "+f"(d[10]), "+f"(d[11]), "+f"(d[12]), "+f"(d[13]), "+f"(d[14]), "+f"(d[15]),
        "+f"(d[16]), "+f"(d[17]), "+f"(d[18]), "+f"(d[19]), "+f"(d[20]), "+f"(d[21]), "+f"(d[22]), "+f"(d[23]),
        "+f"(d[24]), "+f"(d[25]), "+f"(d[26]), "+f"(d[27]), "+f"(d[28]), "+f"(d[29]), "+f"(d[30]), "+f"(d[31]),
        "+f"(d[32]), "+f"(d[33]), "+f"(d[34]), "+f"(d[35]), "+f"(d[36]), "+f"(d[37]), "+f"(d[38]), "+f"(d[39])
      : "l"(adesc), "l"(bdesc), "r"(acc));
}
__device__ __forceinline__ void mma_n24_rs_tb(float (&d)[12], uint32_t a0, uint32_t a1, uint32_t a2, uint32_t a3, uint64_t bdesc, int acc) {
  asm volatile("{\n.reg .pred p;\nsetp.ne.b32 p, %17, 0;\n"
      "wgmma.mma_async.sync.aligned.m64n24k16.f32.bf16.bf16 "
      "{%0,%1,%2,%3,%4,%5,%6,%7,%8,%9,%10,%11}, "
      "{%12,%13,%14,%15}, %16, p, 1, 1, 1;\n}\n"
      : "+f"(d[0]), "+f"(d[1]), "+f"(d[2]), "+f"(d[3]), "+f"(d[4]), "+f"(d[5]), "+f"(d[6]), "+f"(d[7]),
        "+f"(d[8]), "+f"(d[9]), "+f"(d[10]), "+f"(d[11])
      : "r"(a0), "r"(a1), "r"(a2), "r"(a3), "l"(bdesc), "r"(acc));
}
__device__ __forceinline__ void mma_n24_ss_tatb(float (&d)[12], uint64_t adesc, uint64_t bdesc, int acc) {
  asm volatile("{\n.reg .pred p;\nsetp.ne.b32 p, %14, 0;\n"
      "wgmma.mma_async.sync.aligned.m64n24k16.f32.bf16.bf16 "
      "{%0,%1,%2,%3,%4,%5,%6,%7,%8,%9,%10,%11}, "
      "%12, %13, p, 1, 1, 1, 1;\n}\n"
      : "+f"(d[0]), "+f"(d[1]), "+f"(d[2]), "+f"(d[3]), "+f"(d[4]), "+f"(d[5]), "+f"(d[6]), "+f"(d[7]),
        "+f"(d[8]), "+f"(d[9]), "+f"(d[10]), "+f"(d[11])
      : "l"(adesc), "l"(bdesc), "r"(acc));
}

constexpr int W_STAGE = 30720, W_NST = 5;
constexpr int KV_CHUNK = 12288, KV_SLOT = 2 * KV_CHUNK;
constexpr int O_STAGE = 36864;
constexpr int OFF_AK = 2 * KV_SLOT;
constexpr int OFF_PHK = 4 * KV_SLOT;
constexpr int OFF_KVS = OFF_PHK + 2 * 10240 + 4096;
constexpr int OFF_GATE = 112640;
constexpr int OFF_Q = W_NST * W_STAGE;
constexpr int OFF_V = OFF_Q + 24576;
constexpr int OFF_AQ = OFF_V + 24576;
constexpr int OFF_WPH = OFF_AQ + 24576;
constexpr int OFF_BAR = OFF_WPH + 4608;
constexpr int B_WF = 0, B_WE = 40, B_KF = 80, B_KE = 112, B_OF = 208, B_OE = 248, B_RF = 288, B_Z = 296, B_G = 304, B_X = 312, B_P1 = 320, B_R = 328;
constexpr int OFF_MISC = OFF_BAR + 336;
constexpr int SMEM_BYTES = OFF_MISC + 32 + 128;
__device__ __forceinline__ int o_buf(int it) { return it % 5; }
__device__ __forceinline__ int o_use(int it) { return it / 5; }
__device__ __forceinline__ uint32_t o_stage(int s) { return s == 0 ? OFF_V : s == 1 ? OFF_Q - O_STAGE : (s - 2) * O_STAGE; }
__device__ __forceinline__ uint32_t o_stage_a(int s) { return s == 4 ? OFF_V + O_STAGE : o_stage(s); }
constexpr int NB_STAGED = 1, NB_FREE = 2, NB_WG = 3, NB_BG = 7, NB_EPI = 15, NB_PHIK = 8, NB_TAIL = 9, NB_READ = 10, NB_LAST = 11, NB_HELP = 12;

template <int SEC, int J, int HF>
__device__ __forceinline__ float2 grp(const float (&a1)[2][64], const float (&a2)[24]) {
  constexpr int S = SEC & 3, J1 = (SEC & 4) ? J - 2 : J, J2 = (SEC & 4) ? J : J - 8;
  if constexpr (J1 >= 0 && J1 < 8) return make_float2(a1[S >> 1][(8 * (S & 1) + J1) * 4 + 2 * HF], a1[S >> 1][(8 * (S & 1) + J1) * 4 + 2 * HF + 1]);
  else return make_float2(a2[(2 * S + J2) * 4 + 2 * HF], a2[(2 * S + J2) * 4 + 2 * HF + 1]);
}
__device__ __forceinline__ float sq2(float2 v) { return fmaf(v.x, v.x, v.y * v.y); }
__device__ __forceinline__ uint32_t pks(float2 v, float s) { return packbf(v.x * s, v.y * s); }

template <int SEC, int PR>
__device__ __forceinline__ void norms(const float (&a1)[2][64], const float (&a2)[24], int t, float (&n)[2][2]) {
  const float h0 = sq2(grp<SEC, 5 * PR + 2, 0>(a1, a2)), h1 = sq2(grp<SEC, 5 * PR + 2, 1>(a1, a2));
  n[0][0] = sq2(grp<SEC, 5 * PR, 0>(a1, a2)) + sq2(grp<SEC, 5 * PR + 1, 0>(a1, a2)) + (t < 2 ? h0 : 0.f);
  n[0][1] = sq2(grp<SEC, 5 * PR, 1>(a1, a2)) + sq2(grp<SEC, 5 * PR + 1, 1>(a1, a2)) + (t < 2 ? h1 : 0.f);
  n[1][0] = sq2(grp<SEC, 5 * PR + 3, 0>(a1, a2)) + sq2(grp<SEC, 5 * PR + 4, 0>(a1, a2)) + (t < 2 ? 0.f : h0);
  n[1][1] = sq2(grp<SEC, 5 * PR + 3, 1>(a1, a2)) + sq2(grp<SEC, 5 * PR + 4, 1>(a1, a2)) + (t < 2 ? 0.f : h1);
#pragma unroll
  for (int i = 0; i < 4; i++) n[i >> 1][i & 1] += __shfl_xor_sync(~0u, n[i >> 1][i & 1], 1);
#pragma unroll
  for (int i = 0; i < 4; i++) n[i >> 1][i & 1] += __shfl_xor_sync(~0u, n[i >> 1][i & 1], 2);
}

template <int SEC, int PR>
__device__ __forceinline__ void stage_pair(const float (&a1)[2][64], const float (&a2)[24], float sc0, float sc1, float sm, uint32_t xe0, uint32_t xe1,
                                           uint32_t xo0, uint32_t xo1, uint32_t ad01, uint32_t ad2, int t) {
  const uint32_t off = 2 * PR * 3072;
  stsm4(ad01 + off, pks(grp<SEC, 5 * PR, 0>(a1, a2), sc0), pks(grp<SEC, 5 * PR, 1>(a1, a2), sc1), pks(grp<SEC, 5 * PR + 1, 0>(a1, a2), sc0),
        pks(grp<SEC, 5 * PR + 1, 1>(a1, a2), sc1));
  stsm4(ad01 + off + 3072, pks(grp<SEC, 5 * PR + 3, 0>(a1, a2), sc0), pks(grp<SEC, 5 * PR + 3, 1>(a1, a2), sc1),
        pks(grp<SEC, 5 * PR + 4, 0>(a1, a2), sc0), pks(grp<SEC, 5 * PR + 4, 1>(a1, a2), sc1));
  const uint32_t m0 = pks(grp<SEC, 5 * PR + 2, 0>(a1, a2), sc0 * sm), m1 = pks(grp<SEC, 5 * PR + 2, 1>(a1, a2), sc1 * sm);
  const bool lo = t < 2;
  stsm4(ad2 + off, lo ? m0 : xe0, lo ? m1 : xe1, lo ? xo0 : m0, lo ? xo1 : m1);
}

template <bool EXACT>
__device__ __forceinline__ void hedgehog(const float (&p)[12], uint32_t (&f)[10], int t) {
  const bool lo = t < 2;
#pragma unroll
  for (int hf = 0; hf < 2; hf++) {
    const float v[6] = {p[2 * hf], p[2 * hf + 1], p[4 + 2 * hf], p[5 + 2 * hf], p[8 + 2 * hf], p[9 + 2 * hf]};
    float bp = 0.f, bn = 0.f;
    if (EXACT) {
      float mx = fmaxf(fmaxf(fmaxf(v[0], v[1]), fmaxf(v[2], v[3])), fmaxf(v[4], v[5]));
      float mn = fminf(fminf(fminf(v[0], v[1]), fminf(v[2], v[3])), fminf(v[4], v[5]));
      mx = fmaxf(mx, __shfl_xor_sync(~0u, mx, 1)); mn = fminf(mn, __shfl_xor_sync(~0u, mn, 1));
      mx = fmaxf(mx, __shfl_xor_sync(~0u, mx, 2)); mn = fminf(mn, __shfl_xor_sync(~0u, mn, 2));
      bp = -mx * LOG2E; bn = mn * LOG2E;
    }
    float ep[4], en[4];
#pragma unroll
    for (int i = 0; i < 4; i++) ep[i] = ex2(fmaf(v[i], LOG2E, bp));
    if (EXACT || !PAIRINV) {
#pragma unroll
      for (int i = 0; i < 4; i++) en[i] = ex2(fmaf(v[i], -LOG2E, bn));
    } else {
      const float r0 = rcp(ep[0] * ep[1]), r1 = rcp(ep[2] * ep[3]);
      en[0] = r0 * ep[1]; en[1] = r0 * ep[0]; en[2] = r1 * ep[3]; en[3] = r1 * ep[2];
    }
    const float sg = lo ? LOG2E : -LOG2E, bm = lo ? bp : bn;
    const float m0 = ex2(fmaf(v[4], sg, bm)), m1 = ex2(fmaf(v[5], sg, bm)), ms = m0 + m1;
    float sp = (ep[0] + ep[1]) + (ep[2] + ep[3]) + (lo ? ms : 0.f);
    float sn = (en[0] + en[1]) + (en[2] + en[3]) + (lo ? 0.f : ms);
    sp += __shfl_xor_sync(~0u, sp, 1); sn += __shfl_xor_sync(~0u, sn, 1);
    sp += __shfl_xor_sync(~0u, sp, 2); sn += __shfl_xor_sync(~0u, sn, 2);
    const float r = rcp(sp * sn), rp = r * sn, rn = r * sp, rm = lo ? rp : rn;
    f[0 + hf] = packbf(ep[0] * rp, ep[1] * rp);
    f[2 + hf] = packbf(ep[2] * rp, ep[3] * rp);
    f[4 + hf] = packbf(m0 * rm, m1 * rm);
    f[6 + hf] = packbf(en[0] * rn, en[1] * rn);
    f[8 + hf] = packbf(en[2] * rn, en[3] * rn);
  }
}
__device__ __forceinline__ void hedgehog1(const float (&p)[12], uint32_t (&f)[10], int t) {
  float m[2] = {fabsf(p[0]), fabsf(p[6])};
#pragma unroll
  for (int i = 1; i < 6; i++) { m[0] = fmaxf(m[0], fabsf(p[i])); m[1] = fmaxf(m[1], fabsf(p[6 + i])); }
  if (__all_sync(~0u, fmaxf(m[0], m[1]) <= 27.f)) hedgehog<false>(p, f, t);
  else hedgehog<true>(p, f, t);
}

template <int O>
__device__ __forceinline__ void epilogue0(const float (&a1)[2][64], const float (&a2)[24], int rg, int lane, uint32_t ad01, uint32_t ad2, uint32_t kmx) {
  const int t = lane & 3;
  const bool p0 = (POLY_MASK >> rg) & 1, p1 = (POLY_MASK >> (rg + 1)) & 1;
  const uint32_t kp = (t & 1) ? 0u : (BF_ONE | (BF_MAGIC << 16)), km = (t & 1) ? BF_MU_LO : (BF_ONE | (BF_MU_HI << 16));
  const uint32_t vp = (t & 1) ? 0u : (BF_ONE | 0x8000u), vm = (t & 1) ? 0u : BF_ONE;
  const uint32_t k0 = p0 ? kp : km, k1 = p1 ? kp : km, v0 = p0 ? vp : vm, v1 = p1 ? vp : vm;
  const float s0 = p0 ? -1.f : 1.f, s1 = p1 ? -1.f : 1.f;
  stage_pair<O + 0, 0>(a1, a2, 1.f, 1.f, 1.f, k0, k1, k0, k1, ad01 + OFF_Q, ad2 + OFF_Q, t);
  stage_pair<O + 0, 1>(a1, a2, 1.f, 1.f, 1.f, k0, k1, k0, k1, ad01 + OFF_Q, ad2 + OFF_Q, t);
  stage_pair<O + 1, 0>(a1, a2, s0, s1, 1.f, v0, v1, v0, v1, ad01 + OFF_V, ad2 + OFF_V, t);
  stage_pair<O + 1, 1>(a1, a2, s0, s1, 1.f, v0, v1, v0, v1, ad01 + OFF_V, ad2 + OFF_V, t);
  stage_pair<O + 2, 0>(a1, a2, 1.f, 1.f, 0.5f, 0u, 0u, 0u, 0u, ad01 + OFF_AQ, ad2 + OFF_AQ, t);
  stage_pair<O + 2, 1>(a1, a2, 1.f, 1.f, 0.5f, 0u, 0u, 0u, 0u, ad01 + OFF_AQ, ad2 + OFF_AQ, t);
  float n0[2][2], n1[2][2];
  norms<O + 0, 0>(a1, a2, t, n0);
  norms<O + 0, 1>(a1, a2, t, n1);
  const uint32_t m0 = __reduce_max_sync(~0u, __float_as_uint(fmaxf(n0[0][0], n0[0][1])));
  const uint32_t m1 = __reduce_max_sync(~0u, __float_as_uint(fmaxf(n0[1][0], n0[1][1])));
  const uint32_t m2 = __reduce_max_sync(~0u, __float_as_uint(fmaxf(n1[0][0], n1[0][1])));
  const uint32_t m3 = __reduce_max_sync(~0u, __float_as_uint(fmaxf(n1[1][0], n1[1][1])));
  if (lane < 4) asm volatile("red.shared.max.u32 [%0], %1;" ::"r"(kmx + lane * 4), "r"(lane == 0 ? m0 : lane == 1 ? m1 : lane == 2 ? m2 : m3) : "memory");
}

template <int O>
__device__ __forceinline__ bool epilogue1a(const float (&a1)[2][64], const float (&a2)[24], uint32_t (&xq)[4][2], const uint8_t* smem, int wg, int t,
                                           uint32_t ad01, uint32_t ad2) {
  stage_pair<O + 0, 0>(a1, a2, 1.f, 1.f, 0.5f, 0u, 0u, 0u, 0u, ad01 + OFF_AK + wg * 12288, ad2 + OFF_AK + wg * 12288, t);
  stage_pair<O + 0, 1>(a1, a2, 1.f, 1.f, 0.5f, 0u, 0u, 0u, 0u, ad01 + OFF_AK + wg * 12288, ad2 + OFF_AK + wg * 12288, t);
  float n0[2][2], n1[2][2];
  norms<O + 2, 0>(a1, a2, t, n0);
  norms<O + 2, 1>(a1, a2, t, n1);
  const float4 km = *(const float4*)(smem + OFF_MISC);
  const float b[4][2] = {{sqrt_ap(n0[0][0]) * km.x, sqrt_ap(n0[0][1]) * km.x}, {sqrt_ap(n0[1][0]) * km.y, sqrt_ap(n0[1][1]) * km.y},
                         {sqrt_ap(n1[0][0]) * km.z, sqrt_ap(n1[0][1]) * km.z}, {sqrt_ap(n1[1][0]) * km.w, sqrt_ap(n1[1][1]) * km.w}};
  bool unsafe = false;
#pragma unroll
  for (int i = 0; i < 8; i++) unsafe |= !(b[i >> 1][i & 1] <= FAST_BOUND);
  uint32_t any;
  asm volatile("{\n.reg .pred p, q;\nsetp.ne.u32 p, %1, 0;\nbar.red.or.pred q, %2, 128, p;\nselp.u32 %0, 1, 0, q;\n}\n"
               : "=r"(any) : "r"((uint32_t)unsafe), "r"(NB_WG + wg) : "memory");
  const bool slow = __any_sync(~0u, any);
#pragma unroll
  for (int i = 0; i < 8; i++) xq[i >> 1][i & 1] = slow ? 0u : ((t & 1) ? BF_ONE : packbf(-b[i >> 1][i & 1], 1.f));
  return slow;
}
template <int O>
__device__ __forceinline__ void epilogue1b(const float (&a1)[2][64], const float (&a2)[24], const uint32_t (&xq)[4][2], int t, uint32_t ad01, uint32_t ad2) {
  stage_pair<O + 2, 0>(a1, a2, QSCALE, QSCALE, 1.f, xq[0][0], xq[0][1], xq[1][0], xq[1][1], ad01 + OFF_Q, ad2 + OFF_Q, t);
  stage_pair<O + 2, 1>(a1, a2, QSCALE, QSCALE, 1.f, xq[2][0], xq[2][1], xq[3][0], xq[3][1], ad01 + OFF_Q, ad2 + OFF_Q, t);
  const uint32_t one = (t & 1) ? 0u : BF_ONE;
  stage_pair<O + 1, 0>(a1, a2, 1.f, 1.f, 1.f, one, one, one, one, ad01 + OFF_V, ad2 + OFF_V, t);
  stage_pair<O + 1, 1>(a1, a2, 1.f, 1.f, 1.f, one, one, one, one, ad01 + OFF_V, ad2 + OFF_V, t);
}

__device__ __forceinline__ void issue_proj(float (&p)[12], uint32_t img, uint32_t wph) {
  mma_n24_ss_tb(p, mkdesc(img, 128, 384, 0), mkdesc(wph, 384, 128, 0), 0);
  mma_n24_ss_tb(p, mkdesc(img + 256, 0, 384, 0), mkdesc(wph + 768, 0, 128, 0), 1);
}

__device__ __forceinline__ uint32_t exp2_bits(float y0, float y1, uint32_t cm, uint32_t neg1) {
  uint32_t w, m, r;
  asm("prmt.b32 %0, %1, %2, 0x6521;" : "=r"(w) : "f"(y0), "f"(y1));
  asm("lop3.b32 %0, %1, 0x007F007F, %2, 0xEA;" : "=r"(m) : "r"(w), "r"(cm));
  const uint32_t e = m * neg1 + w;
  asm("fma.rn.bf16x2 %0, %1, %2, %3;" : "=r"(r) : "r"(w), "r"(m), "r"(e));
  return r;
}
template <int HI>
__device__ __forceinline__ void exp_tile(const float (&s)[32], uint32_t (&p)[16], uint32_t cm, uint32_t neg1) {
#pragma unroll
  for (int g = 0; g < 8; g++) {
    if ((POLY_MASK >> (g + 8 * HI)) & 1) {
      p[2 * g] = exp2_bits(s[4 * g], s[4 * g + 1], cm, neg1);
      p[2 * g + 1] = exp2_bits(s[4 * g + 2], s[4 * g + 3], cm, neg1);
    } else {
      p[2 * g] = packbf(ex2(s[4 * g]), ex2(s[4 * g + 1]));
      p[2 * g + 1] = packbf(ex2(s[4 * g + 2]), ex2(s[4 * g + 3]));
    }
  }
}
struct AttnDesc { uint64_t k, k2, v; };
__device__ __forceinline__ void issue_qk(float (&s)[32], const uint32_t (&q)[6], const AttnDesc& d, uint32_t ko) {
  mma_n64_rs(s, q[0], q[1], q[2], q[3], d.k + ko, 0);
  mma_n64_rs(s, q[4], q[5], 0u, 0u, d.k2 + ko, 1);
}
__device__ __forceinline__ void issue_pv(float (&o)[12], const uint32_t (&p)[16], uint64_t vd, int acc) {
#pragma unroll
  for (int kk = 0; kk < 4; kk++) mma_n24_rs_tb(o, p[4 * kk], p[4 * kk + 1], p[4 * kk + 2], p[4 * kk + 3], vd + kk * 48, acc | kk);
}
__device__ __forceinline__ void load_q(uint32_t (&q)[6], uint32_t a) {
#pragma unroll
  for (int i = 0; i < 6; i++) asm volatile("ld.shared.b32 %0, [%1];" : "=r"(q[i]) : "r"(a + (i >> 1) * 128 + (i & 1) * 384) : "memory");
}
template <int SL>
__device__ __forceinline__ void attn_chunk(float (&s)[32], uint32_t (&p0)[16], uint32_t (&p1)[16], float (&o)[12], const uint32_t (&q)[6],
                                           const AttnDesc& d, int acc, uint32_t full_next, uint32_t ph_next,
                                           uint32_t bars, uint32_t release, uint32_t cm, uint32_t neg1) {
  exp_tile<0>(s, p0, cm, neg1);
  wg_fence();
  issue_qk(s, q, d, SL * 1536 + 192);
  wg_commit();
  issue_pv(o, p0, d.v + SL * 1536, acc);
  wg_commit();
  wg_wait<1>();
  pin(s); pin(p1);
  mbar_arrive_if(bars + B_KE + 8 * ((SL + 3) & 3), release);
  const uint32_t ready = mbar_test(full_next, ph_next);
  exp_tile<1>(s, p1, cm, neg1);
  pin(p1);
  if (!__all_sync(~0u, ready)) mbar_wait_u(full_next, ph_next);
  wg_fence();
  issue_qk(s, q, d, ((SL + 1) & 3) * 1536);
  wg_commit();
  issue_pv(o, p1, d.v + SL * 1536 + 192, 1);
  wg_commit();
  wg_wait<1>();
  pin(s); pin(p0);
}
__device__ __forceinline__ int bgroup(int G) {
  const int hg = G / 10, j = G % 10;
  return (hg >> 2) * 40 + (j / 5) * 20 + (hg & 3) * 5 + j % 5;
}
__device__ __forceinline__ void stage_o(const float (&o)[12], int odd, uint32_t pair, int w4, int lane, float eps, float s0, float s1) {
  const int src = (lane & ~3) | (odd ? 0 : 2);
  const float l0 = __shfl_sync(~0u, o[8], src) + eps, l1 = __shfl_sync(~0u, o[10], src) + eps;
  const float r0 = s0 * rcp(l0), r1 = s1 * rcp(l1);
  const uint32_t base = pair + w4 * 256;
  stsm4(base + (odd ? 3072 : 0) + (lane >> 4) * 1024 + (lane & 15) * 16, packbf(o[0] * r0, o[1] * r0), packbf(o[2] * r1, o[3] * r1),
        packbf(o[4] * r0, o[5] * r0), packbf(o[6] * r1, o[7] * r1));
  if (((lane & 3) < 2) != (odd != 0)) {
    sts32(base + 2048 + lane * 4, packbf(o[8] * r0, o[9] * r0));
    sts32(base + 2048 + 128 + lane * 4, packbf(o[10] * r1, o[11] * r1));
  }
}
__device__ __forceinline__ void readout_head(float (&p)[12], float (&pn)[12], uint32_t img_next, uint32_t wph_next, uint32_t kvs, int odd,
                                             uint32_t pair, int w4, int lane, float g0, float g1) {
  uint32_t f[10];
  hedgehog1(p, f, lane & 3);
  pin(f);
  const uint64_t kvd = mkdesc(kvs, 384, 128, 0);
  wg_fence();
  mma_n24_rs_tb(p, f[0], f[1], f[2], f[3], kvd, 0);
  mma_n24_rs_tb(p, f[4], f[5], f[6], f[7], kvd + 48, 1);
  mma_n24_rs_tb(p, f[8], f[9], 0u, 0u, mkdesc(kvs + 1536, 0, 128, 0), 1);
  issue_proj(pn, img_next, wph_next);
  wg_commit();
  wg_wait<0>();
  pin(p); pin(pn); pin(f);
  stage_o(p, odd, pair, w4, lane, 1e-6f, g0, g1);
}

struct Maps { CUtensorMap a64, a16, b64, b16, out; };

template <bool MC>
__device__ __forceinline__ void w_load(const Maps& m, int it, uint32_t d, uint32_t b, int hg, int rank) {
  const int kb = (it % 10) * 2 + rank, c = hg * 80 + (hg & 1) * 16, c2 = hg * 80 + ((hg & 1) ? 0 : 64);
  const bool w0 = it < 10;
  const CUtensorMap *p64 = w0 ? &m.b64 : &m.a64, *q64 = w0 ? &m.a64 : &m.b64, *p16 = w0 ? &m.b16 : &m.a16, *q16 = w0 ? &m.a16 : &m.b16;
  const uint32_t d1 = d + rank * 4096, d2 = d + 24576 + rank * 1024;
  tma5<MC>(d1, p64, 640 + c, kb, b);
  tma5<MC>(d1 + 8192, p64, 1280 + c, kb, b);
  tma5<MC>(d1 + 16384, q64, c, kb, b);
  tma5<MC>(d2, p16, 640 + c2, kb, b);
  tma5<MC>(d2 + 2048, p16, 1280 + c2, kb, b);
  tma5<MC>(d2 + 4096, q16, c2, kb, b);
}
__device__ __forceinline__ void x_load(uint4 (&v)[4], const uint8_t* p, int it) {
  const uint8_t* q = p + (it % 10) * 128;
  v[0] = ldg_x(q); v[1] = ldg_x(q + 8 * 1280); v[2] = ldg_x(q + 64); v[3] = ldg_x(q + 8 * 1280 + 64);
}
__device__ __forceinline__ void gemm_step(float (&a1)[2][64], float (&a2)[24], uint4 (&xv)[4], uint32_t (&f)[4][4], uint32_t (&fp)[4][4],
                                          const uint8_t* xp, int it, int acc, uint32_t sb, uint32_t bars, uint32_t lead) {
  const int s = it % W_NST;
  const uint32_t z = mbar_test(bars + B_Z, 1) - 1;
  f[0][0] = xv[0].x ^ z; f[0][1] = xv[1].x ^ z; f[0][2] = xv[0].y ^ z; f[0][3] = xv[1].y ^ z;
  f[1][0] = xv[0].z ^ z; f[1][1] = xv[1].z ^ z; f[1][2] = xv[0].w ^ z; f[1][3] = xv[1].w ^ z;
  f[2][0] = xv[2].x ^ z; f[2][1] = xv[3].x ^ z; f[2][2] = xv[2].y ^ z; f[2][3] = xv[3].y ^ z;
  f[3][0] = xv[2].z ^ z; f[3][1] = xv[3].z ^ z; f[3][2] = xv[2].w ^ z; f[3][3] = xv[3].w ^ z;
#pragma unroll
  for (int i = 0; i < 4; i++) pin(f[i]);
  if (!NOX) x_load(xv, xp, it + 2);
  mbar_wait_u(bars + B_WF + 8 * s, (it / W_NST) & 1);
  const uint64_t b1 = mkdesc(sb + s * W_STAGE, 8192, 1024, 1), b2 = mkdesc(sb + s * W_STAGE + 24576, 2048, 256, 3);
  wg_fence();
#pragma unroll
  for (int kk = 0; kk < 4; kk++) {
    mma_n128_rs_tb(a1[0], f[kk][0], f[kk][1], f[kk][2], f[kk][3], b1 + kk * 128, acc | kk);
    mma_n64_rs_tb(*(float(*)[32])a1[1], f[kk][0], f[kk][1], f[kk][2], f[kk][3], b1 + 1024 + kk * 128, acc | kk);
    mma_n48_rs_tb(a2, f[kk][0], f[kk][1], f[kk][2], f[kk][3], b2 + kk * 32, acc | kk);
  }
  wg_commit();
  wg_wait<1>();
#pragma unroll
  for (int i = 0; i < 4; i++) pin(fp[i]);
  mbar_arrive_pair(bars + B_WE + 8 * ((it + W_NST - 1) % W_NST), lead && acc);
}

__device__ __forceinline__ void kv_stream(uint32_t sb, int hg, int u, uint32_t epoch) {
  const uint32_t bars = sb + OFF_BAR + u * 64;
  cnt_wait(C_KV + hg, 16 * epoch);
  for (int c = 0; c < 32; c++) {
    const int s = c & 3;
    const uint8_t* src = g_KV + (size_t)(hg * 4 + (c >> 4) * 2 + u) * IMG_HEAD + (c & 15) * 6144;
    mbar_wait(bars + B_KE + 8 * s, (c >> 2) & 1);
    mbar_expect(bars + B_KF + 8 * s, 12288);
    bulk_g2s(sb + s * KV_SLOT + u * KV_CHUNK, src, 6144, bars + B_KF + 8 * s);
    bulk_g2s(sb + s * KV_SLOT + u * KV_CHUNK + 6144, src + (size_t)NH * IMG_HEAD, 6144, bars + B_KF + 8 * s);
  }
}

__device__ __forceinline__ void out_step(float (&acc)[80], uint32_t (&f)[4][4], uint32_t (&fp)[4][4], int it, int accum, uint32_t sb, uint32_t arow,
                                         uint32_t bars, uint32_t lead) {
  const int s = it % 5;
  mbar_wait_u(bars + B_OF + 8 * s, it / 5);
  const uint32_t st = sb + o_stage(s);
#pragma unroll
  for (int kk = 0; kk < 4; kk++)
    asm volatile("ldmatrix.sync.aligned.m8n8.x4.shared.b16 {%0,%1,%2,%3}, [%4];"
                 : "=r"(f[kk][0]), "=r"(f[kk][1]), "=r"(f[kk][2]), "=r"(f[kk][3]) : "r"(sb + o_stage_a(s) + arow + kk * 2048) : "memory");
  const uint64_t bd = mkdesc(st + 16384, 2560, 128, 0);
  wg_fence();
#pragma unroll
  for (int kk = 0; kk < 4; kk++) {
    mma_n80_rs_tb(*(float(*)[40])acc, f[kk][0], f[kk][1], f[kk][2], f[kk][3], bd + kk * 320, accum | kk);
    mma_n80_rs_tb(*(float(*)[40])(acc + 40), f[kk][0], f[kk][1], f[kk][2], f[kk][3], bd + kk * 320 + 80, accum | kk);
  }
  wg_commit();
  wg_wait<1>();
#pragma unroll
  for (int i = 0; i < 4; i++) pin(fp[i]);
  mbar_arrive_if(bars + B_OE + 8 * ((it + 4) % 5), lead && accum);
}

__device__ __forceinline__ void middle(uint8_t* smem, int wg, int w4, int lane, uint32_t cm, uint32_t neg1) {
  const uint32_t sb = smem_u32(smem), bars = sb + OFF_BAR, lead = (threadIdx.x & 127) == 0;
  const int t = lane & 3, mi = lane >> 3, r = wg & 1, u = wg >> 1;
  PROF(threadIdx.x == 0, 15);
  const bool slow = __any_sync(~0u, *(volatile uint32_t*)(smem + OFF_MISC + 20 + r * 4));
  if (u == 0) {
    const uint32_t ak = sb + OFF_AK + r * KV_SLOT, wph = sb + OFF_WPH;
    const uint32_t pka = sb + OFF_PHK + (r * 8 + w4 * 2 + (mi & 1)) * 640 + (mi >> 1) * 128 + (lane & 7) * 16;
    float pa[12], pb[12];
    wg_fence();
    issue_proj(pa, ak, wph);
    wg_commit();
    wg_wait<0>();
    pin(pa);
#pragma unroll 1
    for (int i = 0; i < 4; i++) {
      const int n = min(i + 1, 3);
      wg_fence();
      issue_proj(pb, ak + n * 3072, wph + n * 1152);
      wg_commit();
      uint32_t f[10];
      hedgehog1(pa, f, t);
      stsm4(pka + i * 10240, f[0], f[1], f[2], f[3]);
      stsm4(pka + i * 10240 + 256, f[4], f[5], f[6], f[7]);
      stsm2(pka + i * 10240 + 512, f[8], f[9]);
      wg_wait<0>();
      pin(pb);
#pragma unroll
      for (int k = 0; k < 12; k++) pa[k] = pb[k];
    }
    mbar_arrive_if(bars + B_KE + 16, lead);
    mbar_arrive_if(bars + B_KE + 24, lead);
    fence_async_smem();
    PROF(threadIdx.x == 0, 16);
    bar_sync(NB_PHIK, 256);
    wg_fence();
#pragma unroll
    for (int j = 0; j < 2; j++) {
      const uint64_t ad = mkdesc(sb + OFF_PHK + (r * 2 + j) * 10240, 640, 128, 0), vd = mkdesc(sb + OFF_V + (r * 2 + j) * 3072, 384, 128, 0);
#pragma unroll
      for (int ks = 0; ks < 8; ks++) mma_n24_ss_tatb(j ? pb : pa, ad + ks * 80, vd + (ks >> 2) * 768 + (ks & 3) * 48, ks);
    }
    wg_commit();
    wg_wait<0>();
    pin(pa); pin(pb);
    bar_sync(NB_WG + wg, 128);
    float2* dst = (float2*)(smem + OFF_PHK + r * 20480) + w4 * 192 + lane;
    if (w4 < 3) {
      dst[0] = make_float2(pa[0], pa[1]); dst[32] = make_float2(pa[4], pa[5]); dst[64] = make_float2(pa[8], pa[9]);
      dst[1280] = make_float2(pb[0], pb[1]); dst[1312] = make_float2(pb[4], pb[5]); dst[1344] = make_float2(pb[8], pb[9]);
    }
    if (w4 < 2) {
      dst[96] = make_float2(pa[2], pa[3]); dst[128] = make_float2(pa[6], pa[7]); dst[160] = make_float2(pa[10], pa[11]);
      dst[1376] = make_float2(pb[2], pb[3]); dst[1408] = make_float2(pb[6], pb[7]); dst[1440] = make_float2(pb[10], pb[11]);
    }
    fence_async_smem();
    bar_arrive(NB_TAIL, 288);
    PROF(threadIdx.x == 0, 5);
  }
  {
    const uint32_t gate = sb + OFF_GATE + (r * 64 + w4 * 16 + (lane >> 2)) * 8, qs = sb + OFF_Q + r * 12288;
    const uint32_t kb = bars + u * 64;
    AttnDesc d0;
    d0.k = mkdesc(sb + u * KV_CHUNK, 128, 384, 0); d0.k2 = mkdesc(sb + u * KV_CHUNK + 256, 0, 384, 0);
    d0.v = mkdesc(sb + u * KV_CHUNK + 6144, 384, 128, 0);
    const uint32_t qa = qs + u * 3072 + w4 * 768 + lane * 4;
#pragma unroll 1
    for (int pass = 0; pass < 2; pass++) {
      float o[12], s0[32];
      uint32_t q[6];
      load_q(q, qa + pass * 6144);
      if (!slow) {
        uint32_t p0[16], p1[16] = {};
        mbar_wait_u(kb + B_KF, 0);
        wg_fence();
        issue_qk(s0, q, d0, 0);
        wg_commit();
        wg_wait<0>();
        pin(s0);
#pragma unroll 1
        for (int turn = 0; turn < 4; turn++) {
          const int ph = turn & 1;
          AttnDesc d;
          asm volatile("mov.b64 %0, %3;\nmov.b64 %1, %4;\nmov.b64 %2, %5;" : "=l"(d.k), "=l"(d.k2), "=l"(d.v) : "l"(d0.k), "l"(d0.k2), "l"(d0.v));
          attn_chunk<0>(s0, p0, p1, o, q, d, turn, kb + B_KF + 8, ph, kb, lead && turn, cm, neg1);
          attn_chunk<1>(s0, p0, p1, o, q, d, 1, kb + B_KF + 16, ph, kb, lead, cm, neg1);
          attn_chunk<2>(s0, p0, p1, o, q, d, 1, kb + B_KF + 24, ph, kb, lead, cm, neg1);
          attn_chunk<3>(s0, p0, p1, o, q, d, 1, kb + B_KF + (turn == 3 ? 24 : 0), turn == 3 ? 1 : ph ^ 1, kb, lead, cm, neg1);
        }
        wg_wait<0>();
        pin(o); pin(p1); pin(q);
        mbar_arrive_if(kb + B_KE + 24, lead);
      } else {
        uint32_t p[16];
        float m0 = -INFINITY, m1 = -INFINITY;
#pragma unroll
        for (int i = 0; i < 12; i++) o[i] = 0.f;
#pragma unroll 1
        for (int j = 0; j < 32; j++) {
          const int slot = (j >> 1) & 3;
          const uint32_t co = slot * 1536 + (j & 1) * 192, neg = (POLY_MASK >> ((j & 1) * 8)) & 0xFF;
          mbar_wait_u(kb + B_KF + 8 * slot, (j >> 3) & 1);
          wg_fence();
          issue_qk(s0, q, d0, co);
          wg_commit();
          wg_wait<0>();
          pin(s0);
          float n0 = m0, n1 = m1;
#pragma unroll
          for (int g = 0; g < 8; g++) { n0 = fmaxf(n0, fmaxf(s0[4 * g], s0[4 * g + 1])); n1 = fmaxf(n1, fmaxf(s0[4 * g + 2], s0[4 * g + 3])); }
          n0 = fmaxf(n0, __shfl_xor_sync(~0u, n0, 1)); n1 = fmaxf(n1, __shfl_xor_sync(~0u, n1, 1));
          n0 = fmaxf(n0, __shfl_xor_sync(~0u, n0, 2)); n1 = fmaxf(n1, __shfl_xor_sync(~0u, n1, 2));
          const float c0 = ex2(m0 - n0), c1 = ex2(m1 - n1);
          m0 = n0; m1 = n1;
#pragma unroll
          for (int i = 0; i < 3; i++) { o[4 * i] *= c0; o[4 * i + 1] *= c0; o[4 * i + 2] *= c1; o[4 * i + 3] *= c1; }
#pragma unroll
          for (int g = 0; g < 8; g++) {
            const uint32_t sg = ((neg >> g) & 1) ? 0x80008000u : 0u;
            p[2 * g] = packbf(ex2(s0[4 * g] - m0), ex2(s0[4 * g + 1] - m0)) ^ sg;
            p[2 * g + 1] = packbf(ex2(s0[4 * g + 2] - m1), ex2(s0[4 * g + 3] - m1)) ^ sg;
          }
          wg_fence();
          issue_pv(o, p, d0.v + co, 1);
          wg_commit();
          wg_wait<0>();
          pin(o); pin(p);
          mbar_arrive_if(kb + B_KE + 8 * slot, lead && (j & 1));
        }
      }
      mbar_wait_u(bars + B_G, 0);
      stage_o(o, u, qs + pass * 6144, w4, lane, 0.f, lds_f2(gate).y, lds_f2(gate + 64).y);
      PROF(threadIdx.x == 0, 6 + pass);
      PROF(threadIdx.x == 256, 8 + pass);
      if (pass == 0) {
        {
          const uint32_t aq = sb + OFF_AQ + r * 12288;
          const float g0 = lds_f2(gate).x, g1 = lds_f2(gate + 64).x;
          const int h0 = u ? RDS : 0, h1 = u ? 4 : RDS;
          if (h0 < h1) {
            float pa[12], pb[12];
            wg_fence();
            issue_proj(pa, aq + h0 * 3072, sb + OFF_WPH + h0 * 1152);
            wg_commit();
            wg_wait<0>();
            pin(pa);
            if (RDS) { if (u) bar_sync(13 + r, 256); else bar_arrive(13 + r, 256); }
#pragma unroll 1
            for (int i = h0; i < h1; i++) {
              const int n = min(i + 1, 3);
              readout_head(pa, pb, aq + n * 3072, sb + OFF_WPH + n * 1152, sb + OFF_V + i * 1920, i & 1, aq + (i >> 1) * 5120, w4, lane, g0, g1);
#pragma unroll
              for (int k = 0; k < 12; k++) pa[k] = pb[k];
            }
          }
        }
        fence_async_smem();
        bar_arrive(NB_READ, 544);
        PROF(threadIdx.x == 256, 17);
      }
    }
    fence_async_smem();
    bar_arrive(NB_LAST, 544);
  }
}

__global__ void __cluster_dims__(2, 1, 1) __launch_bounds__(640, 1)
fused_block(const __grid_constant__ Maps maps, const __nv_bfloat16* __restrict__ x, const __nv_bfloat16* __restrict__ wphi,
            const __nv_bfloat16* __restrict__ gate_w, const uint8_t* __restrict__ wa, const uint8_t* __restrict__ wb,
            const uint8_t* __restrict__ woa, const uint8_t* __restrict__ wob, uint32_t cm, uint32_t neg1) {
  extern __shared__ __align__(1024) uint8_t smem[];
  const uint32_t sb = smem_u32(smem), bars = sb + OFF_BAR;
  const int warp = __shfl_sync(~0u, threadIdx.x >> 5, 0), lane = threadIdx.x & 31, wg = warp >> 2;
  const int bid = blockIdx.x;
  const int mt = (bid & 1) + 2 * (bid >> 4), hg = (bid >> 1) & 7;
  const int half = bid & 1, nt = (bid >> 1) & 3, mt3 = bid >> 3;
  PROF(threadIdx.x == 0, 0);
  PROFNS(threadIdx.x == 33, 0);
  if (warp >= 16 && lane == 0 && TMPF) asm volatile("prefetch.tensormap [%0];" ::"l"(&maps.a64 + (warp - 16)) : "memory");
  if (warp == 16) {
    if (lane == 0) {
#pragma unroll
      for (int i = 0; i < W_NST; i++) { mbar_init(bars + B_WF + 8 * i, 1); mbar_init(bars + B_WE + 8 * i, 4); }
      mbar_init(bars + B_Z, 1);
      mbar_init(bars + B_X, 1);
      *(uint4*)(smem + OFF_MISC) = make_uint4(0u, 0u, 0u, 0u);
      asm volatile("fence.mbarrier_init.release.cluster;" ::: "memory");
      mbar_expect(bars + B_WF, W_STAGE);
    }
    __syncwarp();
  }
  asm volatile("barrier.cluster.arrive.relaxed.aligned;" ::: "memory");
  if ((warp | 1) == 17) {
    bar_sync(0, 64);
    if (lane == 0) w_load<false>(maps, 0, sb, bars + B_WF, hg, warp & 1);
    __syncwarp();
  }

  if (wg == 4) {
    reg_dec<32>();
    asm volatile("barrier.cluster.wait.aligned;" ::: "memory");
    if (warp == 16) {
      if (lane == 0) {
        for (int it = 1; it < 20; it++) {
          const int s = it % W_NST;
          if (it >= W_NST) mbar_wait(bars + B_WE + 8 * s, ((it / W_NST) - 1) & 1);
          PROF(it == 5, 1);
          mbar_expect(bars + B_WF + 8 * s, W_STAGE);
          w_load<true>(maps, it, sb + s * W_STAGE, bars + B_WF + 8 * s, hg, half);
        }
      }
      __syncwarp();
      bar_sync(NB_HELP, 96);
      const uint32_t epoch = *(volatile uint32_t*)(smem + OFF_MISC + 16);
      if (lane == 0) {
        kv_stream(sb, hg, 0, epoch);
        cnt_wait(C_WO, NCTA * epoch);
        cnt_wait(C_OA + mt3, 8 * epoch);
        mbar_wait(bars + B_RF, 0);
        const uint8_t* ga = g_OAB + (size_t)mt3 * 327680 + half * 5 * 8192;
        for (int it = 0; it < 10; it++) {
          const int s = o_buf(it), ks = it < 5 ? it : it + 5;
          if (it >= 2 && it < 5) {
            mbar_wait(bars + B_P1, 0);
            mbar_wait(bars + B_KE + 8 * (it - 1), 0);
            mbar_wait(bars + B_KE + 64 + 8 * (it - 1), 0);
          }
          if (o_use(it)) mbar_wait(bars + B_OE + 8 * s, (o_use(it) - 1) & 1);
          const uint32_t d = sb + o_stage(s), da = sb + o_stage_a(s), b = bars + B_OF + 8 * s;
          if (it == 1) {
            mbar_expect(bars + B_OF + 32, O_STAGE);
            bulk_g2s(sb + o_stage_a(4), ga + 4 * 8192, 8192, bars + B_OF + 32);
            bulk_g2s(sb + o_stage_a(4) + 8192, ga + 4 * 8192 + 163840, 8192, bars + B_OF + 32);
          }
          if (it != 4) mbar_expect(b, O_STAGE);
          bulk_g2s(d + 16384, g_WOI + (size_t)nt * 409600 + (ks + half * 5) * 20480, 20480, b);
          if (it == 7) { PROF(true, 19); cnt_wait(C_OB + mt3, 8 * epoch); PROF(true, 21); }
          if (it == 4) continue;
          bulk_g2s(da, ga + ks * 8192, 8192, b);
          bulk_g2s(da + 8192, ga + ks * 8192 + 163840, 8192, b);
        }
      }
    } else if (warp == 17) {
      uint32_t epoch = 0;
      if (lane == 0) {
#pragma unroll
        for (int i = 0; i < 8; i++) { mbar_init(bars + B_KF + (i >> 2) * 64 + 8 * (i & 3), 1); mbar_init(bars + B_KE + (i >> 2) * 64 + 8 * (i & 3), 2); }
#pragma unroll
        for (int i = 0; i < 5; i++) { mbar_init(bars + B_OF + 8 * i, 1); mbar_init(bars + B_OE + 8 * i, 2); }
        mbar_init(bars + B_RF, 1);
        mbar_init(bars + B_G, 1);
        mbar_init(bars + B_P1, 1);
        mbar_init(bars + B_R, 1);
        fence_async_smem();
        epoch = atomicAdd(g_CNT + C_START * 8, 1u) / NCTA + 1;
        *(volatile uint32_t*)(smem + OFF_MISC + 16) = epoch;
      }
      epoch = __shfl_sync(~0u, epoch, 0);
      if (lane < 30) { uint4* z = (uint4*)(g_KVA + hg * 1920 + mt * 120) + lane * 2; z[0] = z[1] = make_uint4(0u, 0u, 0u, 0u); }
      __syncwarp();
      asm volatile("fence.acq_rel.gpu;" ::: "memory");
      bar_arrive(NB_HELP, 96);
#pragma unroll 1
      for (int e = lane; e < 96; e += 32) {
        const int i = e / 24, slot = e % 24;
        int d = -1;
        if (i & 1) { if (slot < 16) d = slot + 4; else if (slot >= 20) d = slot - 20; }
        else if (slot < 20) d = slot;
        uint2 v[5] = {};
        if (d >= 0) {
#pragma unroll
          for (int u = 0; u < 5; u++) v[u] = __ldg((const uint2*)(wphi + ((hg * 4 + i) * 20 + d) * 20) + u);
        }
        uint8_t* dst = smem + OFF_WPH + i * 1152 + (slot >> 3) * 384 + (slot & 7) * 16;
        *(uint4*)dst = make_uint4(v[0].x, v[0].y, v[1].x, v[1].y);
        *(uint4*)(dst + 128) = make_uint4(v[2].x, v[2].y, v[3].x, v[3].y);
        *(uint4*)(dst + 256) = make_uint4(v[4].x, v[4].y, v[4].x, v[4].y);
      }
      fence_async_smem();
      bar_sync(NB_STAGED, 288);
      if (lane == 0) {
        bulk_s2g(g_KMAX + hg * 16 + mt, sb + OFF_MISC, 16);
        bulk_commit_wait();
        cnt_add_done(C_KM + hg);
#pragma unroll 1
        for (int i = 0; i < 16; i++) {
          if (!XNOST) bulk_s2g(g_KV + (size_t)((i >> 3) * NH + hg * 4 + (i & 3)) * IMG_HEAD + (mt * 2 + ((i >> 2) & 1)) * 3072, sb + OFF_Q + i * 3072, 3072);
          __nanosleep(STNS);
        }
        bulk_commit_wait();
        PROF(true, 22);
        cnt_add_done(C_KV + hg);
        cnt_wait(C_KM + hg, 16 * epoch);
      }
      __syncwarp();
      {
        uint4 v = ldg_cg4(g_KMAX + hg * 16 + (lane & 15));
        v.x = __reduce_max_sync(~0u, v.x); v.y = __reduce_max_sync(~0u, v.y); v.z = __reduce_max_sync(~0u, v.z); v.w = __reduce_max_sync(~0u, v.w);
        if (lane < 4) *(volatile float*)(smem + OFF_MISC + lane * 4) =
            sqrt_ap(__uint_as_float(lane == 0 ? v.x : lane == 1 ? v.y : lane == 2 ? v.z : v.w)) * (QSCALE * 1.02f);
      }
      bar_arrive(NB_FREE, 288);
      bar_sync(NB_TAIL, 288);
      if (lane == 0) {
#pragma unroll 1
        for (int i = 0; i < 4; i++)
          asm volatile("cp.reduce.async.bulk.global.shared::cta.bulk_group.add.f32 [%0], [%1], %2;" ::"l"(g_KVA + (hg * 4 + i) * 480),
                       "r"(sb + OFF_PHK + i * 10240), "r"(3840) : "memory");
        bulk_commit_wait();
        cnt_add_done(C_KVP + hg);
        cnt_wait(C_GATE + mt, 8 * epoch);
      }
      __syncwarp();
      {
        const uint4 g0 = ldg_cg4(g_GATE + mt * 128 + lane * 2), g1 = ldg_cg4(g_GATE + mt * 128 + 64 + lane * 2);
        *(uint4*)(smem + OFF_GATE + lane * 16) = g0;
        *(uint4*)(smem + OFF_GATE + 512 + lane * 16) = g1;
      }
      if (lane == 0) {
        cnt_wait(C_KVP + hg, 16 * epoch);
        mbar_expect(bars + B_R, 15360);
        bulk_g2s(sb + OFF_KVS, g_KVA + hg * 1920, 15360, bars + B_R);
      }
      mbar_wait(bars + B_R, 0);
#pragma unroll 4
      for (int e = lane; e < 960; e += 32) {
        const float4 v = *(const float4*)(smem + OFF_KVS + e * 16);
        *(uint2*)(smem + OFF_V + e * 8) = make_uint2(packbf(v.x, v.y), packbf(v.z, v.w));
      }
      fence_async_smem();
      PROF(lane == 0, 20);
      __syncwarp();
      if (lane == 0) mbar_arrive(bars + B_G);
      uint8_t* og = g_OAB + (size_t)mt * 327680;
      bar_sync(NB_READ, 544);
      if (lane == 0) {
#pragma unroll 1
        for (int w = 0; w < 2; w++) {
          bulk_s2g(og + w * 163840 + hg * 10240, sb + OFF_AQ + w * 12288, 10240);
          bulk_s2g(og + w * 163840 + (80 + bgroup(hg * 10)) * 1024, sb + OFF_Q + w * 12288, 5120);
        }
        bulk_commit_wait();
        mbar_arrive(bars + B_RF);
        cnt_add_done(C_OA + mt);
      }
      __syncwarp();
      bar_sync(NB_LAST, 544);
      if (lane == 0) {
        bulk_s2g(og + (80 + bgroup(hg * 10 + 5)) * 1024, sb + OFF_Q + 6144, 5120);
        bulk_s2g(og + 163840 + (80 + bgroup(hg * 10 + 5)) * 1024, sb + OFF_Q + 12288 + 6144, 5120);
        bulk_commit_wait();
        cnt_add_done(C_OB + mt);
      }
    } else if (warp == 18) {
      bar_sync(NB_HELP, 96);
      if (lane == 0) { kv_stream(sb, hg, 1, *(volatile uint32_t*)(smem + OFF_MISC + 16)); mbar_arrive(bars + B_P1); }
    }
  } else {
    const int w4 = warp & 3;
    const uint32_t lead = (threadIdx.x & 127) == 0;
    if (wg >= 2) {
      const int ht = threadIdx.x - 256;
      if (ht < PFROWS * 15) {
        const int k = (ht / 15) * 16 + mt, sec = (ht % 15) / 5;
        const uint8_t* p = (sec == 2 ? wa : wb + 1280 + sec * 1280) + (size_t)k * 3840 + hg * 160 + (ht % 5) * 32;
        asm volatile("prefetch.global.L2 [%0];" ::"l"(p));
      }
      reg_dec<24>();
      asm volatile("barrier.cluster.wait.aligned;" ::: "memory");
      __nanosleep(BGNS);
      {
        const int row = mt * 128 + hg * 16 + (ht >> 4);
        const uint4* xr = (const uint4*)(x + (size_t)row * DM) + (ht & 15);
        const uint4* gr = (const uint4*)gate_w + (ht & 15);
        float acc = 0.f;
#pragma unroll 1
        for (int i = 0; i < 5; i++) {
          const uint4 a = __ldg(xr + i * 16), g = __ldg(gr + i * 16);
          const uint32_t av[4] = {a.x, a.y, a.z, a.w}, gv[4] = {g.x, g.y, g.z, g.w};
#pragma unroll
          for (int j = 0; j < 4; j++) {
            uint32_t p;
            asm("mul.rn.bf16x2 %0, %1, %2;" : "=r"(p) : "r"(av[j]), "r"(gv[j]));
            acc += bf_lo(p) + bf_hi(p);
          }
        }
#pragma unroll
        for (int o = 8; o; o >>= 1) acc += __shfl_xor_sync(~0u, acc, o);
        if ((ht & 15) == 0) {
          const float g = bf_round(__fdividef(1.f, 1.f + __expf(-bf_round(acc))));
          g_GATE[row] = make_float2(g, bf_round(1.f - g));
        }
      }
#pragma unroll 1
      for (int e = ht; e < (bid < 32 ? 1280 : 640); e += 256) {
        const int kg = bid + (e >= 640 ? NCTA : 0), c = (e % 640) >> 3;
        const uint8_t* src = (kg < 80 ? woa + (size_t)kg * 10240 : wob + (size_t)(kg - 80) * 10240) + (e & 7) * 1280 + c * 16;
        *(uint4*)(g_WOI + (kg < 80 ? kg : 80 + bgroup(kg - 80)) * 2560 + (size_t)(c / 20) * 409600 + (c % 20) * 128 + (e & 7) * 16) = __ldg((const uint4*)src);
      }
      bar_sync(NB_BG, 256);
      if (ht == 0) { cnt_add(C_GATE + mt); cnt_add_done(C_WO); PROF(true, 18); }
      bar_sync(NB_EPI, 512);
      reg_inc<112>();
    } else {
    const uint8_t* xp = (const uint8_t*)x + (size_t)(mt * 128 + warp * 16 + (lane >> 2)) * 1280 + (lane & 3) * 16;
    uint4 xa[4], xb[4];
    x_load(xa, xp, 0);
    x_load(xb, xp, 1);
    reg_inc<200>();
    asm volatile("barrier.cluster.wait.aligned;" ::: "memory");
    const int t = lane & 3, mi = lane >> 3;
    {
      const uint32_t sbase = sb + wg * 12288 + (w4 * 2 + (mi & 1)) * 384 + (lane & 7) * 16;
      const uint32_t ad01 = sbase + (mi >> 1) * 128, ad2 = sbase + (mi >> 1) * 3072 + 256;
      float a1[2][64], a2[24];
      uint32_t fa[4][4] = {}, fb[4][4] = {};
#pragma unroll 1
      for (int tile = 0; tile < 2; tile++) {
#pragma unroll 1
        for (int ks = 0; ks < 10; ks += 2) {
          gemm_step(a1, a2, xa, fa, fb, xp, tile * 10 + ks, ks, sb, bars, lead);
          gemm_step(a1, a2, xb, fb, fa, xp, tile * 10 + ks + 1, 1, sb, bars, lead);
        }
        wg_wait<0>();
        pin(a1[0]); pin(*(float(*)[32])a1[1]); pin(a2);
#pragma unroll
        for (int i = 0; i < 4; i++) pin(fb[i]);
        mbar_arrive_pair(bars + B_WE + 8 * 4, lead);
        PROF(threadIdx.x == 0, 2 + 2 * tile);
        PROFNS(threadIdx.x == 33 && tile, 1);
        if (tile == 0) {
          if (hg & 1) epilogue0<4>(a1, a2, warp * 2, lane, ad01, ad2, sb + OFF_MISC);
          else epilogue0<0>(a1, a2, warp * 2, lane, ad01, ad2, sb + OFF_MISC);
          fence_async_smem();
          bar_arrive(NB_STAGED, 288);
          PROF(threadIdx.x == 0, 3);
        }
      }
      bar_sync(NB_FREE, 288);
#pragma unroll
      for (int s = 0; s < 6; s++) mbar_arrive_if(bars + B_KE + (s < 4 ? 64 : 0) + 8 * (s & 3), lead);
      mbar_wait_u(bars + B_WE + 8 * 4, 1);
      PROF(threadIdx.x == 0, 23);
      uint32_t xq[4][2];
      bool unsafe;
      if (hg & 1) { unsafe = epilogue1a<4>(a1, a2, xq, smem, wg, t, ad01, ad2); epilogue1b<4>(a1, a2, xq, t, ad01, ad2); }
      else { unsafe = epilogue1a<0>(a1, a2, xq, smem, wg, t, ad01, ad2); epilogue1b<0>(a1, a2, xq, t, ad01, ad2); }
      if (lead) *(volatile uint32_t*)(smem + OFF_MISC + 20 + wg * 4) = unsafe;
      fence_async_smem();
      reg_dec<112>();
      bar_sync(NB_EPI, 512);
    }
    }
    middle(smem, wg, w4, lane, cm, neg1);
    if (wg >= 2) { reg_dec<24>(); return; }
    {
      PROFNS(threadIdx.x == 33, 2);
      asm volatile("barrier.cluster.arrive.relaxed.aligned;" ::: "memory");
      reg_inc<160>();
      float acc[80];
      uint32_t fa[4][4] = {}, fb[4][4] = {};
      const uint32_t arow = wg * 8192 + (lane >> 4) * 1024 + w4 * 256 + (lane & 15) * 16;
#pragma unroll 1
      for (int it = 0; it < 10; it += 2) {
        out_step(acc, fa, fb, it, it, sb, arow, bars, lead);
        out_step(acc, fb, fa, it + 1, 1, sb, arow, bars, lead);
      }
      wg_wait<0>();
      pin(acc);
#pragma unroll
      for (int i = 0; i < 4; i++) pin(fb[i]);
      PROF(threadIdx.x == 0, 12);
      asm volatile("barrier.cluster.wait.aligned;" ::: "memory");
      uint32_t remote, rbar;
      asm volatile("mapa.shared::cluster.u32 %0, %1, %2;" : "=r"(remote) : "r"(sb + OFF_Q + threadIdx.x * 16), "r"(half ^ 1));
      asm volatile("mapa.shared::cluster.u32 %0, %1, %2;" : "=r"(rbar) : "r"(bars + B_X), "r"(half ^ 1));
      if (threadIdx.x == 0) mbar_expect(bars + B_X, 20480);
#pragma unroll
      for (int j = 0; j < 5; j++) {
        uint32_t v[4];
#pragma unroll
        for (int u = 0; u < 4; u++) v[u] = half ? packbf(acc[8 * j + 2 * u], acc[8 * j + 2 * u + 1]) : packbf(acc[40 + 8 * j + 2 * u], acc[41 + 8 * j + 2 * u]);
        asm volatile("st.async.weak.shared::cluster.mbarrier::complete_tx::bytes.v4.b32 [%0], {%1,%2,%3,%4}, [%5];" ::"r"(remote + j * 4096), "r"(v[0]),
                     "r"(v[1]), "r"(v[2]), "r"(v[3]), "r"(rbar) : "memory");
      }
      bar_sync(NB_PHIK, 256);
      mbar_wait_u(bars + B_X, 0);
      PROF(threadIdx.x == 0, 13);
      const uint32_t ob = sb + wg * 10240;
      const uint32_t oa = ob + (w4 * 16 + (lane & 15)) * 160 + (lane >> 4) * 16;
      uint32_t pk[20];
#pragma unroll
      for (int j = 0; j < 5; j++) {
        const uint4 r = *(const uint4*)(smem + OFF_Q + j * 4096 + threadIdx.x * 16);
        const uint32_t rv[4] = {r.x, r.y, r.z, r.w};
#pragma unroll
        for (int u = 0; u < 4; u++) {
          const float v0 = half ? acc[40 + 8 * j + 2 * u] : acc[8 * j + 2 * u], v1 = half ? acc[41 + 8 * j + 2 * u] : acc[8 * j + 2 * u + 1];
          pk[4 * j + u] = packbf(v0 + bf_lo(rv[u]), v1 + bf_hi(rv[u]));
        }
      }
#pragma unroll
      for (int j = 0; j < 10; j += 2) stsm4(oa + j * 16, pk[2 * j], pk[2 * j + 1], pk[2 * j + 2], pk[2 * j + 3]);
      fence_async_smem();
      bar_sync(NB_WG + wg, 128);
      if (lead) {
        asm volatile("cp.async.bulk.tensor.2d.global.shared::cta.bulk_group [%0, {%2,%3}], [%1];" ::"l"(&maps.out), "r"(ob), "r"(nt * 160 + half * 80),
                     "r"(mt3 * 128 + wg * 64) : "memory");
        asm volatile("cp.async.bulk.commit_group;" ::: "memory");
        asm volatile("cp.async.bulk.wait_group.read 0;" ::: "memory");
      }
      PROF(threadIdx.x == 0, 14);
      PROFNS(threadIdx.x == 33, 3);
    }
  }
}

typedef CUresult (*EncodeFn)(CUtensorMap*, CUtensorMapDataType, cuuint32_t, void*, const cuuint64_t*, const cuuint64_t*, const cuuint32_t*,
                             const cuuint32_t*, CUtensorMapInterleave, CUtensorMapSwizzle, CUtensorMapL2promotion, CUtensorMapFloatOOBfill);

void encode(EncodeFn fn, CUtensorMap* m, const void* p, int rank, const cuuint64_t* dims, const cuuint64_t* strides, const cuuint32_t* box,
            CUtensorMapSwizzle sw) {
  const cuuint32_t es[5] = {1, 1, 1, 1, 1};
  fn(m, CU_TENSOR_MAP_DATA_TYPE_BFLOAT16, rank, const_cast<void*>(p), dims, strides, box, es, CU_TENSOR_MAP_INTERLEAVE_NONE, sw,
     CU_TENSOR_MAP_L2_PROMOTION_L2_128B, CU_TENSOR_MAP_FLOAT_OOB_FILL_NONE);
}

}

extern "C" void kernel_launch(void* const* d_in, const int* in_sizes, int n_in, void* d_out, int out_size) {
  (void)in_sizes; (void)n_in; (void)out_size;
  static EncodeFn enc = nullptr;
  if (!enc) {
    void* fn = nullptr;
    cudaDriverEntryPointQueryResult qr;
    cudaGetDriverEntryPoint("cuTensorMapEncodeTiled", &fn, cudaEnableDefault, &qr);
    enc = (EncodeFn)fn;
    cudaFuncSetAttribute(fused_block, cudaFuncAttributeMaxDynamicSharedMemorySize, SMEM_BYTES);
  }
  Maps maps;
  {
    const cuuint64_t dx[2] = {640, 2048}, sx[1] = {1280};
    const cuuint32_t bo[2] = {80, 64};
    encode(enc, &maps.out, d_out, 2, dx, sx, bo, CU_TENSOR_MAP_SWIZZLE_NONE);
    const cuuint64_t dw[5] = {1920, 2, 4, 4, 20}, sw[4] = {3840, 8 * 3840, 2 * 3840, 32 * 3840};
    const cuuint32_t b64[5] = {64, 2, 4, 4, 1}, b16[5] = {16, 2, 4, 4, 1};
    encode(enc, &maps.a64, d_in[1], 5, dw, sw, b64, CU_TENSOR_MAP_SWIZZLE_128B);
    encode(enc, &maps.a16, d_in[1], 5, dw, sw, b16, CU_TENSOR_MAP_SWIZZLE_32B);
    encode(enc, &maps.b64, d_in[5], 5, dw, sw, b64, CU_TENSOR_MAP_SWIZZLE_128B);
    encode(enc, &maps.b16, d_in[5], 5, dw, sw, b16, CU_TENSOR_MAP_SWIZZLE_32B);
  }
  fused_block<<<NCTA, 640, SMEM_BYTES, cudaStreamPerThread>>>(maps, (const __nv_bfloat16*)d_in[0], (const __nv_bfloat16*)d_in[2],
                                                               (const __nv_bfloat16*)d_in[7], (const uint8_t*)d_in[1], (const uint8_t*)d_in[5],
                                                               (const uint8_t*)d_in[3], (const uint8_t*)d_in[6], 0x1F801F80u, 0xFFFFFFFFu);
}
```

```cpp
#include <cuda_runtime.h>
#include <cuda_bf16.h>
#include <cuda.h>
#include <stdint.h>

namespace {

constexpr int SEQ = 2048, DM = 640, NH = 32, NCTA = 128;
constexpr int IMG_HEAD = SEQ * 48;
#define POLY_MASK 0xF8F8u
constexpr float LOG2E = 1.4426950408889634f;
constexpr float QSCALE = 0.22360679774997896f * 1.4426950408889634f;
constexpr uint32_t BF_ONE = 0x3F80u;
constexpr uint32_t BF_MAGIC = 0x43E0u;
constexpr uint32_t BF_MU_HI = 0x4025u;
constexpr uint32_t BF_MU_LO = 0x3B8Bu;
constexpr float FAST_BOUND = 40.0f;

__device__ __align__(1024) uint8_t g_KV[2 * NH * IMG_HEAD];
__device__ __align__(1024) float2 g_KVA[NH * 480];
__device__ __align__(1024) float4 g_KMAX[8 * 16];
__device__ __align__(1024) float2 g_GATE[SEQ];
__device__ __align__(1024) uint8_t g_OAB[16 * 2 * 160 * 1024];
__device__ __align__(1024) uint8_t g_WOI[4 * 409600];
__device__ __align__(1024) uint32_t g_CNT[82 * 8];
constexpr int C_START = 0, C_WO = 1, C_KV = 2, C_KVP = 10, C_GATE = 26, C_OA = 42, C_OB = 58, C_KM = 74;

#define SPIN_LIMIT (1ll << 29)
#define SPIN_FAIL(code) __trap()
__device__ __forceinline__ uint32_t smem_u32(const void* p) { return (uint32_t)__cvta_generic_to_shared(p); }
__device__ __forceinline__ void mbar_init(uint32_t a, uint32_t c) { asm volatile("mbarrier.init.shared::cta.b64 [%0], %1;" ::"r"(a), "r"(c) : "memory"); }
__device__ __forceinline__ void mbar_expect(uint32_t a, uint32_t b) { asm volatile("mbarrier.arrive.expect_tx.shared::cta.b64 _, [%0], %1;" ::"r"(a), "r"(b) : "memory"); }
__device__ __forceinline__ void mbar_arrive(uint32_t a) { asm volatile("mbarrier.arrive.shared::cta.b64 _, [%0];" ::"r"(a) : "memory"); }
__device__ __forceinline__ uint32_t mbar_try(uint32_t a, uint32_t ph) {
  uint32_t ok;
  asm volatile("{\n.reg .pred p;\nmbarrier.try_wait.parity.shared::cta.b64 p, [%1], %2;\nselp.u32 %0, 1, 0, p;\n}\n" : "=r"(ok) : "r"(a), "r"(ph) : "memory");
  return ok;
}
__device__ __forceinline__ void mbar_wait(uint32_t a, uint32_t ph) {
  if (mbar_try(a, ph)) return;
  const long long t0 = clock64();
  while (!mbar_try(a, ph))
    if (clock64() - t0 > SPIN_LIMIT) { SPIN_FAIL(1000 + (a & 0x1FF) * 2 + ph); break; }
}
__device__ __forceinline__ void mbar_wait_u(uint32_t a, uint32_t ph) {
#pragma unroll 1
  for (int n = 0; n < (1 << 18); n++)
    if (__all_sync(~0u, mbar_try(a, ph))) break;
}
__device__ __forceinline__ uint32_t mbar_test(uint32_t a, uint32_t ph) {
  uint32_t ok;
  asm volatile("{\n.reg .pred p;\nmbarrier.test_wait.parity.shared::cta.b64 p, [%1], %2;\nselp.u32 %0, 1, 0, p;\n}\n" : "=r"(ok) : "r"(a), "r"(ph) : "memory");
  return ok;
}
__device__ __forceinline__ void mbar_arrive_if(uint32_t a, uint32_t flag) {
  asm volatile("{\n.reg .pred p;\nsetp.ne.u32 p, %1, 0;\n@p mbarrier.arrive.shared::cta.b64 _, [%0];\n}\n" ::"r"(a), "r"(flag) : "memory");
}
__device__ __forceinline__ void cnt_add_done(int slot) { asm volatile("red.relaxed.gpu.global.add.u32 [%0], 1;" ::"l"(g_CNT + slot * 8) : "memory"); }
__device__ __forceinline__ void cnt_add(int slot) {
  asm volatile("fence.acq_rel.gpu;" ::: "memory");
  cnt_add_done(slot);
}
__device__ __forceinline__ void cnt_wait(int slot, uint32_t target) {
  uint32_t v;
  long long t0 = 0;
  for (;;) {
    asm volatile("ld.relaxed.gpu.global.u32 %0, [%1];" : "=r"(v) : "l"(g_CNT + slot * 8) : "memory");
    if ((int32_t)(v - target) >= 0) break;
    __nanosleep(40);
    if (!t0) t0 = clock64();
    else if (clock64() - t0 > SPIN_LIMIT) { SPIN_FAIL(slot); break; }
  }
  asm volatile("ld.acquire.gpu.global.u32 %0, [%1];" : "=r"(v) : "l"(g_CNT + slot * 8) : "memory");
}
__device__ __forceinline__ void bulk_commit_wait() { asm volatile("cp.async.bulk.commit_group;\ncp.async.bulk.wait_group 0;" ::: "memory"); }
template <bool MC>
__device__ __forceinline__ void tma5(uint32_t dst, const CUtensorMap* m, int c0, int c4, uint32_t bar) {
  if (MC)
    asm volatile("cp.async.bulk.tensor.5d.shared::cluster.global.mbarrier::complete_tx::bytes.multicast::cluster [%0], [%1, {%3,%5,%5,%5,%4}], [%2], %6;"
                 ::"r"(dst), "l"(m), "r"(bar), "r"(c0), "r"(c4), "r"(0), "h"((uint16_t)3) : "memory");
  else
    asm volatile("cp.async.bulk.tensor.5d.shared::cluster.global.mbarrier::complete_tx::bytes [%0], [%1, {%3,%5,%5,%5,%4}], [%2];"
                 ::"r"(dst), "l"(m), "r"(bar), "r"(c0), "r"(c4), "r"(0) : "memory");
}
__device__ __forceinline__ void mbar_arrive_pair(uint32_t a, uint32_t flag) {
  asm volatile("{\n.reg .pred p;\n.reg .b32 r0, r1;\nsetp.ne.u32 p, %1, 0;\nmapa.shared::cluster.u32 r0, %0, 0;\nmapa.shared::cluster.u32 r1, %0, 1;\n"
               "@p mbarrier.arrive.relaxed.cluster.shared::cluster.b64 _, [r0];\n@p mbarrier.arrive.relaxed.cluster.shared::cluster.b64 _, [r1];\n}\n" ::"r"(a), "r"(flag) : "memory");
}
__device__ __forceinline__ void bulk_g2s(uint32_t dst, const void* src, uint32_t bytes, uint32_t bar) {
  asm volatile("cp.async.bulk.shared::cluster.global.mbarrier::complete_tx::bytes [%0], [%1], %2, [%3];" ::"r"(dst), "l"(src), "r"(bytes), "r"(bar) : "memory");
}
__device__ __forceinline__ void fence_async_smem() { asm volatile("fence.proxy.async.shared::cta;" ::: "memory"); }
__device__ __forceinline__ void bar_sync(int id, int n) { asm volatile("bar.sync %0, %1;" ::"r"(id), "r"(n) : "memory"); }
__device__ __forceinline__ void bar_arrive(int id, int n) { asm volatile("bar.arrive %0, %1;" ::"r"(id), "r"(n) : "memory"); }
__device__ __forceinline__ void wg_fence() { asm volatile("wgmma.fence.sync.aligned;" ::: "memory"); }
__device__ __forceinline__ void wg_commit() { asm volatile("wgmma.commit_group.sync.aligned;" ::: "memory"); }
template <int N> __device__ __forceinline__ void wg_wait() { asm volatile("wgmma.wait_group.sync.aligned %0;" ::"n"(N) : "memory"); }
template <int N> __device__ __forceinline__ void reg_inc() { asm volatile("setmaxnreg.inc.sync.aligned.u32 %0;" ::"n"(N)); }
template <int N> __device__ __forceinline__ void reg_dec() { asm volatile("setmaxnreg.dec.sync.aligned.u32 %0;" ::"n"(N)); }
template <int N> __device__ __forceinline__ void pin(float (&r)[N]) {
#pragma unroll
  for (int i = 0; i < N; i++) asm volatile("" : "+f"(r[i])::"memory");
}
template <int N> __device__ __forceinline__ void pin(uint32_t (&r)[N]) {
#pragma unroll
  for (int i = 0; i < N; i++) asm volatile("" : "+r"(r[i])::"memory");
}
__device__ __forceinline__ uint64_t mkdesc(uint32_t addr, uint32_t lbo, uint32_t sbo, uint32_t swz) {
  return (uint64_t)((addr & 0x3FFFF) >> 4) | ((uint64_t)(lbo >> 4) << 16) | ((uint64_t)(sbo >> 4) << 32) | ((uint64_t)swz << 62);
}
__device__ __forceinline__ float ex2(float x) { float y; asm("ex2.approx.ftz.f32 %0, %1;" : "=f"(y) : "f"(x)); return y; }
__device__ __forceinline__ float rcp(float x) { float y; asm("rcp.approx.ftz.f32 %0, %1;" : "=f"(y) : "f"(x)); return y; }
__device__ __forceinline__ float sqrt_ap(float x) { float y; asm("sqrt.approx.f32 %0, %1;" : "=f"(y) : "f"(x)); return y; }
__device__ __forceinline__ uint32_t packbf(float lo, float hi) { uint32_t d; asm("cvt.rn.bf16x2.f32 %0, %1, %2;" : "=r"(d) : "f"(hi), "f"(lo)); return d; }
__device__ __forceinline__ float bf_lo(uint32_t v) { return __uint_as_float(v << 16); }
__device__ __forceinline__ float bf_hi(uint32_t v) { return __uint_as_float(v & 0xFFFF0000u); }
__device__ __forceinline__ float bf_round(float x) { return bf_lo(packbf(x, 0.f)); }
__device__ __forceinline__ uint4 ldg_cg4(const void* p) { uint4 v; asm volatile("ld.global.cg.v4.b32 {%0,%1,%2,%3}, [%4];" : "=r"(v.x), "=r"(v.y), "=r"(v.z), "=r"(v.w) : "l"(p) : "memory"); return v; }
__device__ __forceinline__ void sts32(uint32_t a, uint32_t v) { asm volatile("st.shared.b32 [%0], %1;" ::"r"(a), "r"(v) : "memory"); }
__device__ __forceinline__ void stsm4(uint32_t a, uint32_t r0, uint32_t r1, uint32_t r2, uint32_t r3) {
  asm volatile("stmatrix.sync.aligned.m8n8.x4.shared.b16 [%0], {%1,%2,%3,%4};" ::"r"(a), "r"(r0), "r"(r1), "r"(r2), "r"(r3) : "memory");
}

__device__ __forceinline__ void stsm2(uint32_t a, uint32_t r0, uint32_t r1) {
  asm volatile("stmatrix.sync.aligned.m8n8.x2.shared.b16 [%0], {%1,%2};" ::"r"(a), "r"(r0), "r"(r1) : "memory");
}
__device__ __forceinline__ uint4 ldg_x(const void* p) {
  uint4 v;
  asm volatile("ld.global.nc.L1::no_allocate.L2::128B.v4.b32 {%0,%1,%2,%3}, [%4];" : "=r"(v.x), "=r"(v.y), "=r"(v.z), "=r"(v.w) : "l"(p));
  return v;
}
__device__ __forceinline__ float2 lds_f2(uint32_t a) { float2 v; asm volatile("ld.shared.v2.f32 {%0,%1}, [%2];" : "=f"(v.x), "=f"(v.y) : "r"(a) : "memory"); return v; }
__device__ __forceinline__ void bulk_s2g(void* dst, uint32_t src, uint32_t bytes) {
  asm volatile("cp.async.bulk.global.shared::cta.bulk_group [%0], [%1], %2;" ::"l"(dst), "r"(src), "r"(bytes) : "memory");
}

__device__ __forceinline__ void mma_n24_ss_tb(float (&d)[12], uint64_t adesc, uint64_t bdesc, int acc) {
  asm volatile("{\n.reg .pred p;\nsetp.ne.b32 p, %14, 0;\n"
      "wgmma.mma_async.sync.aligned.m64n24k16.f32.bf16.bf16 "
      "{%0,%1,%2,%3,%4,%5,%6,%7,%8,%9,%10,%11}, "
      "%12, %13, p, 1, 1, 0, 1;\n}\n"
      : "+f"(d[0]), "+f"(d[1]), "+f"(d[2]), "+f"(d[3]), "+f"(d[4]), "+f"(d[5]), "+f"(d[6]), "+f"(d[7]),
        "+f"(d[8]), "+f"(d[9]), "+f"(d[10]), "+f"(d[11])
      : "l"(adesc), "l"(bdesc), "r"(acc));
}
__device__ __forceinline__ void mma_n128_rs_tb(float (&d)[64], uint32_t a0, uint32_t a1, uint32_t a2, uint32_t a3, uint64_t bdesc, int acc) {
  asm volatile("{\n.reg .pred p;\nsetp.ne.b32 p, %69, 0;\n"
      "wgmma.mma_async.sync.aligned.m64n128k16.f32.bf16.bf16 "
      "{%0,%1,%2,%3,%4,%5,%6,%7,%8,%9,%10,%11,%12,%13,%14,%15,"
      "%16,%17,%18,%19,%20,%21,%22,%23,%24,%25,%26,%27,%28,%29,%30,%31,"
      "%32,%33,%34,%35,%36,%37,%38,%39,%40,%41,%42,%43,%44,%45,%46,%47,"
      "%48,%49,%50,%51,%52,%53,%54,%55,%56,%57,%58,%59,%60,%61,%62,%63}, "
      "{%64,%65,%66,%67}, %68, p, 1, 1, 1;\n}\n"
      : "+f"(d[0]), "+f"(d[1]), "+f"(d[2]), "+f"(d[3]), "+f"(d[4]), "+f"(d[5]), "+f"(d[6]), "+f"(d[7]),
        "+f"(d[8]), "+f"(d[9]), "+f"(d[10]), "+f"(d[11]), "+f"(d[12]), "+f"(d[13]), "+f"(d[14]), "+f"(d[15]),
        "+f"(d[16]), "+f"(d[17]), "+f"(d[18]), "+f"(d[19]), "+f"(d[20]), "+f"(d[21]), "+f"(d[22]), "+f"(d[23]),
        "+f"(d[24]), "+f"(d[25]), "+f"(d[26]), "+f"(d[27]), "+f"(d[28]), "+f"(d[29]), "+f"(d[30]), "+f"(d[31]),
        "+f"(d[32]), "+f"(d[33]), "+f"(d[34]), "+f"(d[35]), "+f"(d[36]), "+f"(d[37]), "+f"(d[38]), "+f"(d[39]),
        "+f"(d[40]), "+f"(d[41]), "+f"(d[42]), "+f"(d[43]), "+f"(d[44]), "+f"(d[45]), "+f"(d[46]), "+f"(d[47]),
        "+f"(d[48]), "+f"(d[49]), "+f"(d[50]), "+f"(d[51]), "+f"(d[52]), "+f"(d[53]), "+f"(d[54]), "+f"(d[55]),
        "+f"(d[56]), "+f"(d[57]), "+f"(d[58]), "+f"(d[59]), "+f"(d[60]), "+f"(d[61]), "+f"(d[62]), "+f"(d[63])
      : "r"(a0), "r"(a1), "r"(a2), "r"(a3), "l"(bdesc), "r"(acc));
}
__device__ __forceinline__ void mma_n64_rs_tb(float (&d)[32], uint32_t a0, uint32_t a1, uint32_t a2, uint32_t a3, uint64_t bdesc, int acc) {
  asm volatile("{\n.reg .pred p;\nsetp.ne.b32 p, %37, 0;\n"
      "wgmma.mma_async.sync.aligned.m64n64k16.f32.bf16.bf16 "
      "{%0,%1,%2,%3,%4,%5,%6,%7,%8,%9,%10,%11,%12,%13,%14,%15,"
      "%16,%17,%18,%19,%20,%21,%22,%23,%24,%25,%26,%27,%28,%29,%30,%31}, "
      "{%32,%33,%34,%35}, %36, p, 1, 1, 1;\n}\n"
      : "+f"(d[0]), "+f"(d[1]), "+f"(d[2]), "+f"(d[3]), "+f"(d[4]), "+f"(d[5]), "+f"(d[6]), "+f"(d[7]),
        "+f"(d[8]), "+f"(d[9]), "+f"(d[10]), "+f"(d[11]), "+f"(d[12]), "+f"(d[13]), "+f"(d[14]), "+f"(d[15]),
        "+f"(d[16]), "+f"(d[17]), "+f"(d[18]), "+f"(d[19]), "+f"(d[20]), "+f"(d[21]), "+f"(d[22]), "+f"(d[23]),
        "+f"(d[24]), "+f"(d[25]), "+f"(d[26]), "+f"(d[27]), "+f"(d[28]), "+f"(d[29]), "+f"(d[30]), "+f"(d[31])
      : "r"(a0), "r"(a1), "r"(a2), "r"(a3), "l"(bdesc), "r"(acc));
}
__device__ __forceinline__ void mma_n48_rs_tb(float (&d)[24], uint32_t a0, uint32_t a1, uint32_t a2, uint32_t a3, uint64_t bdesc, int acc) {
  asm volatile("{\n.reg .pred p;\nsetp.ne.b32 p, %29, 0;\n"
      "wgmma.mma_async.sync.aligned.m64n48k16.f32.bf16.bf16 "
      "{%0,%1,%2,%3,%4,%5,%6,%7,%8,%9,%10,%11,%12,%13,%14,%15,"
      "%16,%17,%18,%19,%20,%21,%22,%23}, "
      "{%24,%25,%26,%27}, %28, p, 1, 1, 1;\n}\n"
      : "+f"(d[0]), "+f"(d[1]), "+f"(d[2]), "+f"(d[3]), "+f"(d[4]), "+f"(d[5]), "+f"(d[6]), "+f"(d[7]),
        "+f"(d[8]), "+f"(d[9]), "+f"(d[10]), "+f"(d[11]), "+f"(d[12]), "+f"(d[13]), "+f"(d[14]), "+f"(d[15]),
        "+f"(d[16]), "+f"(d[17]), "+f"(d[18]), "+f"(d[19]), "+f"(d[20]), "+f"(d[21]), "+f"(d[22]), "+f"(d[23])
      : "r"(a0), "r"(a1), "r"(a2), "r"(a3), "l"(bdesc), "r"(acc));
}
__device__ __forceinline__ void mma_n64_rs(float (&d)[32], uint32_t a0, uint32_t a1, uint32_t a2, uint32_t a3, uint64_t bdesc, int acc) {
  asm volatile("{\n.reg .pred p;\nsetp.ne.b32 p, %37, 0;\n"
      "wgmma.mma_async.sync.aligned.m64n64k16.f32.bf16.bf16 "
      "{%0,%1,%2,%3,%4,%5,%6,%7,%8,%9,%10,%11,%12,%13,%14,%15,"
      "%16,%17,%18,%19,%20,%21,%22,%23,%24,%25,%26,%27,%28,%29,%30,%31}, "
      "{%32,%33,%34,%35}, %36, p, 1, 1, 0;\n}\n"
      : "+f"(d[0]), "+f"(d[1]), "+f"(d[2]), "+f"(d[3]), "+f"(d[4]), "+f"(d[5]), "+f"(d[6]), "+f"(d[7]),
        "+f"(d[8]), "+f"(d[9]), "+f"(d[10]), "+f"(d[11]), "+f"(d[12]), "+f"(d[13]), "+f"(d[14]), "+f"(d[15]),
        "+f"(d[16]), "+f"(d[17]), "+f"(d[18]), "+f"(d[19]), "+f"(d[20]), "+f"(d[21]), "+f"(d[22]), "+f"(d[23]),
        "+f"(d[24]), "+f"(d[25]), "+f"(d[26]), "+f"(d[27]), "+f"(d[28]), "+f"(d[29]), "+f"(d[30]), "+f"(d[31])
      : "r"(a0), "r"(a1), "r"(a2), "r"(a3), "l"(bdesc), "r"(acc));
}
__device__ __forceinline__ void mma_n80_rs_tb(float (&d)[40], uint32_t a0, uint32_t a1, uint32_t a2, uint32_t a3, uint64_t bdesc, int acc) {
  asm volatile("{\n.reg .pred p;\nsetp.ne.b32 p, %45, 0;\n"
      "wgmma.mma_async.sync.aligned.m64n80k16.f32.bf16.bf16 "
      "{%0,%1,%2,%3,%4,%5,%6,%7,%8,%9,%10,%11,%12,%13,%14,%15,"
      "%16,%17,%18,%19,%20,%21,%22,%23,%24,%25,%26,%27,%28,%29,%30,%31,"
      "%32,%33,%34,%35,%36,%37,%38,%39}, "
      "{%40,%41,%42,%43}, %44, p, 1, 1, 1;\n}\n"
      : "+f"(d[0]), "+f"(d[1]), "+f"(d[2]), "+f"(d[3]), "+f"(d[4]), "+f"(d[5]), "+f"(d[6]), "+f"(d[7]),
        "+f"(d[8]), "+f"(d[9]), "+f"(d[10]), "+f"(d[11]), "+f"(d[12]), "+f"(d[13]), "+f"(d[14]), "+f"(d[15]),
        "+f"(d[16]), "+f"(d[17]), "+f"(d[18]), "+f"(d[19]), "+f"(d[20]), "+f"(d[21]), "+f"(d[22]), "+f"(d[23]),
        "+f"(d[24]), "+f"(d[25]), "+f"(d[26]), "+f"(d[27]), "+f"(d[28]), "+f"(d[29]), "+f"(d[30]), "+f"(d[31]),
        "+f"(d[32]), "+f"(d[33]), "+f"(d[34]), "+f"(d[35]), "+f"(d[36]), "+f"(d[37]), "+f"(d[38]), "+f"(d[39])
      : "r"(a0), "r"(a1), "r"(a2), "r"(a3), "l"(bdesc), "r"(acc));
}
__device__ __forceinline__ void mma_n24_rs_tb(float (&d)[12], uint32_t a0, uint32_t a1, uint32_t a2, uint32_t a3, uint64_t bdesc, int acc) {
  asm volatile("{\n.reg .pred p;\nsetp.ne.b32 p, %17, 0;\n"
      "wgmma.mma_async.sync.aligned.m64n24k16.f32.bf16.bf16 "
      "{%0,%1,%2,%3,%4,%5,%6,%7,%8,%9,%10,%11}, "
      "{%12,%13,%14,%15}, %16, p, 1, 1, 1;\n}\n"
      : "+f"(d[0]), "+f"(d[1]), "+f"(d[2]), "+f"(d[3]), "+f"(d[4]), "+f"(d[5]), "+f"(d[6]), "+f"(d[7]),
        "+f"(d[8]), "+f"(d[9]), "+f"(d[10]), "+f"(d[11])
      : "r"(a0), "r"(a1), "r"(a2), "r"(a3), "l"(bdesc), "r"(acc));
}
__device__ __forceinline__ void mma_n24_ss_tatb(float (&d)[12], uint64_t adesc, uint64_t bdesc, int acc) {
  asm volatile("{\n.reg .pred p;\nsetp.ne.b32 p, %14, 0;\n"
      "wgmma.mma_async.sync.aligned.m64n24k16.f32.bf16.bf16 "
      "{%0,%1,%2,%3,%4,%5,%6,%7,%8,%9,%10,%11}, "
      "%12, %13, p, 1, 1, 1, 1;\n}\n"
      : "+f"(d[0]), "+f"(d[1]), "+f"(d[2]), "+f"(d[3]), "+f"(d[4]), "+f"(d[5]), "+f"(d[6]), "+f"(d[7]),
        "+f"(d[8]), "+f"(d[9]), "+f"(d[10]), "+f"(d[11])
      : "l"(adesc), "l"(bdesc), "r"(acc));
}

constexpr int W_STAGE = 30720, W_NST = 5;
constexpr int KV_CHUNK = 12288, KV_SLOT = 2 * KV_CHUNK;
constexpr int O_STAGE = 36864;
constexpr int OFF_AK = 2 * KV_SLOT;
constexpr int OFF_PHK = 4 * KV_SLOT;
constexpr int OFF_KVS = OFF_PHK + 2 * 10240 + 4096;
constexpr int OFF_GATE = 112640;
constexpr int OFF_Q = W_NST * W_STAGE;
constexpr int OFF_V = OFF_Q + 24576;
constexpr int OFF_AQ = OFF_V + 24576;
constexpr int OFF_WPH = OFF_AQ + 24576;
constexpr int OFF_BAR = OFF_WPH + 4608;
constexpr int B_WF = 0, B_WE = 40, B_KF = 80, B_KE = 112, B_OF = 208, B_OE = 248, B_RF = 288, B_Z = 296, B_G = 304, B_X = 312, B_P1 = 320, B_R = 328;
constexpr int OFF_MISC = OFF_BAR + 336;
constexpr int SMEM_BYTES = OFF_MISC + 32;
__device__ __forceinline__ uint32_t o_stage(int s) { return s == 0 ? OFF_V : s == 1 ? OFF_Q - O_STAGE : (s - 2) * O_STAGE; }
__device__ __forceinline__ uint32_t o_stage_a(int s) { return s == 4 ? OFF_V + O_STAGE : o_stage(s); }
constexpr int NB_STAGED = 1, NB_FREE = 2, NB_WG = 3, NB_BG = 7, NB_EPI = 15, NB_PHIK = 8, NB_TAIL = 9, NB_READ = 10, NB_LAST = 11, NB_HELP = 12;

template <int SEC, int J, int HF>
__device__ __forceinline__ float2 grp(const float (&a1)[2][64], const float (&a2)[24]) {
  constexpr int S = SEC & 3, J1 = (SEC & 4) ? J - 2 : J, J2 = (SEC & 4) ? J : J - 8;
  if constexpr (J1 >= 0 && J1 < 8) return make_float2(a1[S >> 1][(8 * (S & 1) + J1) * 4 + 2 * HF], a1[S >> 1][(8 * (S & 1) + J1) * 4 + 2 * HF + 1]);
  else return make_float2(a2[(2 * S + J2) * 4 + 2 * HF], a2[(2 * S + J2) * 4 + 2 * HF + 1]);
}
__device__ __forceinline__ float sq2(float2 v) { return fmaf(v.x, v.x, v.y * v.y); }
__device__ __forceinline__ uint32_t pks(float2 v, float s) { return packbf(v.x * s, v.y * s); }

template <int SEC, int PR>
__device__ __forceinline__ void norms(const float (&a1)[2][64], const float (&a2)[24], int t, float (&n)[2][2]) {
  const float h0 = sq2(grp<SEC, 5 * PR + 2, 0>(a1, a2)), h1 = sq2(grp<SEC, 5 * PR + 2, 1>(a1, a2));
  n[0][0] = sq2(grp<SEC, 5 * PR, 0>(a1, a2)) + sq2(grp<SEC, 5 * PR + 1, 0>(a1, a2)) + (t < 2 ? h0 : 0.f);
  n[0][1] = sq2(grp<SEC, 5 * PR, 1>(a1, a2)) + sq2(grp<SEC, 5 * PR + 1, 1>(a1, a2)) + (t < 2 ? h1 : 0.f);
  n[1][0] = sq2(grp<SEC, 5 * PR + 3, 0>(a1, a2)) + sq2(grp<SEC, 5 * PR + 4, 0>(a1, a2)) + (t < 2 ? 0.f : h0);
  n[1][1] = sq2(grp<SEC, 5 * PR + 3, 1>(a1, a2)) + sq2(grp<SEC, 5 * PR + 4, 1>(a1, a2)) + (t < 2 ? 0.f : h1);
#pragma unroll
  for (int i = 0; i < 4; i++) n[i >> 1][i & 1] += __shfl_xor_sync(~0u, n[i >> 1][i & 1], 1);
#pragma unroll
  for (int i = 0; i < 4; i++) n[i >> 1][i & 1] += __shfl_xor_sync(~0u, n[i >> 1][i & 1], 2);
}

template <int SEC, int PR>
__device__ __forceinline__ void stage_pair(const float (&a1)[2][64], const float (&a2)[24], float sc0, float sc1, float sm, uint32_t xe0, uint32_t xe1,
                                           uint32_t xo0, uint32_t xo1, uint32_t ad01, uint32_t ad2, int t) {
  const uint32_t off = 2 * PR * 3072;
  stsm4(ad01 + off, pks(grp<SEC, 5 * PR, 0>(a1, a2), sc0), pks(grp<SEC, 5 * PR, 1>(a1, a2), sc1), pks(grp<SEC, 5 * PR + 1, 0>(a1, a2), sc0),
        pks(grp<SEC, 5 * PR + 1, 1>(a1, a2), sc1));
  stsm4(ad01 + off + 3072, pks(grp<SEC, 5 * PR + 3, 0>(a1, a2), sc0), pks(grp<SEC, 5 * PR + 3, 1>(a1, a2), sc1),
        pks(grp<SEC, 5 * PR + 4, 0>(a1, a2), sc0), pks(grp<SEC, 5 * PR + 4, 1>(a1, a2), sc1));
  const uint32_t m0 = pks(grp<SEC, 5 * PR + 2, 0>(a1, a2), sc0 * sm), m1 = pks(grp<SEC, 5 * PR + 2, 1>(a1, a2), sc1 * sm);
  const bool lo = t < 2;
  stsm4(ad2 + off, lo ? m0 : xe0, lo ? m1 : xe1, lo ? xo0 : m0, lo ? xo1 : m1);
}

template <bool EXACT>
__device__ __forceinline__ bool hedgehog(const float (&p)[12], uint32_t (&f)[10], int t) {
  const bool lo = t < 2;
  bool safe = true;
#pragma unroll
  for (int hf = 0; hf < 2; hf++) {
    const float v[6] = {p[2 * hf], p[2 * hf + 1], p[4 + 2 * hf], p[5 + 2 * hf], p[8 + 2 * hf], p[9 + 2 * hf]};
    float ep[4], en[4], m0, m1;
    const float sg = lo ? LOG2E : -LOG2E;
    if (EXACT) {
      float mx = fmaxf(fmaxf(fmaxf(v[0], v[1]), fmaxf(v[2], v[3])), fmaxf(v[4], v[5]));
      float mn = fminf(fminf(fminf(v[0], v[1]), fminf(v[2], v[3])), fminf(v[4], v[5]));
      mx = fmaxf(mx, __shfl_xor_sync(~0u, mx, 1)); mn = fminf(mn, __shfl_xor_sync(~0u, mn, 1));
      mx = fmaxf(mx, __shfl_xor_sync(~0u, mx, 2)); mn = fminf(mn, __shfl_xor_sync(~0u, mn, 2));
      const float bp = -mx * LOG2E, bn = mn * LOG2E, bm = lo ? bp : bn;
#pragma unroll
      for (int i = 0; i < 4; i++) { ep[i] = ex2(fmaf(v[i], LOG2E, bp)); en[i] = ex2(fmaf(v[i], -LOG2E, bn)); }
      m0 = ex2(fmaf(v[4], sg, bm)); m1 = ex2(fmaf(v[5], sg, bm));
    } else {
#pragma unroll
      for (int i = 0; i < 4; i++) ep[i] = ex2(v[i] * LOG2E);
      const float r0 = rcp(ep[0] * ep[1]), r1 = rcp(ep[2] * ep[3]);
      en[0] = r0 * ep[1]; en[1] = r0 * ep[0]; en[2] = r1 * ep[3]; en[3] = r1 * ep[2];
      m0 = ex2(v[4] * sg); m1 = ex2(v[5] * sg);
    }
    const float ms = m0 + m1;
    float sp = (ep[0] + ep[1]) + (ep[2] + ep[3]) + (lo ? ms : 0.f);
    float sn = (en[0] + en[1]) + (en[2] + en[3]) + (lo ? 0.f : ms);
    sp += __shfl_xor_sync(~0u, sp, 1); sn += __shfl_xor_sync(~0u, sn, 1);
    sp += __shfl_xor_sync(~0u, sp, 2); sn += __shfl_xor_sync(~0u, sn, 2);
    safe = safe && sp <= 1.0e12f && sn <= 1.0e12f;
    const float r = rcp(sp * sn), rp = r * sn, rn = r * sp, rm = lo ? rp : rn;
    f[0 + hf] = packbf(ep[0] * rp, ep[1] * rp);
    f[2 + hf] = packbf(ep[2] * rp, ep[3] * rp);
    f[4 + hf] = packbf(m0 * rm, m1 * rm);
    f[6 + hf] = packbf(en[0] * rn, en[1] * rn);
    f[8 + hf] = packbf(en[2] * rn, en[3] * rn);
  }
  return safe;
}
__device__ __forceinline__ void hedgehog2(const float (&p)[2][12], uint32_t (&f)[2][10], int t) {
  const bool s0 = hedgehog<false>(p[0], f[0], t), s1 = hedgehog<false>(p[1], f[1], t);
  if (!__all_sync(~0u, s0 && s1)) { hedgehog<true>(p[0], f[0], t); hedgehog<true>(p[1], f[1], t); }
}

template <int O>
__device__ __forceinline__ void epilogue0(const float (&a1)[2][64], const float (&a2)[24], int rg, int lane, uint32_t ad01, uint32_t ad2, uint32_t kmx) {
  const int t = lane & 3;
  const bool p0 = (POLY_MASK >> rg) & 1, p1 = (POLY_MASK >> (rg + 1)) & 1;
  const uint32_t kp = (t & 1) ? 0u : (BF_ONE | (BF_MAGIC << 16)), km = (t & 1) ? BF_MU_LO : (BF_ONE | (BF_MU_HI << 16));
  const uint32_t vp = (t & 1) ? 0u : (BF_ONE | 0x8000u), vm = (t & 1) ? 0u : BF_ONE;
  const uint32_t k0 = p0 ? kp : km, k1 = p1 ? kp : km, v0 = p0 ? vp : vm, v1 = p1 ? vp : vm;
  const float s0 = p0 ? -1.f : 1.f, s1 = p1 ? -1.f : 1.f;
  stage_pair<O + 0, 0>(a1, a2, 1.f, 1.f, 1.f, k0, k1, k0, k1, ad01 + OFF_Q, ad2 + OFF_Q, t);
  stage_pair<O + 0, 1>(a1, a2, 1.f, 1.f, 1.f, k0, k1, k0, k1, ad01 + OFF_Q, ad2 + OFF_Q, t);
  stage_pair<O + 1, 0>(a1, a2, s0, s1, 1.f, v0, v1, v0, v1, ad01 + OFF_V, ad2 + OFF_V, t);
  stage_pair<O + 1, 1>(a1, a2, s0, s1, 1.f, v0, v1, v0, v1, ad01 + OFF_V, ad2 + OFF_V, t);
  stage_pair<O + 2, 0>(a1, a2, 1.f, 1.f, 0.5f, 0u, 0u, 0u, 0u, ad01 + OFF_AQ, ad2 + OFF_AQ, t);
  stage_pair<O + 2, 1>(a1, a2, 1.f, 1.f, 0.5f, 0u, 0u, 0u, 0u, ad01 + OFF_AQ, ad2 + OFF_AQ, t);
  float n0[2][2], n1[2][2];
  norms<O + 0, 0>(a1, a2, t, n0);
  norms<O + 0, 1>(a1, a2, t, n1);
  const uint32_t m0 = __reduce_max_sync(~0u, __float_as_uint(fmaxf(n0[0][0], n0[0][1])));
  const uint32_t m1 = __reduce_max_sync(~0u, __float_as_uint(fmaxf(n0[1][0], n0[1][1])));
  const uint32_t m2 = __reduce_max_sync(~0u, __float_as_uint(fmaxf(n1[0][0], n1[0][1])));
  const uint32_t m3 = __reduce_max_sync(~0u, __float_as_uint(fmaxf(n1[1][0], n1[1][1])));
  if (lane < 4) asm volatile("red.shared.max.u32 [%0], %1;" ::"r"(kmx + lane * 4), "r"(lane == 0 ? m0 : lane == 1 ? m1 : lane == 2 ? m2 : m3) : "memory");
}

template <int O>
__device__ __forceinline__ bool epilogue1a(const float (&a1)[2][64], const float (&a2)[24], uint32_t (&xq)[4][2], const uint8_t* smem, int wg, int t,
                                           uint32_t ad01, uint32_t ad2) {
  stage_pair<O + 0, 0>(a1, a2, 1.f, 1.f, 0.5f, 0u, 0u, 0u, 0u, ad01 + OFF_AK + wg * 12288, ad2 + OFF_AK + wg * 12288, t);
  stage_pair<O + 0, 1>(a1, a2, 1.f, 1.f, 0.5f, 0u, 0u, 0u, 0u, ad01 + OFF_AK + wg * 12288, ad2 + OFF_AK + wg * 12288, t);
  float n0[2][2], n1[2][2];
  norms<O + 2, 0>(a1, a2, t, n0);
  norms<O + 2, 1>(a1, a2, t, n1);
  const float4 km = *(const float4*)(smem + OFF_MISC);
  const float b[4][2] = {{sqrt_ap(n0[0][0]) * km.x, sqrt_ap(n0[0][1]) * km.x}, {sqrt_ap(n0[1][0]) * km.y, sqrt_ap(n0[1][1]) * km.y},
                         {sqrt_ap(n1[0][0]) * km.z, sqrt_ap(n1[0][1]) * km.z}, {sqrt_ap(n1[1][0]) * km.w, sqrt_ap(n1[1][1]) * km.w}};
  bool unsafe = false;
#pragma unroll
  for (int i = 0; i < 8; i++) unsafe |= !(b[i >> 1][i & 1] <= FAST_BOUND);
  uint32_t any;
  asm volatile("{\n.reg .pred p, q;\nsetp.ne.u32 p, %1, 0;\nbar.red.or.pred q, %2, 128, p;\nselp.u32 %0, 1, 0, q;\n}\n"
               : "=r"(any) : "r"((uint32_t)unsafe), "r"(NB_WG + wg) : "memory");
  const bool slow = __any_sync(~0u, any);
#pragma unroll
  for (int i = 0; i < 8; i++) xq[i >> 1][i & 1] = slow ? 0u : ((t & 1) ? BF_ONE : packbf(-b[i >> 1][i & 1], 1.f));
  return slow;
}
template <int O>
__device__ __forceinline__ void epilogue1b(const float (&a1)[2][64], const float (&a2)[24], const uint32_t (&xq)[4][2], int t, uint32_t ad01, uint32_t ad2) {
  stage_pair<O + 2, 0>(a1, a2, QSCALE, QSCALE, 1.f, xq[0][0], xq[0][1], xq[1][0], xq[1][1], ad01 + OFF_Q, ad2 + OFF_Q, t);
  stage_pair<O + 2, 1>(a1, a2, QSCALE, QSCALE, 1.f, xq[2][0], xq[2][1], xq[3][0], xq[3][1], ad01 + OFF_Q, ad2 + OFF_Q, t);
  const uint32_t one = (t & 1) ? 0u : BF_ONE;
  stage_pair<O + 1, 0>(a1, a2, 1.f, 1.f, 1.f, one, one, one, one, ad01 + OFF_V, ad2 + OFF_V, t);
  stage_pair<O + 1, 1>(a1, a2, 1.f, 1.f, 1.f, one, one, one, one, ad01 + OFF_V, ad2 + OFF_V, t);
}

__device__ __forceinline__ void issue_proj(float (&p)[2][12], uint32_t img, uint32_t wph) {
  const uint64_t ad = mkdesc(img, 128, 384, 0), ad2 = mkdesc(img + 256, 0, 384, 0), wd = mkdesc(wph, 384, 128, 0), wd2 = mkdesc(wph + 768, 0, 128, 0);
#pragma unroll
  for (int i = 0; i < 2; i++) {
    mma_n24_ss_tb(p[i], ad + i * 192, wd + i * 72, 0);
    mma_n24_ss_tb(p[i], ad2 + i * 192, wd2 + i * 72, 1);
  }
}

__device__ __forceinline__ uint32_t exp2_bits(float y0, float y1, uint32_t cm, uint32_t neg1) {
  uint32_t w, m, r;
  asm("prmt.b32 %0, %1, %2, 0x6521;" : "=r"(w) : "f"(y0), "f"(y1));
  asm("lop3.b32 %0, %1, 0x007F007F, %2, 0xEA;" : "=r"(m) : "r"(w), "r"(cm));
  const uint32_t e = m * neg1 + w;
  asm("fma.rn.bf16x2 %0, %1, %2, %3;" : "=r"(r) : "r"(w), "r"(m), "r"(e));
  return r;
}
template <int HI>
__device__ __forceinline__ void exp_tile(const float (&s)[32], uint32_t (&p)[16], uint32_t cm, uint32_t neg1) {
#pragma unroll
  for (int g = 0; g < 8; g++) {
    if ((POLY_MASK >> (g + 8 * HI)) & 1) {
      p[2 * g] = exp2_bits(s[4 * g], s[4 * g + 1], cm, neg1);
      p[2 * g + 1] = exp2_bits(s[4 * g + 2], s[4 * g + 3], cm, neg1);
    } else {
      p[2 * g] = packbf(ex2(s[4 * g]), ex2(s[4 * g + 1]));
      p[2 * g + 1] = packbf(ex2(s[4 * g + 2]), ex2(s[4 * g + 3]));
    }
  }
}
struct AttnDesc { uint64_t k, k2, v; };
__device__ __forceinline__ void issue_qk(float (&s)[32], const uint32_t (&q)[8], const AttnDesc& d, uint32_t ko) {
  mma_n64_rs(s, q[0], q[1], q[2], q[3], d.k + ko, 0);
  mma_n64_rs(s, q[4], q[5], q[6], q[7], d.k2 + ko, 1);
}
__device__ __forceinline__ void issue_pv(float (&o)[12], const uint32_t (&p)[16], uint64_t vd, int acc) {
#pragma unroll
  for (int kk = 0; kk < 4; kk++) mma_n24_rs_tb(o, p[4 * kk], p[4 * kk + 1], p[4 * kk + 2], p[4 * kk + 3], vd + kk * 48, acc | kk);
}
__device__ __forceinline__ void load_q(uint32_t (&q)[8], uint32_t a) {
#pragma unroll
  for (int i = 0; i < 6; i++) asm volatile("ld.shared.b32 %0, [%1];" : "=r"(q[i]) : "r"(a + (i >> 1) * 128 + (i & 1) * 384) : "memory");
}
template <int SL>
__device__ __forceinline__ void attn_chunk(float (&s)[32], uint32_t (&p0)[16], uint32_t (&p1)[16], float (&o)[12], const uint32_t (&q)[8],
                                           const AttnDesc& d, int acc, uint32_t full_next, uint32_t ph_next,
                                           uint32_t bars, uint32_t release, uint32_t cm, uint32_t neg1) {
  exp_tile<0>(s, p0, cm, neg1);
  wg_fence();
  issue_qk(s, q, d, SL * 1536 + 192);
  wg_commit();
  issue_pv(o, p0, d.v + SL * 1536, acc);
  wg_commit();
  wg_wait<1>();
  pin(s); pin(p1);
  mbar_arrive_if(bars + B_KE + 8 * ((SL + 3) & 3), release);
  const uint32_t ready = mbar_test(full_next, ph_next);
  exp_tile<1>(s, p1, cm, neg1);
  pin(p1);
  if (!__all_sync(~0u, ready)) mbar_wait_u(full_next, ph_next);
  wg_fence();
  issue_qk(s, q, d, ((SL + 1) & 3) * 1536);
  wg_commit();
  issue_pv(o, p1, d.v + SL * 1536 + 192, 1);
  wg_commit();
  wg_wait<1>();
  pin(s); pin(p0);
}
__device__ __forceinline__ int bgroup(int G) {
  const int hg = G / 10, j = G % 10;
  return (hg >> 2) * 40 + (j / 5) * 20 + (hg & 3) * 5 + j % 5;
}
__device__ __forceinline__ void stage_o(const float (&o)[12], int odd, uint32_t pair, int w4, int lane, float eps, float s0, float s1) {
  const int src = (lane & ~3) | (odd ? 0 : 2);
  const float l0 = __shfl_sync(~0u, o[8], src) + eps, l1 = __shfl_sync(~0u, o[10], src) + eps;
  const float r0 = s0 * rcp(l0), r1 = s1 * rcp(l1);
  const uint32_t base = pair + w4 * 256;
  stsm4(base + (odd ? 3072 : 0) + (lane >> 4) * 1024 + (lane & 15) * 16, packbf(o[0] * r0, o[1] * r0), packbf(o[2] * r1, o[3] * r1),
        packbf(o[4] * r0, o[5] * r0), packbf(o[6] * r1, o[7] * r1));
  if (((lane & 3) < 2) != (odd != 0)) {
    sts32(base + 2048 + lane * 4, packbf(o[8] * r0, o[9] * r0));
    sts32(base + 2048 + 128 + lane * 4, packbf(o[10] * r1, o[11] * r1));
  }
}
struct Maps { CUtensorMap a64, a16, b64, b16, out; };

template <bool MC>
__device__ __forceinline__ void w_load(const Maps& m, int it, uint32_t d, uint32_t b, int hg, int rank) {
  const int kb = (it % 10) * 2 + rank, c = hg * 80 + (hg & 1) * 16, c2 = hg * 80 + ((hg & 1) ? 0 : 64);
  const bool w0 = it < 10;
  const CUtensorMap *p64 = w0 ? &m.b64 : &m.a64, *q64 = w0 ? &m.a64 : &m.b64, *p16 = w0 ? &m.b16 : &m.a16, *q16 = w0 ? &m.a16 : &m.b16;
  const uint32_t d1 = d + rank * 4096, d2 = d + 24576 + rank * 1024;
  tma5<MC>(d1, p64, 640 + c, kb, b);
  tma5<MC>(d1 + 8192, p64, 1280 + c, kb, b);
  tma5<MC>(d1 + 16384, q64, c, kb, b);
  tma5<MC>(d2, p16, 640 + c2, kb, b);
  tma5<MC>(d2 + 2048, p16, 1280 + c2, kb, b);
  tma5<MC>(d2 + 4096, q16, c2, kb, b);
}
__device__ __forceinline__ void x_load(uint4 (&v)[4], const uint8_t* p, int it) {
  const uint8_t* q = p + (it % 10) * 128;
  v[0] = ldg_x(q); v[1] = ldg_x(q + 8 * 1280); v[2] = ldg_x(q + 64); v[3] = ldg_x(q + 8 * 1280 + 64);
}
__device__ __forceinline__ void gemm_step(float (&a1)[2][64], float (&a2)[24], uint4 (&xv)[4], uint32_t (&f)[4][4], uint32_t (&fp)[4][4],
                                          const uint8_t* xp, int it, int acc, uint32_t sb, uint32_t bars, uint32_t lead) {
  const int s = it % W_NST;
  const uint32_t z = mbar_test(bars + B_Z, 1) - 1;
  f[0][0] = xv[0].x ^ z; f[0][1] = xv[1].x ^ z; f[0][2] = xv[0].y ^ z; f[0][3] = xv[1].y ^ z;
  f[1][0] = xv[0].z ^ z; f[1][1] = xv[1].z ^ z; f[1][2] = xv[0].w ^ z; f[1][3] = xv[1].w ^ z;
  f[2][0] = xv[2].x ^ z; f[2][1] = xv[3].x ^ z; f[2][2] = xv[2].y ^ z; f[2][3] = xv[3].y ^ z;
  f[3][0] = xv[2].z ^ z; f[3][1] = xv[3].z ^ z; f[3][2] = xv[2].w ^ z; f[3][3] = xv[3].w ^ z;
#pragma unroll
  for (int i = 0; i < 4; i++) pin(f[i]);
  x_load(xv, xp, it + 2);
  mbar_wait_u(bars + B_WF + 8 * s, (it / W_NST) & 1);
  const uint64_t b1 = mkdesc(sb + s * W_STAGE, 8192, 1024, 1), b2 = mkdesc(sb + s * W_STAGE + 24576, 2048, 256, 3);
  wg_fence();
#pragma unroll
  for (int kk = 0; kk < 4; kk++) {
    mma_n128_rs_tb(a1[0], f[kk][0], f[kk][1], f[kk][2], f[kk][3], b1 + kk * 128, acc | kk);
    mma_n64_rs_tb(*(float(*)[32])a1[1], f[kk][0], f[kk][1], f[kk][2], f[kk][3], b1 + 1024 + kk * 128, acc | kk);
    mma_n48_rs_tb(a2, f[kk][0], f[kk][1], f[kk][2], f[kk][3], b2 + kk * 32, acc | kk);
  }
  wg_commit();
  wg_wait<1>();
#pragma unroll
  for (int i = 0; i < 4; i++) pin(fp[i]);
  mbar_arrive_pair(bars + B_WE + 8 * ((it + W_NST - 1) % W_NST), lead && acc);
}

__device__ __forceinline__ void kv_stream(uint32_t sb, int hg, int u, uint32_t epoch) {
  const uint32_t bars = sb + OFF_BAR + u * 64;
  cnt_wait(C_KV + hg, 16 * epoch);
  for (int c = 0; c < 32; c++) {
    const int s = c & 3;
    const uint8_t* src = g_KV + (size_t)(hg * 4 + (c >> 4) * 2 + u) * IMG_HEAD + (c & 15) * 6144;
    mbar_wait(bars + B_KE + 8 * s, (c >> 2) & 1);
    mbar_expect(bars + B_KF + 8 * s, 12288);
    bulk_g2s(sb + s * KV_SLOT + u * KV_CHUNK, src, 6144, bars + B_KF + 8 * s);
    bulk_g2s(sb + s * KV_SLOT + u * KV_CHUNK + 6144, src + (size_t)NH * IMG_HEAD, 6144, bars + B_KF + 8 * s);
  }
}

__device__ __forceinline__ void out_step(float (&acc)[80], uint32_t (&f)[4][4], uint32_t (&fp)[4][4], int it, int accum, uint32_t sb, uint32_t arow,
                                         uint32_t bars, uint32_t lead) {
  const int s = it % 5;
  mbar_wait_u(bars + B_OF + 8 * s, it / 5);
  const uint32_t st = sb + o_stage(s);
#pragma unroll
  for (int kk = 0; kk < 4; kk++)
    asm volatile("ldmatrix.sync.aligned.m8n8.x4.shared.b16 {%0,%1,%2,%3}, [%4];"
                 : "=r"(f[kk][0]), "=r"(f[kk][1]), "=r"(f[kk][2]), "=r"(f[kk][3]) : "r"(sb + o_stage_a(s) + arow + kk * 2048) : "memory");
  const uint64_t bd = mkdesc(st + 16384, 2560, 128, 0);
  wg_fence();
#pragma unroll
  for (int kk = 0; kk < 4; kk++) {
    mma_n80_rs_tb(*(float(*)[40])acc, f[kk][0], f[kk][1], f[kk][2], f[kk][3], bd + kk * 320, accum | kk);
    mma_n80_rs_tb(*(float(*)[40])(acc + 40), f[kk][0], f[kk][1], f[kk][2], f[kk][3], bd + kk * 320 + 80, accum | kk);
  }
  wg_commit();
  wg_wait<1>();
#pragma unroll
  for (int i = 0; i < 4; i++) pin(fp[i]);
  mbar_arrive_if(bars + B_OE + 8 * ((it + 4) % 5), lead && accum);
}

__device__ __forceinline__ void middle(uint8_t* smem, int wg, int w4, int lane, uint32_t cm, uint32_t neg1) {
  const uint32_t sb = smem_u32(smem), bars = sb + OFF_BAR, lead = (threadIdx.x & 127) == 0;
  const int t = lane & 3, mi = lane >> 3, r = wg & 1, u = wg >> 1;
  const bool slow = __any_sync(~0u, *(volatile uint32_t*)(smem + OFF_MISC + 20 + r * 4));
  if (u == 0) {
    const uint32_t ak = sb + OFF_AK + r * KV_SLOT, wph = sb + OFF_WPH;
    const uint32_t pka = sb + OFF_PHK + (r * 8 + w4 * 2 + (mi & 1)) * 640 + (mi >> 1) * 128 + (lane & 7) * 16;
    float pp[2][12], pn[2][12];
    wg_fence();
    issue_proj(pp, ak, wph);
    issue_proj(pn, ak + 6144, wph + 2304);
    wg_commit();
    wg_wait<0>();
    pin(pp[0]); pin(pp[1]); pin(pn[0]); pin(pn[1]);
    mbar_arrive_if(bars + B_KE + 16, lead);
    mbar_arrive_if(bars + B_KE + 24, lead);
#pragma unroll 1
    for (int i = 0; i < 4; i += 2) {
      uint32_t f[2][10];
      hedgehog2(pp, f, t);
#pragma unroll
      for (int j = 0; j < 2; j++) {
        stsm4(pka + (i + j) * 10240, f[j][0], f[j][1], f[j][2], f[j][3]);
        stsm4(pka + (i + j) * 10240 + 256, f[j][4], f[j][5], f[j][6], f[j][7]);
        stsm2(pka + (i + j) * 10240 + 512, f[j][8], f[j][9]);
      }
#pragma unroll
      for (int k = 0; k < 24; k++) pp[k / 12][k % 12] = pn[k / 12][k % 12];
    }
    float (&pa)[12] = pp[0], (&pb)[12] = pp[1];
    fence_async_smem();
    bar_sync(NB_PHIK, 256);
    wg_fence();
#pragma unroll
    for (int j = 0; j < 2; j++) {
      const uint64_t ad = mkdesc(sb + OFF_PHK + (r * 2 + j) * 10240, 640, 128, 0), vd = mkdesc(sb + OFF_V + (r * 2 + j) * 3072, 384, 128, 0);
#pragma unroll
      for (int ks = 0; ks < 8; ks++) mma_n24_ss_tatb(j ? pb : pa, ad + ks * 80, vd + (ks >> 2) * 768 + (ks & 3) * 48, ks);
    }
    wg_commit();
    wg_wait<0>();
    pin(pa); pin(pb);
    bar_sync(NB_WG + wg, 128);
    float2* dst = (float2*)(smem + OFF_PHK + r * 20480) + w4 * 192 + lane;
    if (w4 < 3) {
      dst[0] = make_float2(pa[0], pa[1]); dst[32] = make_float2(pa[4], pa[5]); dst[64] = make_float2(pa[8], pa[9]);
      dst[1280] = make_float2(pb[0], pb[1]); dst[1312] = make_float2(pb[4], pb[5]); dst[1344] = make_float2(pb[8], pb[9]);
    }
    if (w4 < 2) {
      dst[96] = make_float2(pa[2], pa[3]); dst[128] = make_float2(pa[6], pa[7]); dst[160] = make_float2(pa[10], pa[11]);
      dst[1376] = make_float2(pb[2], pb[3]); dst[1408] = make_float2(pb[6], pb[7]); dst[1440] = make_float2(pb[10], pb[11]);
    }
    fence_async_smem();
    bar_arrive(NB_TAIL, 288);
  }
  {
    const uint32_t gate = sb + OFF_GATE + (r * 64 + w4 * 16 + (lane >> 2)) * 8, qs = sb + OFF_Q + r * 12288;
    const uint32_t kb = bars + u * 64;
    AttnDesc d0;
    d0.k = mkdesc(sb + u * KV_CHUNK, 128, 384, 0); d0.k2 = mkdesc(sb + u * KV_CHUNK + 256, 0, 384, 0);
    d0.v = mkdesc(sb + u * KV_CHUNK + 6144, 384, 128, 0);
    const uint32_t qa = qs + u * 3072 + w4 * 768 + lane * 4;
#pragma unroll 1
    for (int pass = 0; pass < 2; pass++) {
      float o[12], s0[32];
      uint32_t q[8];
      load_q(q, qa + pass * 6144);
      q[6] = q[7] = neg1 + 1;
      if (!slow) {
        uint32_t p0[16], p1[16] = {};
        mbar_wait_u(kb + B_KF, 0);
        wg_fence();
        issue_qk(s0, q, d0, 0);
        wg_commit();
        wg_wait<0>();
        pin(s0);
#pragma unroll 1
        for (int turn = 0; turn < 4; turn++) {
          const int ph = turn & 1;
          AttnDesc d;
          asm volatile("mov.b64 %0, %3;\nmov.b64 %1, %4;\nmov.b64 %2, %5;" : "=l"(d.k), "=l"(d.k2), "=l"(d.v) : "l"(d0.k), "l"(d0.k2), "l"(d0.v));
          attn_chunk<0>(s0, p0, p1, o, q, d, turn, kb + B_KF + 8, ph, kb, lead && turn, cm, neg1);
          attn_chunk<1>(s0, p0, p1, o, q, d, 1, kb + B_KF + 16, ph, kb, lead, cm, neg1);
          attn_chunk<2>(s0, p0, p1, o, q, d, 1, kb + B_KF + 24, ph, kb, lead, cm, neg1);
          attn_chunk<3>(s0, p0, p1, o, q, d, 1, kb + B_KF + (turn == 3 ? 24 : 0), turn == 3 ? 1 : ph ^ 1, kb, lead, cm, neg1);
        }
        wg_wait<0>();
        pin(o); pin(p1); pin(q);
        mbar_arrive_if(kb + B_KE + 24, lead);
      } else {
        uint32_t p[16];
        float m0 = -INFINITY, m1 = -INFINITY;
#pragma unroll
        for (int i = 0; i < 12; i++) o[i] = 0.f;
#pragma unroll 1
        for (int j = 0; j < 32; j++) {
          const int slot = (j >> 1) & 3;
          const uint32_t co = slot * 1536 + (j & 1) * 192, neg = (POLY_MASK >> ((j & 1) * 8)) & 0xFF;
          mbar_wait_u(kb + B_KF + 8 * slot, (j >> 3) & 1);
          wg_fence();
          issue_qk(s0, q, d0, co);
          wg_commit();
          wg_wait<0>();
          pin(s0);
          float n0 = m0, n1 = m1;
#pragma unroll
          for (int g = 0; g < 8; g++) { n0 = fmaxf(n0, fmaxf(s0[4 * g], s0[4 * g + 1])); n1 = fmaxf(n1, fmaxf(s0[4 * g + 2], s0[4 * g + 3])); }
          n0 = fmaxf(n0, __shfl_xor_sync(~0u, n0, 1)); n1 = fmaxf(n1, __shfl_xor_sync(~0u, n1, 1));
          n0 = fmaxf(n0, __shfl_xor_sync(~0u, n0, 2)); n1 = fmaxf(n1, __shfl_xor_sync(~0u, n1, 2));
          const float c0 = ex2(m0 - n0), c1 = ex2(m1 - n1);
          m0 = n0; m1 = n1;
#pragma unroll
          for (int i = 0; i < 3; i++) { o[4 * i] *= c0; o[4 * i + 1] *= c0; o[4 * i + 2] *= c1; o[4 * i + 3] *= c1; }
#pragma unroll
          for (int g = 0; g < 8; g++) {
            const uint32_t sg = ((neg >> g) & 1) ? 0x80008000u : 0u;
            p[2 * g] = packbf(ex2(s0[4 * g] - m0), ex2(s0[4 * g + 1] - m0)) ^ sg;
            p[2 * g + 1] = packbf(ex2(s0[4 * g + 2] - m1), ex2(s0[4 * g + 3] - m1)) ^ sg;
          }
          wg_fence();
          issue_pv(o, p, d0.v + co, 1);
          wg_commit();
          wg_wait<0>();
          pin(o); pin(p);
          mbar_arrive_if(kb + B_KE + 8 * slot, lead && (j & 1));
        }
      }
      mbar_wait_u(bars + B_G, 0);
      stage_o(o, u, qs + pass * 6144, w4, lane, 0.f, lds_f2(gate).y, lds_f2(gate + 64).y);
      if (pass == 0) {
        if (u == 1) {
          const uint32_t aq = sb + OFF_AQ + r * 12288;
          const float g0 = lds_f2(gate).x, g1 = lds_f2(gate + 64).x;
#pragma unroll 1
          for (int j = 0; j < 2; j++) {
            float pp[2][12];
            wg_fence();
            issue_proj(pp, aq + j * 6144, sb + OFF_WPH + j * 2304);
            wg_commit();
            wg_wait<0>();
            pin(pp[0]); pin(pp[1]);
            uint32_t f[2][10];
            hedgehog2(pp, f, t);
            pin(f[0]); pin(f[1]);
            const uint64_t kvd = mkdesc(sb + OFF_V + j * 3840, 384, 128, 0), kvd2 = mkdesc(sb + OFF_V + j * 3840 + 1536, 0, 128, 0);
            wg_fence();
#pragma unroll
            for (int i = 0; i < 2; i++) {
              mma_n24_rs_tb(pp[i], f[i][0], f[i][1], f[i][2], f[i][3], kvd + i * 120, 0);
              mma_n24_rs_tb(pp[i], f[i][4], f[i][5], f[i][6], f[i][7], kvd + i * 120 + 48, 1);
              mma_n24_rs_tb(pp[i], f[i][8], f[i][9], 0u, 0u, kvd2 + i * 120, 1);
            }
            wg_commit();
            wg_wait<0>();
            pin(pp[0]); pin(pp[1]); pin(f[0]); pin(f[1]);
            stage_o(pp[0], 0, aq + j * 5120, w4, lane, 1e-6f, g0, g1);
            stage_o(pp[1], 1, aq + j * 5120, w4, lane, 1e-6f, g0, g1);
          }
        }
        fence_async_smem();
        bar_arrive(NB_READ, 544);
      }
    }
    fence_async_smem();
    bar_arrive(NB_LAST, 544);
  }
}

__global__ void __cluster_dims__(2, 1, 1) __launch_bounds__(640, 1)
fused_block(const __grid_constant__ Maps maps, const __nv_bfloat16* __restrict__ x, const __nv_bfloat16* __restrict__ wphi,
            const __nv_bfloat16* __restrict__ gate_w, const uint8_t* __restrict__ woa, const uint8_t* __restrict__ wob, uint32_t cm, uint32_t neg1) {
  extern __shared__ __align__(1024) uint8_t smem[];
  const uint32_t sb = smem_u32(smem), bars = sb + OFF_BAR;
  const int warp = __shfl_sync(~0u, threadIdx.x >> 5, 0), lane = threadIdx.x & 31, wg = warp >> 2;
  const int bid = blockIdx.x;
  const int mt = (bid & 1) + 2 * (bid >> 4), hg = (bid >> 1) & 7;
  const int half = bid & 1, nt = (bid >> 1) & 3, mt3 = bid >> 3;
  if (warp == 16) {
    if (lane == 0) {
#pragma unroll
      for (int i = 0; i < W_NST; i++) { mbar_init(bars + B_WF + 8 * i, 1); mbar_init(bars + B_WE + 8 * i, 4); }
      mbar_init(bars + B_Z, 1);
      mbar_init(bars + B_X, 1);
      *(uint4*)(smem + OFF_MISC) = make_uint4(0u, 0u, 0u, 0u);
      asm volatile("fence.mbarrier_init.release.cluster;" ::: "memory");
      mbar_expect(bars + B_WF, W_STAGE);
    }
    __syncwarp();
  }
  asm volatile("barrier.cluster.arrive.relaxed.aligned;" ::: "memory");
  if ((warp | 1) == 17) {
    bar_sync(0, 64);
    if (lane == 0) w_load<false>(maps, 0, sb, bars + B_WF, hg, warp & 1);
    __syncwarp();
  }

  if (wg == 4) {
    reg_dec<32>();
    asm volatile("barrier.cluster.wait.aligned;" ::: "memory");
    if (warp == 16) {
      if (lane == 0) {
        for (int it = 1; it < 20; it++) {
          const int s = it % W_NST;
          if (it >= W_NST) mbar_wait(bars + B_WE + 8 * s, ((it / W_NST) - 1) & 1);
          mbar_expect(bars + B_WF + 8 * s, W_STAGE);
          w_load<true>(maps, it, sb + s * W_STAGE, bars + B_WF + 8 * s, hg, half);
        }
      }
      __syncwarp();
      bar_sync(NB_HELP, 128);
      const uint32_t epoch = *(volatile uint32_t*)(smem + OFF_MISC + 16);
      if (lane == 0) {
        kv_stream(sb, hg, 0, epoch);
        cnt_wait(C_WO, NCTA * epoch);
        cnt_wait(C_OA + mt3, 8 * epoch);
        mbar_wait(bars + B_RF, 0);
        const uint8_t* ga = g_OAB + (size_t)mt3 * 327680 + half * 5 * 8192;
        for (int it = 0; it < 10; it++) {
          const int s = it % 5, ks = it < 5 ? it : it + 5;
          if (it >= 2 && it < 5) {
            mbar_wait(bars + B_P1, 0);
            mbar_wait(bars + B_KE + 8 * (it - 1), 0);
            mbar_wait(bars + B_KE + 64 + 8 * (it - 1), 0);
          }
          if (it >= 5) mbar_wait(bars + B_OE + 8 * s, 0);
          const uint32_t d = sb + o_stage(s), da = sb + o_stage_a(s), b = bars + B_OF + 8 * s;
          if (it == 1) {
            mbar_expect(bars + B_OF + 32, O_STAGE);
            bulk_g2s(sb + o_stage_a(4), ga + 4 * 8192, 8192, bars + B_OF + 32);
            bulk_g2s(sb + o_stage_a(4) + 8192, ga + 4 * 8192 + 163840, 8192, bars + B_OF + 32);
          }
          if (it != 4) mbar_expect(b, O_STAGE);
          bulk_g2s(d + 16384, g_WOI + (size_t)nt * 409600 + (ks + half * 5) * 20480, 20480, b);
          if (it == 7) { cnt_wait(C_OB + mt3, 8 * epoch); }
          if (it == 4) continue;
          bulk_g2s(da, ga + ks * 8192, 8192, b);
          bulk_g2s(da + 8192, ga + ks * 8192 + 163840, 8192, b);
        }
      }
    } else if (warp == 17) {
      uint32_t epoch = 0;
      if (lane == 0) {
#pragma unroll
        for (int i = 0; i < 8; i++) { mbar_init(bars + B_KF + (i >> 2) * 64 + 8 * (i & 3), 1); mbar_init(bars + B_KE + (i >> 2) * 64 + 8 * (i & 3), 2); }
#pragma unroll
        for (int i = 0; i < 5; i++) { mbar_init(bars + B_OF + 8 * i, 1); mbar_init(bars + B_OE + 8 * i, 2); }
        mbar_init(bars + B_RF, 1);
        mbar_init(bars + B_G, 1);
        mbar_init(bars + B_P1, 1);
        mbar_init(bars + B_R, 1);
        fence_async_smem();
        epoch = atomicAdd(g_CNT + C_START * 8, 1u) / NCTA + 1;
        *(volatile uint32_t*)(smem + OFF_MISC + 16) = epoch;
      }
      epoch = __shfl_sync(~0u, epoch, 0);
      if (lane < 30) { uint4* z = (uint4*)(g_KVA + hg * 1920 + mt * 120) + lane * 2; z[0] = z[1] = make_uint4(0u, 0u, 0u, 0u); }
      __syncwarp();
      asm volatile("fence.acq_rel.gpu;" ::: "memory");
      bar_arrive(NB_HELP, 128);
#pragma unroll 1
      for (int e = lane; e < 96; e += 32) {
        const int i = e / 24, slot = e % 24;
        int d = -1;
        if (i & 1) { if (slot < 16) d = slot + 4; else if (slot >= 20) d = slot - 20; }
        else if (slot < 20) d = slot;
        uint2 v[5] = {};
        if (d >= 0) {
#pragma unroll
          for (int u = 0; u < 5; u++) v[u] = __ldg((const uint2*)(wphi + ((hg * 4 + i) * 20 + d) * 20) + u);
        }
        uint8_t* dst = smem + OFF_WPH + i * 1152 + (slot >> 3) * 384 + (slot & 7) * 16;
        *(uint4*)dst = make_uint4(v[0].x, v[0].y, v[1].x, v[1].y);
        *(uint4*)(dst + 128) = make_uint4(v[2].x, v[2].y, v[3].x, v[3].y);
        *(uint4*)(dst + 256) = make_uint4(v[4].x, v[4].y, v[4].x, v[4].y);
      }
      fence_async_smem();
      bar_sync(NB_STAGED, 288);
      if (lane == 0) {
        bulk_s2g(g_KMAX + hg * 16 + mt, sb + OFF_MISC, 16);
        bulk_commit_wait();
        cnt_add_done(C_KM + hg);
#pragma unroll 1
        for (int i = 0; i < 16; i++) {
          bulk_s2g(g_KV + (size_t)((i >> 3) * NH + hg * 4 + (i & 3)) * IMG_HEAD + (mt * 2 + ((i >> 2) & 1)) * 3072, sb + OFF_Q + i * 3072, 3072);
          __nanosleep(100);
        }
        bulk_commit_wait();
        cnt_add_done(C_KV + hg);
        cnt_wait(C_KM + hg, 16 * epoch);
      }
      __syncwarp();
      {
        uint4 v = ldg_cg4(g_KMAX + hg * 16 + (lane & 15));
        v.x = __reduce_max_sync(~0u, v.x); v.y = __reduce_max_sync(~0u, v.y); v.z = __reduce_max_sync(~0u, v.z); v.w = __reduce_max_sync(~0u, v.w);
        if (lane < 4) *(volatile float*)(smem + OFF_MISC + lane * 4) =
            sqrt_ap(__uint_as_float(lane == 0 ? v.x : lane == 1 ? v.y : lane == 2 ? v.z : v.w)) * (QSCALE * 1.02f);
      }
      bar_arrive(NB_FREE, 288);
      bar_sync(NB_TAIL, 288);
      if (lane == 0) {
#pragma unroll 1
        for (int i = 0; i < 4; i++)
          asm volatile("cp.reduce.async.bulk.global.shared::cta.bulk_group.add.f32 [%0], [%1], %2;" ::"l"(g_KVA + (hg * 4 + i) * 480),
                       "r"(sb + OFF_PHK + i * 10240), "r"(3840) : "memory");
        bulk_commit_wait();
        cnt_add_done(C_KVP + hg);
        cnt_wait(C_GATE + mt, 8 * epoch);
      }
      __syncwarp();
      {
        const uint4 g0 = ldg_cg4(g_GATE + mt * 128 + lane * 2), g1 = ldg_cg4(g_GATE + mt * 128 + 64 + lane * 2);
        *(uint4*)(smem + OFF_GATE + lane * 16) = g0;
        *(uint4*)(smem + OFF_GATE + 512 + lane * 16) = g1;
      }
      if (lane == 0) {
        cnt_wait(C_KVP + hg, 16 * epoch);
        mbar_expect(bars + B_R, 15360);
        bulk_g2s(sb + OFF_KVS, g_KVA + hg * 1920, 15360, bars + B_R);
      }
      mbar_wait(bars + B_R, 0);
#pragma unroll 4
      for (int e = lane; e < 960; e += 32) {
        const float4 v = *(const float4*)(smem + OFF_KVS + e * 16);
        *(uint2*)(smem + OFF_V + e * 8) = make_uint2(packbf(v.x, v.y), packbf(v.z, v.w));
      }
      fence_async_smem();
      __syncwarp();
      if (lane == 0) mbar_arrive(bars + B_G);
      uint8_t* og = g_OAB + (size_t)mt * 327680;
      bar_sync(NB_READ, 544);
      if (lane == 0) {
#pragma unroll 1
        for (int w = 0; w < 2; w++) {
          bulk_s2g(og + w * 163840 + hg * 10240, sb + OFF_AQ + w * 12288, 10240);
          bulk_s2g(og + w * 163840 + (80 + bgroup(hg * 10)) * 1024, sb + OFF_Q + w * 12288, 5120);
        }
        bulk_commit_wait();
        mbar_arrive(bars + B_RF);
        cnt_add_done(C_OA + mt);
      }
      __syncwarp();
      bar_sync(NB_LAST, 544);
      if (lane == 0) {
        bulk_s2g(og + (80 + bgroup(hg * 10 + 5)) * 1024, sb + OFF_Q + 6144, 5120);
        bulk_s2g(og + 163840 + (80 + bgroup(hg * 10 + 5)) * 1024, sb + OFF_Q + 12288 + 6144, 5120);
        bulk_commit_wait();
        cnt_add_done(C_OB + mt);
      }
    } else if (warp == 18) {
      bar_sync(NB_HELP, 128);
      if (lane == 0) { kv_stream(sb, hg, 1, *(volatile uint32_t*)(smem + OFF_MISC + 16)); mbar_arrive(bars + B_P1); }
    } else {
      bar_sync(NB_HELP, 128);
#pragma unroll 1
      for (int kg = bid; kg < 160; kg += NCTA) {
        const uint8_t* src = (kg < 80 ? woa + (size_t)kg * 10240 : wob + (size_t)(kg - 80) * 10240) + (lane & 7) * 1280 + (lane >> 3) * 16;
        uint8_t* dst = g_WOI + (kg < 80 ? kg : 80 + bgroup(kg - 80)) * 2560 + (lane & 7) * 16 + (lane >> 3) * 128;
#pragma unroll 1
        for (int n4 = 0; n4 < 4; n4++) {
          uint4 v[5];
#pragma unroll
          for (int u = 0; u < 5; u++) v[u] = __ldg((const uint4*)(src + (n4 * 20 + u * 4) * 16));
#pragma unroll
          for (int u = 0; u < 5; u++) *(uint4*)(dst + (size_t)n4 * 409600 + u * 512) = v[u];
        }
      }
      __syncwarp();
      if (lane == 0) cnt_add(C_WO);
    }
  } else {
    const int w4 = warp & 3;
    const uint32_t lead = (threadIdx.x & 127) == 0;
    if (wg >= 2) {
      const int ht = threadIdx.x - 256;
      reg_dec<24>();
      asm volatile("barrier.cluster.wait.aligned;" ::: "memory");
      __nanosleep(2500);
      {
        const int row = mt * 128 + hg * 16 + (ht >> 4);
        const uint4* xr = (const uint4*)(x + (size_t)row * DM) + (ht & 15);
        const uint4* gr = (const uint4*)gate_w + (ht & 15);
        float acc = 0.f;
#pragma unroll 1
        for (int i = 0; i < 5; i++) {
          const uint4 a = __ldg(xr + i * 16), g = __ldg(gr + i * 16);
          const uint32_t av[4] = {a.x, a.y, a.z, a.w}, gv[4] = {g.x, g.y, g.z, g.w};
#pragma unroll
          for (int j = 0; j < 4; j++) {
            uint32_t p;
            asm("mul.rn.bf16x2 %0, %1, %2;" : "=r"(p) : "r"(av[j]), "r"(gv[j]));
            acc += bf_lo(p) + bf_hi(p);
          }
        }
#pragma unroll
        for (int o = 8; o; o >>= 1) acc += __shfl_xor_sync(~0u, acc, o);
        if ((ht & 15) == 0) {
          const float g = bf_round(__fdividef(1.f, 1.f + __expf(-bf_round(acc))));
          g_GATE[row] = make_float2(g, bf_round(1.f - g));
        }
      }
      bar_sync(NB_BG, 256);
      if (ht == 0) { cnt_add(C_GATE + mt); }
      bar_sync(NB_EPI, 512);
      reg_inc<112>();
    } else {
    const uint8_t* xp = (const uint8_t*)x + (size_t)(mt * 128 + warp * 16 + (lane >> 2)) * 1280 + (lane & 3) * 16;
    uint4 xa[4], xb[4];
    x_load(xa, xp, 0);
    x_load(xb, xp, 1);
    reg_inc<200>();
    asm volatile("barrier.cluster.wait.aligned;" ::: "memory");
    const int t = lane & 3, mi = lane >> 3;
    {
      const uint32_t sbase = sb + wg * 12288 + (w4 * 2 + (mi & 1)) * 384 + (lane & 7) * 16;
      const uint32_t ad01 = sbase + (mi >> 1) * 128, ad2 = sbase + (mi >> 1) * 3072 + 256;
      float a1[2][64], a2[24];
      uint32_t fa[4][4] = {}, fb[4][4] = {};
#pragma unroll 1
      for (int tile = 0; tile < 2; tile++) {
#pragma unroll 1
        for (int ks = 0; ks < 10; ks += 2) {
          gemm_step(a1, a2, xa, fa, fb, xp, tile * 10 + ks, ks, sb, bars, lead);
          gemm_step(a1, a2, xb, fb, fa, xp, tile * 10 + ks + 1, 1, sb, bars, lead);
        }
        wg_wait<0>();
        pin(a1[0]); pin(*(float(*)[32])a1[1]); pin(a2);
#pragma unroll
        for (int i = 0; i < 4; i++) pin(fb[i]);
        mbar_arrive_pair(bars + B_WE + 8 * 4, lead);
        if (tile == 0) {
          if (hg & 1) epilogue0<4>(a1, a2, warp * 2, lane, ad01, ad2, sb + OFF_MISC);
          else epilogue0<0>(a1, a2, warp * 2, lane, ad01, ad2, sb + OFF_MISC);
          fence_async_smem();
          bar_arrive(NB_STAGED, 288);
        }
      }
      bar_sync(NB_FREE, 288);
#pragma unroll
      for (int s = 0; s < 6; s++) mbar_arrive_if(bars + B_KE + (s < 4 ? 64 : 0) + 8 * (s & 3), lead);
      mbar_wait_u(bars + B_WE + 8 * 4, 1);
      uint32_t xq[4][2];
      bool unsafe;
      if (hg & 1) { unsafe = epilogue1a<4>(a1, a2, xq, smem, wg, t, ad01, ad2); epilogue1b<4>(a1, a2, xq, t, ad01, ad2); }
      else { unsafe = epilogue1a<0>(a1, a2, xq, smem, wg, t, ad01, ad2); epilogue1b<0>(a1, a2, xq, t, ad01, ad2); }
      if (lead) *(volatile uint32_t*)(smem + OFF_MISC + 20 + wg * 4) = unsafe;
      fence_async_smem();
      reg_dec<112>();
      bar_sync(NB_EPI, 512);
    }
    }
    middle(smem, wg, w4, lane, cm, neg1);
    if (wg >= 2) { reg_dec<24>(); return; }
    {
      if (lane == 0) asm volatile("prefetch.tensormap [%0];" ::"l"(&maps.out) : "memory");
      __syncwarp();
      asm volatile("barrier.cluster.arrive.relaxed.aligned;" ::: "memory");
      reg_inc<160>();
      float acc[80];
      uint32_t fa[4][4] = {}, fb[4][4] = {};
      const uint32_t arow = wg * 8192 + (lane >> 4) * 1024 + w4 * 256 + (lane & 15) * 16;
#pragma unroll 1
      for (int it = 0; it < 10; it += 2) {
        out_step(acc, fa, fb, it, it, sb, arow, bars, lead);
        out_step(acc, fb, fa, it + 1, 1, sb, arow, bars, lead);
      }
      wg_wait<0>();
      pin(acc);
#pragma unroll
      for (int i = 0; i < 4; i++) pin(fb[i]);
      asm volatile("barrier.cluster.wait.aligned;" ::: "memory");
      uint32_t remote, rbar;
      asm volatile("mapa.shared::cluster.u32 %0, %1, %2;" : "=r"(remote) : "r"(sb + OFF_Q + threadIdx.x * 16), "r"(half ^ 1));
      asm volatile("mapa.shared::cluster.u32 %0, %1, %2;" : "=r"(rbar) : "r"(bars + B_X), "r"(half ^ 1));
      if (threadIdx.x == 0) mbar_expect(bars + B_X, 20480);
#pragma unroll
      for (int j = 0; j < 5; j++) {
        uint32_t v[4];
#pragma unroll
        for (int u = 0; u < 4; u++) v[u] = half ? packbf(acc[8 * j + 2 * u], acc[8 * j + 2 * u + 1]) : packbf(acc[40 + 8 * j + 2 * u], acc[41 + 8 * j + 2 * u]);
        asm volatile("st.async.weak.shared::cluster.mbarrier::complete_tx::bytes.v4.b32 [%0], {%1,%2,%3,%4}, [%5];" ::"r"(remote + j * 4096), "r"(v[0]),
                     "r"(v[1]), "r"(v[2]), "r"(v[3]), "r"(rbar) : "memory");
      }
      mbar_wait_u(bars + B_OE, 1);
      mbar_wait_u(bars + B_X, 0);
      const uint32_t ob = sb + OFF_V + warp * 2560;
      const uint32_t oa = ob + (lane & 15) * 160 + (lane >> 4) * 16;
      uint32_t pk[20];
#pragma unroll
      for (int j = 0; j < 5; j++) {
        const uint4 r = *(const uint4*)(smem + OFF_Q + j * 4096 + threadIdx.x * 16);
        const uint32_t rv[4] = {r.x, r.y, r.z, r.w};
#pragma unroll
        for (int u = 0; u < 4; u++) {
          const float v0 = half ? acc[40 + 8 * j + 2 * u] : acc[8 * j + 2 * u], v1 = half ? acc[41 + 8 * j + 2 * u] : acc[8 * j + 2 * u + 1];
          pk[4 * j + u] = packbf(v0 + bf_lo(rv[u]), v1 + bf_hi(rv[u]));
        }
      }
#pragma unroll
      for (int j = 0; j < 10; j += 2) stsm4(oa + j * 16, pk[2 * j], pk[2 * j + 1], pk[2 * j + 2], pk[2 * j + 3]);
      fence_async_smem();
      __syncwarp();
      if (lane == 0) {
        asm volatile("cp.async.bulk.tensor.2d.global.shared::cta.bulk_group [%0, {%2,%3}], [%1];" ::"l"(&maps.out), "r"(ob), "r"(nt * 160 + half * 80),
                     "r"(mt3 * 128 + warp * 16) : "memory");
        asm volatile("cp.async.bulk.commit_group;" ::: "memory");
        asm volatile("cp.async.bulk.wait_group.read 0;" ::: "memory");
      }
    }
  }
}

typedef CUresult (*EncodeFn)(CUtensorMap*, CUtensorMapDataType, cuuint32_t, void*, const cuuint64_t*, const cuuint64_t*, const cuuint32_t*,
                             const cuuint32_t*, CUtensorMapInterleave, CUtensorMapSwizzle, CUtensorMapL2promotion, CUtensorMapFloatOOBfill);

void encode(EncodeFn fn, CUtensorMap* m, const void* p, int rank, const cuuint64_t* dims, const cuuint64_t* strides, const cuuint32_t* box,
            CUtensorMapSwizzle sw) {
  const cuuint32_t es[5] = {1, 1, 1, 1, 1};
  fn(m, CU_TENSOR_MAP_DATA_TYPE_BFLOAT16, rank, const_cast<void*>(p), dims, strides, box, es, CU_TENSOR_MAP_INTERLEAVE_NONE, sw,
     CU_TENSOR_MAP_L2_PROMOTION_L2_128B, CU_TENSOR_MAP_FLOAT_OOB_FILL_NONE);
}

}

extern "C" void kernel_launch(void* const* d_in, const int* in_sizes, int n_in, void* d_out, int out_size) {
  (void)in_sizes; (void)n_in; (void)out_size;
  static EncodeFn enc = nullptr;
  if (!enc) {
    void* fn = nullptr;
    cudaDriverEntryPointQueryResult qr;
    cudaGetDriverEntryPoint("cuTensorMapEncodeTiled", &fn, cudaEnableDefault, &qr);
    enc = (EncodeFn)fn;
    cudaFuncSetAttribute(fused_block, cudaFuncAttributeMaxDynamicSharedMemorySize, SMEM_BYTES);
  }
  Maps maps;
  {
    const cuuint64_t dx[2] = {640, 2048}, sx[1] = {1280};
    const cuuint32_t bo[2] = {80, 16};
    encode(enc, &maps.out, d_out, 2, dx, sx, bo, CU_TENSOR_MAP_SWIZZLE_NONE);
    const cuuint64_t dw[5] = {1920, 2, 4, 4, 20}, sw[4] = {3840, 8 * 3840, 2 * 3840, 32 * 3840};
    const cuuint32_t b64[5] = {64, 2, 4, 4, 1}, b16[5] = {16, 2, 4, 4, 1};
    encode(enc, &maps.a64, d_in[1], 5, dw, sw, b64, CU_TENSOR_MAP_SWIZZLE_128B);
    encode(enc, &maps.a16, d_in[1], 5, dw, sw, b16, CU_TENSOR_MAP_SWIZZLE_32B);
    encode(enc, &maps.b64, d_in[5], 5, dw, sw, b64, CU_TENSOR_MAP_SWIZZLE_128B);
    encode(enc, &maps.b16, d_in[5], 5, dw, sw, b16, CU_TENSOR_MAP_SWIZZLE_32B);
  }
  fused_block<<<NCTA, 640, SMEM_BYTES, cudaStreamPerThread>>>(maps, (const __nv_bfloat16*)d_in[0], (const __nv_bfloat16*)d_in[2],
                                                               (const __nv_bfloat16*)d_in[7],
                                                               (const uint8_t*)d_in[3], (const uint8_t*)d_in[6], 0x1F801F80u, 0xFFFFFFFFu);
}
```

```cpp
#include <cuda_runtime.h>
#include <cuda_bf16.h>
#include <cuda.h>
#include <stdint.h>

namespace {

constexpr int SEQ = 2048, DM = 640, NH = 32, NCTA = 128;
constexpr int IMG_HEAD = SEQ * 48;
#define POLY_MASK 0xF8F8u
constexpr float LOG2E = 1.4426950408889634f;
constexpr float QSCALE = 0.22360679774997896f * 1.4426950408889634f;
constexpr uint32_t BF_ONE = 0x3F80u;
constexpr uint32_t BF_MAGIC = 0x43E0u;
constexpr uint32_t BF_MU_HI = 0x4025u;
constexpr uint32_t BF_MU_LO = 0x3B8Bu;
constexpr float FAST_BOUND = 40.0f;

__device__ __align__(1024) uint8_t g_KV[2 * NH * IMG_HEAD];
__device__ __align__(1024) float2 g_KVA[NH * 480];
__device__ __align__(1024) float4 g_KMAX[8 * 16];
__device__ __align__(1024) float2 g_GATE[SEQ];
__device__ __align__(1024) uint8_t g_OAB[16 * 2 * 160 * 1024];
__device__ __align__(1024) uint8_t g_WOI[4 * 409600];
__device__ __align__(1024) uint32_t g_CNT[74 * 8];
constexpr int C_START = 0, C_WO = 1, C_KV = 2, C_KVP = 10, C_GATE = 26, C_OA = 42, C_OB = 58;

#define SPIN_LIMIT (1ll << 29)
#define SPIN_FAIL(code) __trap()
__device__ __forceinline__ uint32_t smem_u32(const void* p) { return (uint32_t)__cvta_generic_to_shared(p); }
__device__ __forceinline__ void mbar_init(uint32_t a, uint32_t c) { asm volatile("mbarrier.init.shared::cta.b64 [%0], %1;" ::"r"(a), "r"(c) : "memory"); }
__device__ __forceinline__ void mbar_expect(uint32_t a, uint32_t b) { asm volatile("mbarrier.arrive.expect_tx.shared::cta.b64 _, [%0], %1;" ::"r"(a), "r"(b) : "memory"); }
__device__ __forceinline__ void mbar_arrive(uint32_t a) { asm volatile("mbarrier.arrive.shared::cta.b64 _, [%0];" ::"r"(a) : "memory"); }
__device__ __forceinline__ uint32_t mbar_try(uint32_t a, uint32_t ph) {
  uint32_t ok;
  asm volatile("{\n.reg .pred p;\nmbarrier.try_wait.parity.shared::cta.b64 p, [%1], %2;\nselp.u32 %0, 1, 0, p;\n}\n" : "=r"(ok) : "r"(a), "r"(ph) : "memory");
  return ok;
}
__device__ __forceinline__ void mbar_wait(uint32_t a, uint32_t ph) {
  if (mbar_try(a, ph)) return;
  const long long t0 = clock64();
  while (!mbar_try(a, ph))
    if (clock64() - t0 > SPIN_LIMIT) { SPIN_FAIL(1000 + (a & 0x1FF) * 2 + ph); break; }
}
__device__ __forceinline__ void mbar_wait_u(uint32_t a, uint32_t ph) {
#pragma unroll 1
  for (int n = 0; n < (1 << 18); n++)
    if (__all_sync(~0u, mbar_try(a, ph))) break;
}
__device__ __forceinline__ uint32_t mbar_test(uint32_t a, uint32_t ph) {
  uint32_t ok;
  asm volatile("{\n.reg .pred p;\nmbarrier.test_wait.parity.shared::cta.b64 p, [%1], %2;\nselp.u32 %0, 1, 0, p;\n}\n" : "=r"(ok) : "r"(a), "r"(ph) : "memory");
  return ok;
}
__device__ __forceinline__ void mbar_arrive_if(uint32_t a, uint32_t flag) {
  asm volatile("{\n.reg .pred p;\nsetp.ne.u32 p, %1, 0;\n@p mbarrier.arrive.shared::cta.b64 _, [%0];\n}\n" ::"r"(a), "r"(flag) : "memory");
}
__device__ __forceinline__ void cnt_add_done(int slot) { asm volatile("red.relaxed.gpu.global.add.u32 [%0], 1;" ::"l"(g_CNT + slot * 8) : "memory"); }
__device__ __forceinline__ void cnt_add(int slot) {
  asm volatile("fence.acq_rel.gpu;" ::: "memory");
  cnt_add_done(slot);
}
__device__ __forceinline__ void cnt_wait(int slot, uint32_t target) {
  uint32_t v;
  long long t0 = 0;
  for (;;) {
    asm volatile("ld.relaxed.gpu.global.u32 %0, [%1];" : "=r"(v) : "l"(g_CNT + slot * 8) : "memory");
    if ((int32_t)(v - target) >= 0) break;
    __nanosleep(40);
    if (!t0) t0 = clock64();
    else if (clock64() - t0 > SPIN_LIMIT) { SPIN_FAIL(slot); break; }
  }
  asm volatile("ld.acquire.gpu.global.u32 %0, [%1];" : "=r"(v) : "l"(g_CNT + slot * 8) : "memory");
}
__device__ __forceinline__ void bulk_commit_wait() { asm volatile("cp.async.bulk.commit_group;\ncp.async.bulk.wait_group 0;" ::: "memory"); }
template <bool MC>
__device__ __forceinline__ void tma5(uint32_t dst, const CUtensorMap* m, int c0, int c4, uint32_t bar) {
  if (MC)
    asm volatile("cp.async.bulk.tensor.5d.shared::cluster.global.mbarrier::complete_tx::bytes.multicast::cluster [%0], [%1, {%3,%5,%5,%5,%4}], [%2], %6;"
                 ::"r"(dst), "l"(m), "r"(bar), "r"(c0), "r"(c4), "r"(0), "h"((uint16_t)3) : "memory");
  else
    asm volatile("cp.async.bulk.tensor.5d.shared::cluster.global.mbarrier::complete_tx::bytes [%0], [%1, {%3,%5,%5,%5,%4}], [%2];"
                 ::"r"(dst), "l"(m), "r"(bar), "r"(c0), "r"(c4), "r"(0) : "memory");
}
__device__ __forceinline__ void mbar_arrive_pair(uint32_t a, uint32_t flag) {
  asm volatile("{\n.reg .pred p;\n.reg .b32 r0, r1;\nsetp.ne.u32 p, %1, 0;\nmapa.shared::cluster.u32 r0, %0, 0;\nmapa.shared::cluster.u32 r1, %0, 1;\n"
               "@p mbarrier.arrive.relaxed.cluster.shared::cluster.b64 _, [r0];\n@p mbarrier.arrive.relaxed.cluster.shared::cluster.b64 _, [r1];\n}\n" ::"r"(a), "r"(flag) : "memory");
}
__device__ __forceinline__ void bulk_g2s(uint32_t dst, const void* src, uint32_t bytes, uint32_t bar) {
  asm volatile("cp.async.bulk.shared::cluster.global.mbarrier::complete_tx::bytes [%0], [%1], %2, [%3];" ::"r"(dst), "l"(src), "r"(bytes), "r"(bar) : "memory");
}
__device__ __forceinline__ void fence_async_smem() { asm volatile("fence.proxy.async.shared::cta;" ::: "memory"); }
__device__ __forceinline__ void bar_sync(int id, int n) { asm volatile("bar.sync %0, %1;" ::"r"(id), "r"(n) : "memory"); }
__device__ __forceinline__ void bar_arrive(int id, int n) { asm volatile("bar.arrive %0, %1;" ::"r"(id), "r"(n) : "memory"); }
__device__ __forceinline__ void wg_fence() { asm volatile("wgmma.fence.sync.aligned;" ::: "memory"); }
__device__ __forceinline__ void wg_commit() { asm volatile("wgmma.commit_group.sync.aligned;" ::: "memory"); }
template <int N> __device__ __forceinline__ void wg_wait() { asm volatile("wgmma.wait_group.sync.aligned %0;" ::"n"(N) : "memory"); }
template <int N> __device__ __forceinline__ void reg_inc() { asm volatile("setmaxnreg.inc.sync.aligned.u32 %0;" ::"n"(N)); }
template <int N> __device__ __forceinline__ void reg_dec() { asm volatile("setmaxnreg.dec.sync.aligned.u32 %0;" ::"n"(N)); }
template <int N> __device__ __forceinline__ void pin(float (&r)[N]) {
#pragma unroll
  for (int i = 0; i < N; i++) asm volatile("" : "+f"(r[i])::"memory");
}
template <int N> __device__ __forceinline__ void pin(uint32_t (&r)[N]) {
#pragma unroll
  for (int i = 0; i < N; i++) asm volatile("" : "+r"(r[i])::"memory");
}
__device__ __forceinline__ uint64_t mkdesc(uint32_t addr, uint32_t lbo, uint32_t sbo, uint32_t swz) {
  return (uint64_t)((addr & 0x3FFFF) >> 4) | ((uint64_t)(lbo >> 4) << 16) | ((uint64_t)(sbo >> 4) << 32) | ((uint64_t)swz << 62);
}
__device__ __forceinline__ float ex2(float x) { float y; asm("ex2.approx.ftz.f32 %0, %1;" : "=f"(y) : "f"(x)); return y; }
__device__ __forceinline__ float rcp(float x) { float y; asm("rcp.approx.ftz.f32 %0, %1;" : "=f"(y) : "f"(x)); return y; }
__device__ __forceinline__ float sqrt_ap(float x) { float y; asm("sqrt.approx.f32 %0, %1;" : "=f"(y) : "f"(x)); return y; }
__device__ __forceinline__ uint32_t packbf(float lo, float hi) { uint32_t d; asm("cvt.rn.bf16x2.f32 %0, %1, %2;" : "=r"(d) : "f"(hi), "f"(lo)); return d; }
__device__ __forceinline__ float bf_lo(uint32_t v) { return __uint_as_float(v << 16); }
__device__ __forceinline__ float bf_hi(uint32_t v) { return __uint_as_float(v & 0xFFFF0000u); }
__device__ __forceinline__ float bf_round(float x) { return bf_lo(packbf(x, 0.f)); }
__device__ __forceinline__ uint4 ldg_cg4(const void* p) { uint4 v; asm volatile("ld.global.cg.v4.b32 {%0,%1,%2,%3}, [%4];" : "=r"(v.x), "=r"(v.y), "=r"(v.z), "=r"(v.w) : "l"(p) : "memory"); return v; }
__device__ __forceinline__ void sts32(uint32_t a, uint32_t v) { asm volatile("st.shared.b32 [%0], %1;" ::"r"(a), "r"(v) : "memory"); }
__device__ __forceinline__ void stsm4(uint32_t a, uint32_t r0, uint32_t r1, uint32_t r2, uint32_t r3) {
  asm volatile("stmatrix.sync.aligned.m8n8.x4.shared.b16 [%0], {%1,%2,%3,%4};" ::"r"(a), "r"(r0), "r"(r1), "r"(r2), "r"(r3) : "memory");
}

__device__ __forceinline__ void stsm2(uint32_t a, uint32_t r0, uint32_t r1) {
  asm volatile("stmatrix.sync.aligned.m8n8.x2.shared.b16 [%0], {%1,%2};" ::"r"(a), "r"(r0), "r"(r1) : "memory");
}
__device__ __forceinline__ uint4 ldg_x(const void* p) {
  uint4 v;
  asm volatile("ld.global.nc.L1::no_allocate.L2::128B.v4.b32 {%0,%1,%2,%3}, [%4];" : "=r"(v.x), "=r"(v.y), "=r"(v.z), "=r"(v.w) : "l"(p));
  return v;
}
__device__ __forceinline__ float2 lds_f2(uint32_t a) { float2 v; asm volatile("ld.shared.v2.f32 {%0,%1}, [%2];" : "=f"(v.x), "=f"(v.y) : "r"(a) : "memory"); return v; }
__device__ __forceinline__ void bulk_s2g(void* dst, uint32_t src, uint32_t bytes) {
  asm volatile("cp.async.bulk.global.shared::cta.bulk_group [%0], [%1], %2;" ::"l"(dst), "r"(src), "r"(bytes) : "memory");
}

__device__ __forceinline__ void mma_n24_ss_tb(float (&d)[12], uint64_t adesc, uint64_t bdesc, int acc) {
  asm volatile("{\n.reg .pred p;\nsetp.ne.b32 p, %14, 0;\n"
      "wgmma.mma_async.sync.aligned.m64n24k16.f32.bf16.bf16 "
      "{%0,%1,%2,%3,%4,%5,%6,%7,%8,%9,%10,%11}, "
      "%12, %13, p, 1, 1, 0, 1;\n}\n"
      : "+f"(d[0]), "+f"(d[1]), "+f"(d[2]), "+f"(d[3]), "+f"(d[4]), "+f"(d[5]), "+f"(d[6]), "+f"(d[7]),
        "+f"(d[8]), "+f"(d[9]), "+f"(d[10]), "+f"(d[11])
      : "l"(adesc), "l"(bdesc), "r"(acc));
}
__device__ __forceinline__ void mma_n128_rs_tb(float (&d)[64], uint32_t a0, uint32_t a1, uint32_t a2, uint32_t a3, uint64_t bdesc, int acc) {
  asm volatile("{\n.reg .pred p;\nsetp.ne.b32 p, %69, 0;\n"
      "wgmma.mma_async.sync.aligned.m64n128k16.f32.bf16.bf16 "
      "{%0,%1,%2,%3,%4,%5,%6,%7,%8,%9,%10,%11,%12,%13,%14,%15,"
      "%16,%17,%18,%19,%20,%21,%22,%23,%24,%25,%26,%27,%28,%29,%30,%31,"
      "%32,%33,%34,%35,%36,%37,%38,%39,%40,%41,%42,%43,%44,%45,%46,%47,"
      "%48,%49,%50,%51,%52,%53,%54,%55,%56,%57,%58,%59,%60,%61,%62,%63}, "
      "{%64,%65,%66,%67}, %68, p, 1, 1, 1;\n}\n"
      : "+f"(d[0]), "+f"(d[1]), "+f"(d[2]), "+f"(d[3]), "+f"(d[4]), "+f"(d[5]), "+f"(d[6]), "+f"(d[7]),
        "+f"(d[8]), "+f"(d[9]), "+f"(d[10]), "+f"(d[11]), "+f"(d[12]), "+f"(d[13]), "+f"(d[14]), "+f"(d[15]),
        "+f"(d[16]), "+f"(d[17]), "+f"(d[18]), "+f"(d[19]), "+f"(d[20]), "+f"(d[21]), "+f"(d[22]), "+f"(d[23]),
        "+f"(d[24]), "+f"(d[25]), "+f"(d[26]), "+f"(d[27]), "+f"(d[28]), "+f"(d[29]), "+f"(d[30]), "+f"(d[31]),
        "+f"(d[32]), "+f"(d[33]), "+f"(d[34]), "+f"(d[35]), "+f"(d[36]), "+f"(d[37]), "+f"(d[38]), "+f"(d[39]),
        "+f"(d[40]), "+f"(d[41]), "+f"(d[42]), "+f"(d[43]), "+f"(d[44]), "+f"(d[45]), "+f"(d[46]), "+f"(d[47]),
        "+f"(d[48]), "+f"(d[49]), "+f"(d[50]), "+f"(d[51]), "+f"(d[52]), "+f"(d[53]), "+f"(d[54]), "+f"(d[55]),
        "+f"(d[56]), "+f"(d[57]), "+f"(d[58]), "+f"(d[59]), "+f"(d[60]), "+f"(d[61]), "+f"(d[62]), "+f"(d[63])
      : "r"(a0), "r"(a1), "r"(a2), "r"(a3), "l"(bdesc), "r"(acc));
}
__device__ __forceinline__ void mma_n64_rs_tb(float (&d)[32], uint32_t a0, uint32_t a1, uint32_t a2, uint32_t a3, uint64_t bdesc, int acc) {
  asm volatile("{\n.reg .pred p;\nsetp.ne.b32 p, %37, 0;\n"
      "wgmma.mma_async.sync.aligned.m64n64k16.f32.bf16.bf16 "
      "{%0,%1,%2,%3,%4,%5,%6,%7,%8,%9,%10,%11,%12,%13,%14,%15,"
      "%16,%17,%18,%19,%20,%21,%22,%23,%24,%25,%26,%27,%28,%29,%30,%31}, "
      "{%32,%33,%34,%35}, %36, p, 1, 1, 1;\n}\n"
      : "+f"(d[0]), "+f"(d[1]), "+f"(d[2]), "+f"(d[3]), "+f"(d[4]), "+f"(d[5]), "+f"(d[6]), "+f"(d[7]),
        "+f"(d[8]), "+f"(d[9]), "+f"(d[10]), "+f"(d[11]), "+f"(d[12]), "+f"(d[13]), "+f"(d[14]), "+f"(d[15]),
        "+f"(d[16]), "+f"(d[17]), "+f"(d[18]), "+f"(d[19]), "+f"(d[20]), "+f"(d[21]), "+f"(d[22]), "+f"(d[23]),
        "+f"(d[24]), "+f"(d[25]), "+f"(d[26]), "+f"(d[27]), "+f"(d[28]), "+f"(d[29]), "+f"(d[30]), "+f"(d[31])
      : "r"(a0), "r"(a1), "r"(a2), "r"(a3), "l"(bdesc), "r"(acc));
}
__device__ __forceinline__ void mma_n48_rs_tb(float (&d)[24], uint32_t a0, uint32_t a1, uint32_t a2, uint32_t a3, uint64_t bdesc, int acc) {
  asm volatile("{\n.reg .pred p;\nsetp.ne.b32 p, %29, 0;\n"
      "wgmma.mma_async.sync.aligned.m64n48k16.f32.bf16.bf16 "
      "{%0,%1,%2,%3,%4,%5,%6,%7,%8,%9,%10,%11,%12,%13,%14,%15,"
      "%16,%17,%18,%19,%20,%21,%22,%23}, "
      "{%24,%25,%26,%27}, %28, p, 1, 1, 1;\n}\n"
      : "+f"(d[0]), "+f"(d[1]), "+f"(d[2]), "+f"(d[3]), "+f"(d[4]), "+f"(d[5]), "+f"(d[6]), "+f"(d[7]),
        "+f"(d[8]), "+f"(d[9]), "+f"(d[10]), "+f"(d[11]), "+f"(d[12]), "+f"(d[13]), "+f"(d[14]), "+f"(d[15]),
        "+f"(d[16]), "+f"(d[17]), "+f"(d[18]), "+f"(d[19]), "+f"(d[20]), "+f"(d[21]), "+f"(d[22]), "+f"(d[23])
      : "r"(a0), "r"(a1), "r"(a2), "r"(a3), "l"(bdesc), "r"(acc));
}
__device__ __forceinline__ void mma_n64_rs(float (&d)[32], uint32_t a0, uint32_t a1, uint32_t a2, uint32_t a3, uint64_t bdesc, int acc) {
  asm volatile("{\n.reg .pred p;\nsetp.ne.b32 p, %37, 0;\n"
      "wgmma.mma_async.sync.aligned.m64n64k16.f32.bf16.bf16 "
      "{%0,%1,%2,%3,%4,%5,%6,%7,%8,%9,%10,%11,%12,%13,%14,%15,"
      "%16,%17,%18,%19,%20,%21,%22,%23,%24,%25,%26,%27,%28,%29,%30,%31}, "
      "{%32,%33,%34,%35}, %36, p, 1, 1, 0;\n}\n"
      : "+f"(d[0]), "+f"(d[1]), "+f"(d[2]), "+f"(d[3]), "+f"(d[4]), "+f"(d[5]), "+f"(d[6]), "+f"(d[7]),
        "+f"(d[8]), "+f"(d[9]), "+f"(d[10]), "+f"(d[11]), "+f"(d[12]), "+f"(d[13]), "+f"(d[14]), "+f"(d[15]),
        "+f"(d[16]), "+f"(d[17]), "+f"(d[18]), "+f"(d[19]), "+f"(d[20]), "+f"(d[21]), "+f"(d[22]), "+f"(d[23]),
        "+f"(d[24]), "+f"(d[25]), "+f"(d[26]), "+f"(d[27]), "+f"(d[28]), "+f"(d[29]), "+f"(d[30]), "+f"(d[31])
      : "r"(a0), "r"(a1), "r"(a2), "r"(a3), "l"(bdesc), "r"(acc));
}
__device__ __forceinline__ void mma_n80_rs_tb(float (&d)[40], uint32_t a0, uint32_t a1, uint32_t a2, uint32_t a3, uint64_t bdesc, int acc) {
  asm volatile("{\n.reg .pred p;\nsetp.ne.b32 p, %45, 0;\n"
      "wgmma.mma_async.sync.aligned.m64n80k16.f32.bf16.bf16 "
      "{%0,%1,%2,%3,%4,%5,%6,%7,%8,%9,%10,%11,%12,%13,%14,%15,"
      "%16,%17,%18,%19,%20,%21,%22,%23,%24,%25,%26,%27,%28,%29,%30,%31,"
      "%32,%33,%34,%35,%36,%37,%38,%39}, "
      "{%40,%41,%42,%43}, %44, p, 1, 1, 1;\n}\n"
      : "+f"(d[0]), "+f"(d[1]), "+f"(d[2]), "+f"(d[3]), "+f"(d[4]), "+f"(d[5]), "+f"(d[6]), "+f"(d[7]),
        "+f"(d[8]), "+f"(d[9]), "+f"(d[10]), "+f"(d[11]), "+f"(d[12]), "+f"(d[13]), "+f"(d[14]), "+f"(d[15]),
        "+f"(d[16]), "+f"(d[17]), "+f"(d[18]), "+f"(d[19]), "+f"(d[20]), "+f"(d[21]), "+f"(d[22]), "+f"(d[23]),
        "+f"(d[24]), "+f"(d[25]), "+f"(d[26]), "+f"(d[27]), "+f"(d[28]), "+f"(d[29]), "+f"(d[30]), "+f"(d[31]),
        "+f"(d[32]), "+f"(d[33]), "+f"(d[34]), "+f"(d[35]), "+f"(d[36]), "+f"(d[37]), "+f"(d[38]), "+f"(d[39])
      : "r"(a0), "r"(a1), "r"(a2), "r"(a3), "l"(bdesc), "r"(acc));
}
__device__ __forceinline__ void mma_n24_rs_tb(float (&d)[12], uint32_t a0, uint32_t a1, uint32_t a2, uint32_t a3, uint64_t bdesc, int acc) {
  asm volatile("{\n.reg .pred p;\nsetp.ne.b32 p, %17, 0;\n"
      "wgmma.mma_async.sync.aligned.m64n24k16.f32.bf16.bf16 "
      "{%0,%1,%2,%3,%4,%5,%6,%7,%8,%9,%10,%11}, "
      "{%12,%13,%14,%15}, %16, p, 1, 1, 1;\n}\n"
      : "+f"(d[0]), "+f"(d[1]), "+f"(d[2]), "+f"(d[3]), "+f"(d[4]), "+f"(d[5]), "+f"(d[6]), "+f"(d[7]),
        "+f"(d[8]), "+f"(d[9]), "+f"(d[10]), "+f"(d[11])
      : "r"(a0), "r"(a1), "r"(a2), "r"(a3), "l"(bdesc), "r"(acc));
}
__device__ __forceinline__ void mma_n24_ss_tatb(float (&d)[12], uint64_t adesc, uint64_t bdesc, int acc) {
  asm volatile("{\n.reg .pred p;\nsetp.ne.b32 p, %14, 0;\n"
      "wgmma.mma_async.sync.aligned.m64n24k16.f32.bf16.bf16 "
      "{%0,%1,%2,%3,%4,%5,%6,%7,%8,%9,%10,%11}, "
      "%12, %13, p, 1, 1, 1, 1;\n}\n"
      : "+f"(d[0]), "+f"(d[1]), "+f"(d[2]), "+f"(d[3]), "+f"(d[4]), "+f"(d[5]), "+f"(d[6]), "+f"(d[7]),
        "+f"(d[8]), "+f"(d[9]), "+f"(d[10]), "+f"(d[11])
      : "l"(adesc), "l"(bdesc), "r"(acc));
}

constexpr int W_STAGE = 30720, W_NST = 5;
constexpr int KV_CHUNK = 12288, KV_SLOT = 2 * KV_CHUNK;
constexpr int O_STAGE = 36864;
constexpr int OFF_PHK = 4 * KV_SLOT;
constexpr int OFF_KVS = OFF_PHK + 2 * 10240 + 4096;
constexpr int OFF_GATE = 112640;
constexpr int OFF_Q = W_NST * W_STAGE;
constexpr int OFF_V = OFF_Q + 24576;
constexpr int OFF_AQ = OFF_V + 24576;
constexpr int OFF_WPH = OFF_AQ + 24576;
constexpr int OFF_BAR = OFF_WPH + 4608;
constexpr int B_WF = 0, B_WE = 40, B_KF = 80, B_KE = 112, B_OF = 208, B_OE = 248, B_RF = 288, B_Z = 296, B_G = 304, B_X = 312, B_P1 = 320, B_R = 328, B_F = 336;
constexpr int OFF_MISC = OFF_BAR + 352;
constexpr int SMEM_BYTES = OFF_MISC + 32;
__device__ __forceinline__ uint32_t o_stage(int s) { return s == 0 ? OFF_V : s == 1 ? OFF_Q - O_STAGE : (s - 2) * O_STAGE; }
__device__ __forceinline__ uint32_t o_stage_a(int s) { return s == 4 ? OFF_V + O_STAGE : o_stage(s); }
constexpr int NB_STAGED = 1, NB_WG = 3, NB_BG = 7, NB_NORM = 13, NB_BOUND = 14, NB_EPI = 15, NB_PHIK = 8, NB_TAIL = 9, NB_READ = 10, NB_LAST = 11, NB_HELP = 12;

template <int SEC, int J, int HF>
__device__ __forceinline__ float2 grp(const float (&a1)[2][64], const float (&a2)[24]) {
  constexpr int S = SEC & 3, J1 = (SEC & 4) ? J - 2 : J, J2 = (SEC & 4) ? J : J - 8;
  if constexpr (J1 >= 0 && J1 < 8) return make_float2(a1[S >> 1][(8 * (S & 1) + J1) * 4 + 2 * HF], a1[S >> 1][(8 * (S & 1) + J1) * 4 + 2 * HF + 1]);
  else return make_float2(a2[(2 * S + J2) * 4 + 2 * HF], a2[(2 * S + J2) * 4 + 2 * HF + 1]);
}
__device__ __forceinline__ uint32_t pks(float2 v, float s) { return packbf(v.x * s, v.y * s); }

template <int SEC, int PR>
__device__ __forceinline__ void stage_pair(const float (&a1)[2][64], const float (&a2)[24], float sc0, float sc1, float sm, uint32_t xe0, uint32_t xe1,
                                           uint32_t xo0, uint32_t xo1, uint32_t ad01, uint32_t ad2, int t) {
  const uint32_t off = 2 * PR * 3072;
  stsm4(ad01 + off, pks(grp<SEC, 5 * PR, 0>(a1, a2), sc0), pks(grp<SEC, 5 * PR, 1>(a1, a2), sc1), pks(grp<SEC, 5 * PR + 1, 0>(a1, a2), sc0),
        pks(grp<SEC, 5 * PR + 1, 1>(a1, a2), sc1));
  stsm4(ad01 + off + 3072, pks(grp<SEC, 5 * PR + 3, 0>(a1, a2), sc0), pks(grp<SEC, 5 * PR + 3, 1>(a1, a2), sc1),
        pks(grp<SEC, 5 * PR + 4, 0>(a1, a2), sc0), pks(grp<SEC, 5 * PR + 4, 1>(a1, a2), sc1));
  const uint32_t m0 = pks(grp<SEC, 5 * PR + 2, 0>(a1, a2), sc0 * sm), m1 = pks(grp<SEC, 5 * PR + 2, 1>(a1, a2), sc1 * sm);
  const bool lo = t < 2;
  stsm4(ad2 + off, lo ? m0 : xe0, lo ? m1 : xe1, lo ? xo0 : m0, lo ? xo1 : m1);
}

template <bool EXACT>
__device__ __forceinline__ bool hedgehog(const float (&p)[12], uint32_t (&f)[10], int t) {
  const bool lo = t < 2;
  bool safe = true;
#pragma unroll
  for (int hf = 0; hf < 2; hf++) {
    const float v[6] = {p[2 * hf], p[2 * hf + 1], p[4 + 2 * hf], p[5 + 2 * hf], p[8 + 2 * hf], p[9 + 2 * hf]};
    float ep[4], en[4], m0, m1;
    const float sg = lo ? LOG2E : -LOG2E;
    if (EXACT) {
      float mx = fmaxf(fmaxf(fmaxf(v[0], v[1]), fmaxf(v[2], v[3])), fmaxf(v[4], v[5]));
      float mn = fminf(fminf(fminf(v[0], v[1]), fminf(v[2], v[3])), fminf(v[4], v[5]));
      mx = fmaxf(mx, __shfl_xor_sync(~0u, mx, 1)); mn = fminf(mn, __shfl_xor_sync(~0u, mn, 1));
      mx = fmaxf(mx, __shfl_xor_sync(~0u, mx, 2)); mn = fminf(mn, __shfl_xor_sync(~0u, mn, 2));
      const float bp = -mx * LOG2E, bn = mn * LOG2E, bm = lo ? bp : bn;
#pragma unroll
      for (int i = 0; i < 4; i++) { ep[i] = ex2(fmaf(v[i], LOG2E, bp)); en[i] = ex2(fmaf(v[i], -LOG2E, bn)); }
      m0 = ex2(fmaf(v[4], sg, bm)); m1 = ex2(fmaf(v[5], sg, bm));
    } else {
#pragma unroll
      for (int i = 0; i < 4; i++) ep[i] = ex2(v[i] * LOG2E);
      const float r0 = rcp(ep[0] * ep[1]), r1 = rcp(ep[2] * ep[3]);
      en[0] = r0 * ep[1]; en[1] = r0 * ep[0]; en[2] = r1 * ep[3]; en[3] = r1 * ep[2];
      m0 = ex2(v[4] * sg); m1 = ex2(v[5] * sg);
    }
    const float ms = m0 + m1;
    float sp = (ep[0] + ep[1]) + (ep[2] + ep[3]) + (lo ? ms : 0.f);
    float sn = (en[0] + en[1]) + (en[2] + en[3]) + (lo ? 0.f : ms);
    sp += __shfl_xor_sync(~0u, sp, 1); sn += __shfl_xor_sync(~0u, sn, 1);
    sp += __shfl_xor_sync(~0u, sp, 2); sn += __shfl_xor_sync(~0u, sn, 2);
    safe = safe && sp <= 1.0e12f && sn <= 1.0e12f;
    const float r = rcp(sp * sn), rp = r * sn, rn = r * sp, rm = lo ? rp : rn;
    f[0 + hf] = packbf(ep[0] * rp, ep[1] * rp);
    f[2 + hf] = packbf(ep[2] * rp, ep[3] * rp);
    f[4 + hf] = packbf(m0 * rm, m1 * rm);
    f[6 + hf] = packbf(en[0] * rn, en[1] * rn);
    f[8 + hf] = packbf(en[2] * rn, en[3] * rn);
  }
  return safe;
}
__device__ __forceinline__ void hedgehog2(const float (&p)[2][12], uint32_t (&f)[2][10], int t) {
  const bool s0 = hedgehog<false>(p[0], f[0], t), s1 = hedgehog<false>(p[1], f[1], t);
  if (!__all_sync(~0u, s0 && s1)) { hedgehog<true>(p[0], f[0], t); hedgehog<true>(p[1], f[1], t); }
}

template <int O>
__device__ __forceinline__ void epilogue0(const float (&a1)[2][64], const float (&a2)[24], int rg, int t, uint32_t ad01, uint32_t ad2) {
  const bool p0 = (POLY_MASK >> rg) & 1, p1 = (POLY_MASK >> (rg + 1)) & 1;
  const uint32_t kp = (t & 1) ? 0u : (BF_ONE | (BF_MAGIC << 16)), km = (t & 1) ? BF_MU_LO : (BF_ONE | (BF_MU_HI << 16));
  const uint32_t vp = (t & 1) ? 0u : (BF_ONE | 0x8000u), vm = (t & 1) ? 0u : BF_ONE;
  const uint32_t k0 = p0 ? kp : km, k1 = p1 ? kp : km, v0 = p0 ? vp : vm, v1 = p1 ? vp : vm;
  const float s0 = p0 ? -1.f : 1.f, s1 = p1 ? -1.f : 1.f;
  stage_pair<O + 1, 0>(a1, a2, 1.f, 1.f, 1.f, k0, k1, k0, k1, ad01 + OFF_AQ, ad2 + OFF_AQ, t);
  stage_pair<O + 1, 1>(a1, a2, 1.f, 1.f, 1.f, k0, k1, k0, k1, ad01 + OFF_AQ, ad2 + OFF_AQ, t);
  stage_pair<O + 2, 0>(a1, a2, s0, s1, 1.f, v0, v1, v0, v1, ad01 + OFF_V, ad2 + OFF_V, t);
  stage_pair<O + 2, 1>(a1, a2, s0, s1, 1.f, v0, v1, v0, v1, ad01 + OFF_V, ad2 + OFF_V, t);
  stage_pair<O + 0, 0>(a1, a2, QSCALE, QSCALE, 1.f, 0u, 0u, 0u, 0u, ad01 + OFF_Q, ad2 + OFF_Q, t);
  stage_pair<O + 0, 1>(a1, a2, QSCALE, QSCALE, 1.f, 0u, 0u, 0u, 0u, ad01 + OFF_Q, ad2 + OFF_Q, t);
}
template <int O, int PR>
__device__ __forceinline__ void pack_pair(const float (&a1)[2][64], const float (&a2)[24], uint32_t (&k)[10]) {
#pragma unroll
  for (int hf = 0; hf < 2; hf++) {
    k[0 + hf] = pks(hf ? grp<O + 1, 5 * PR, 1>(a1, a2) : grp<O + 1, 5 * PR, 0>(a1, a2), 1.f);
    k[2 + hf] = pks(hf ? grp<O + 1, 5 * PR + 1, 1>(a1, a2) : grp<O + 1, 5 * PR + 1, 0>(a1, a2), 1.f);
    k[4 + hf] = pks(hf ? grp<O + 1, 5 * PR + 3, 1>(a1, a2) : grp<O + 1, 5 * PR + 3, 0>(a1, a2), 1.f);
    k[6 + hf] = pks(hf ? grp<O + 1, 5 * PR + 4, 1>(a1, a2) : grp<O + 1, 5 * PR + 4, 0>(a1, a2), 1.f);
    k[8 + hf] = pks(hf ? grp<O + 1, 5 * PR + 2, 1>(a1, a2) : grp<O + 1, 5 * PR + 2, 0>(a1, a2), 1.f);
  }
}
template <int O>
__device__ __forceinline__ void epilogue1(const float (&a1)[2][64], const float (&a2)[24], uint32_t (&k)[2][10], int t, uint32_t ad01, uint32_t ad2) {
  stage_pair<O + 0, 0>(a1, a2, 1.f, 1.f, 0.5f, 0u, 0u, 0u, 0u, ad01 + OFF_AQ, ad2 + OFF_AQ, t);
  stage_pair<O + 0, 1>(a1, a2, 1.f, 1.f, 0.5f, 0u, 0u, 0u, 0u, ad01 + OFF_AQ, ad2 + OFF_AQ, t);
  const uint32_t one = (t & 1) ? 0u : BF_ONE;
  stage_pair<O + 2, 0>(a1, a2, 1.f, 1.f, 1.f, one, one, one, one, ad01 + OFF_V, ad2 + OFF_V, t);
  stage_pair<O + 2, 1>(a1, a2, 1.f, 1.f, 1.f, one, one, one, one, ad01 + OFF_V, ad2 + OFF_V, t);
  pack_pair<O, 0>(a1, a2, k[0]);
  pack_pair<O, 1>(a1, a2, k[1]);
}
__device__ __forceinline__ float row_norm2(const uint8_t* a, int odd) {
  float n = 0.f;
#pragma unroll
  for (int c = 0; c < 2; c++) {
    const uint4 v = *(const uint4*)(a + c * 128);
    const uint32_t w[4] = {v.x, v.y, v.z, v.w};
#pragma unroll
    for (int i = 0; i < 4; i++) n = fmaf(bf_lo(w[i]), bf_lo(w[i]), fmaf(bf_hi(w[i]), bf_hi(w[i]), n));
  }
  const uint2 v = *(const uint2*)(a + 256 + odd * 8);
  n = fmaf(bf_lo(v.x), bf_lo(v.x), fmaf(bf_hi(v.x), bf_hi(v.x), n));
  return fmaf(bf_lo(v.y), bf_lo(v.y), fmaf(bf_hi(v.y), bf_hi(v.y), n));
}

__device__ __forceinline__ void issue_proj(float (&p)[2][12], uint32_t img, uint32_t wph) {
  const uint64_t ad = mkdesc(img, 128, 384, 0), ad2 = mkdesc(img + 256, 0, 384, 0), wd = mkdesc(wph, 384, 128, 0), wd2 = mkdesc(wph + 768, 0, 128, 0);
#pragma unroll
  for (int i = 0; i < 2; i++) {
    mma_n24_ss_tb(p[i], ad + i * 192, wd + i * 72, 0);
    mma_n24_ss_tb(p[i], ad2 + i * 192, wd2 + i * 72, 1);
  }
}

__device__ __forceinline__ uint32_t exp2_bits(float y0, float y1, uint32_t cm, uint32_t neg1) {
  uint32_t w, m, r;
  asm("prmt.b32 %0, %1, %2, 0x6521;" : "=r"(w) : "f"(y0), "f"(y1));
  asm("lop3.b32 %0, %1, 0x007F007F, %2, 0xEA;" : "=r"(m) : "r"(w), "r"(cm));
  const uint32_t e = m * neg1 + w;
  asm("fma.rn.bf16x2 %0, %1, %2, %3;" : "=r"(r) : "r"(w), "r"(m), "r"(e));
  return r;
}
template <int HI>
__device__ __forceinline__ void exp_tile(const float (&s)[32], uint32_t (&p)[16], uint32_t cm, uint32_t neg1) {
#pragma unroll
  for (int g = 0; g < 8; g++) {
    if ((POLY_MASK >> (g + 8 * HI)) & 1) {
      p[2 * g] = exp2_bits(s[4 * g], s[4 * g + 1], cm, neg1);
      p[2 * g + 1] = exp2_bits(s[4 * g + 2], s[4 * g + 3], cm, neg1);
    } else {
      p[2 * g] = packbf(ex2(s[4 * g]), ex2(s[4 * g + 1]));
      p[2 * g + 1] = packbf(ex2(s[4 * g + 2]), ex2(s[4 * g + 3]));
    }
  }
}
struct AttnDesc { uint64_t k, k2, v; };
__device__ __forceinline__ void issue_qk(float (&s)[32], const uint32_t (&q)[8], const AttnDesc& d, uint32_t ko) {
  mma_n64_rs(s, q[0], q[1], q[2], q[3], d.k + ko, 0);
  mma_n64_rs(s, q[4], q[5], q[6], q[7], d.k2 + ko, 1);
}
__device__ __forceinline__ void issue_pv(float (&o)[12], const uint32_t (&p)[16], uint64_t vd, int acc) {
#pragma unroll
  for (int kk = 0; kk < 4; kk++) mma_n24_rs_tb(o, p[4 * kk], p[4 * kk + 1], p[4 * kk + 2], p[4 * kk + 3], vd + kk * 48, acc | kk);
}
__device__ __forceinline__ void load_q(uint32_t (&q)[8], uint32_t a) {
#pragma unroll
  for (int i = 0; i < 6; i++) asm volatile("ld.shared.b32 %0, [%1];" : "=r"(q[i]) : "r"(a + (i >> 1) * 128 + (i & 1) * 384) : "memory");
}
template <int SL>
__device__ __forceinline__ void attn_chunk(float (&s)[32], uint32_t (&p0)[16], uint32_t (&p1)[16], float (&o)[12], const uint32_t (&q)[8],
                                           const AttnDesc& d, int acc, uint32_t full_next, uint32_t ph_next,
                                           uint32_t bars, uint32_t release, uint32_t cm, uint32_t neg1) {
  exp_tile<0>(s, p0, cm, neg1);
  wg_fence();
  issue_qk(s, q, d, SL * 1536 + 192);
  wg_commit();
  issue_pv(o, p0, d.v + SL * 1536, acc);
  wg_commit();
  wg_wait<1>();
  pin(s); pin(p1);
  mbar_arrive_if(bars + B_KE + 8 * ((SL + 3) & 3), release);
  const uint32_t ready = mbar_test(full_next, ph_next);
  exp_tile<1>(s, p1, cm, neg1);
  pin(p1);
  if (!__all_sync(~0u, ready)) mbar_wait_u(full_next, ph_next);
  wg_fence();
  issue_qk(s, q, d, ((SL + 1) & 3) * 1536);
  wg_commit();
  issue_pv(o, p1, d.v + SL * 1536 + 192, 1);
  wg_commit();
  wg_wait<1>();
  pin(s); pin(p0);
}
__device__ __forceinline__ int bgroup(int G) {
  const int hg = G / 10, j = G % 10;
  return (hg >> 2) * 40 + (j / 5) * 20 + (hg & 3) * 5 + j % 5;
}
__device__ __forceinline__ void stage_o(const float (&o)[12], int odd, uint32_t pair, int w4, int lane, float eps, float s0, float s1) {
  const int src = (lane & ~3) | (odd ? 0 : 2);
  const float l0 = __shfl_sync(~0u, o[8], src) + eps, l1 = __shfl_sync(~0u, o[10], src) + eps;
  const float r0 = s0 * rcp(l0), r1 = s1 * rcp(l1);
  const uint32_t base = pair + w4 * 256;
  stsm4(base + (odd ? 3072 : 0) + (lane >> 4) * 1024 + (lane & 15) * 16, packbf(o[0] * r0, o[1] * r0), packbf(o[2] * r1, o[3] * r1),
        packbf(o[4] * r0, o[5] * r0), packbf(o[6] * r1, o[7] * r1));
  if (((lane & 3) < 2) != (odd != 0)) {
    sts32(base + 2048 + lane * 4, packbf(o[8] * r0, o[9] * r0));
    sts32(base + 2048 + 128 + lane * 4, packbf(o[10] * r1, o[11] * r1));
  }
}
struct Maps { CUtensorMap a64, a16, b64, b16, out; };

template <bool MC>
__device__ __forceinline__ void w_load(const Maps& m, int it, uint32_t d, uint32_t b, int hg, int rank) {
  const int kb = (it % 10) * 2 + rank, c = hg * 80 + (hg & 1) * 16, c2 = hg * 80 + ((hg & 1) ? 0 : 64);
  const CUtensorMap *m64 = it < 10 ? &m.b64 : &m.a64, *m16 = it < 10 ? &m.b16 : &m.a16;
  const uint32_t d1 = d + rank * 4096, d2 = d + 24576 + rank * 1024;
#pragma unroll
  for (int sec = 0; sec < 3; sec++) tma5<MC>(d1 + sec * 8192, m64, sec * 640 + c, kb, b);
#pragma unroll
  for (int sec = 0; sec < 3; sec++) tma5<MC>(d2 + sec * 2048, m16, sec * 640 + c2, kb, b);
}
__device__ __forceinline__ void x_load(uint4 (&v)[4], const uint8_t* p, int it) {
  const uint8_t* q = p + (it % 10) * 128;
  v[0] = ldg_x(q); v[1] = ldg_x(q + 8 * 1280); v[2] = ldg_x(q + 64); v[3] = ldg_x(q + 8 * 1280 + 64);
}
__device__ __forceinline__ void gemm_step(float (&a1)[2][64], float (&a2)[24], uint4 (&xv)[4], uint32_t (&f)[4][4], uint32_t (&fp)[4][4],
                                          const uint8_t* xp, int it, int acc, uint32_t sb, uint32_t bars, uint32_t lead) {
  const int s = it % W_NST;
  const uint32_t z = mbar_test(bars + B_Z, 1) - 1;
  f[0][0] = xv[0].x ^ z; f[0][1] = xv[1].x ^ z; f[0][2] = xv[0].y ^ z; f[0][3] = xv[1].y ^ z;
  f[1][0] = xv[0].z ^ z; f[1][1] = xv[1].z ^ z; f[1][2] = xv[0].w ^ z; f[1][3] = xv[1].w ^ z;
  f[2][0] = xv[2].x ^ z; f[2][1] = xv[3].x ^ z; f[2][2] = xv[2].y ^ z; f[2][3] = xv[3].y ^ z;
  f[3][0] = xv[2].z ^ z; f[3][1] = xv[3].z ^ z; f[3][2] = xv[2].w ^ z; f[3][3] = xv[3].w ^ z;
#pragma unroll
  for (int i = 0; i < 4; i++) pin(f[i]);
  x_load(xv, xp, it + 2);
  mbar_wait_u(bars + B_WF + 8 * s, (it / W_NST) & 1);
  const uint64_t b1 = mkdesc(sb + s * W_STAGE, 8192, 1024, 1), b2 = mkdesc(sb + s * W_STAGE + 24576, 2048, 256, 3);
  wg_fence();
#pragma unroll
  for (int kk = 0; kk < 4; kk++) {
    mma_n128_rs_tb(a1[0], f[kk][0], f[kk][1], f[kk][2], f[kk][3], b1 + kk * 128, acc | kk);
    mma_n64_rs_tb(*(float(*)[32])a1[1], f[kk][0], f[kk][1], f[kk][2], f[kk][3], b1 + 1024 + kk * 128, acc | kk);
    mma_n48_rs_tb(a2, f[kk][0], f[kk][1], f[kk][2], f[kk][3], b2 + kk * 32, acc | kk);
  }
  wg_commit();
  wg_wait<1>();
#pragma unroll
  for (int i = 0; i < 4; i++) pin(fp[i]);
  mbar_arrive_pair(bars + B_WE + 8 * ((it + W_NST - 1) % W_NST), lead && acc);
}

__device__ __forceinline__ void kv_stream(uint32_t sb, int hg, int u, uint32_t epoch) {
  const uint32_t bars = sb + OFF_BAR + u * 64;
  cnt_wait(C_KV + hg, 16 * epoch);
  for (int c = 0; c < 32; c++) {
    const int s = c & 3;
    const uint8_t* src = g_KV + (size_t)(hg * 4 + (c >> 4) * 2 + u) * IMG_HEAD + (c & 15) * 6144;
    mbar_wait(bars + B_KE + 8 * s, (c >> 2) & 1);
    mbar_expect(bars + B_KF + 8 * s, 12288);
    bulk_g2s(sb + s * KV_SLOT + u * KV_CHUNK, src, 6144, bars + B_KF + 8 * s);
    bulk_g2s(sb + s * KV_SLOT + u * KV_CHUNK + 6144, src + (size_t)NH * IMG_HEAD, 6144, bars + B_KF + 8 * s);
  }
}

__device__ __forceinline__ void out_step(float (&acc)[80], uint32_t (&f)[4][4], uint32_t (&fp)[4][4], int it, int accum, uint32_t sb, uint32_t arow,
                                         uint32_t bars, uint32_t lead) {
  const int s = it % 5;
  mbar_wait_u(bars + B_OF + 8 * s, it / 5);
  const uint32_t st = sb + o_stage(s);
#pragma unroll
  for (int kk = 0; kk < 4; kk++)
    asm volatile("ldmatrix.sync.aligned.m8n8.x4.shared.b16 {%0,%1,%2,%3}, [%4];"
                 : "=r"(f[kk][0]), "=r"(f[kk][1]), "=r"(f[kk][2]), "=r"(f[kk][3]) : "r"(sb + o_stage_a(s) + arow + kk * 2048) : "memory");
  const uint64_t bd = mkdesc(st + 16384, 2560, 128, 0);
  wg_fence();
#pragma unroll
  for (int kk = 0; kk < 4; kk++) {
    mma_n80_rs_tb(*(float(*)[40])acc, f[kk][0], f[kk][1], f[kk][2], f[kk][3], bd + kk * 320, accum | kk);
    mma_n80_rs_tb(*(float(*)[40])(acc + 40), f[kk][0], f[kk][1], f[kk][2], f[kk][3], bd + kk * 320 + 80, accum | kk);
  }
  wg_commit();
  wg_wait<1>();
#pragma unroll
  for (int i = 0; i < 4; i++) pin(fp[i]);
  mbar_arrive_if(bars + B_OE + 8 * ((it + 4) % 5), lead && accum);
}

__device__ __forceinline__ void middle(uint8_t* smem, const uint32_t (&k)[2][10], int wg, int w4, int lane, uint32_t cm, uint32_t neg1) {
  const uint32_t sb = smem_u32(smem), bars = sb + OFF_BAR, lead = (threadIdx.x & 127) == 0;
  const int t = lane & 3, mi = lane >> 3, r = wg & 1, u = wg >> 1;
  const bool slow = __any_sync(~0u, *(volatile uint32_t*)(smem + OFF_MISC + 20 + r * 4));
  if (u == 0) {
    const uint32_t pka = sb + OFF_PHK + (r * 8 + w4 * 2 + (mi & 1)) * 640 + (mi >> 1) * 128 + (lane & 7) * 16;
    const uint64_t wd = mkdesc(sb + OFF_WPH, 384, 128, 0), wd2 = mkdesc(sb + OFF_WPH + 768, 0, 128, 0);
    float pp[2][12], pn[2][12];
    uint32_t c2[4][2];
#pragma unroll
    for (int i = 0; i < 8; i++) c2[i >> 1][i & 1] = ((t < 2) == !(i & 2)) ? k[i >> 2][8 + (i & 1)] : 0u;
#pragma unroll
    for (int i = 0; i < 4; i++) pin(c2[i]);
    wg_fence();
#pragma unroll
    for (int i = 0; i < 4; i++) {
      float (&p)[12] = i < 2 ? pp[i & 1] : pn[i & 1];
      const uint32_t* kk = &k[i >> 1][(i & 1) * 4];
      mma_n24_rs_tb(p, kk[0], kk[1], kk[2], kk[3], wd + i * 72, 0);
      mma_n24_rs_tb(p, c2[i][0], c2[i][1], 0u, 0u, wd2 + i * 72, 1);
    }
    wg_commit();
    wg_wait<0>();
    pin(pp[0]); pin(pp[1]); pin(pn[0]); pin(pn[1]);
#pragma unroll 1
    for (int i = 0; i < 4; i += 2) {
      uint32_t f[2][10];
      hedgehog2(pp, f, t);
#pragma unroll
      for (int j = 0; j < 2; j++) {
        stsm4(pka + (i + j) * 10240, f[j][0], f[j][1], f[j][2], f[j][3]);
        stsm4(pka + (i + j) * 10240 + 256, f[j][4], f[j][5], f[j][6], f[j][7]);
        stsm2(pka + (i + j) * 10240 + 512, f[j][8], f[j][9]);
      }
#pragma unroll
      for (int k = 0; k < 24; k++) pp[k / 12][k % 12] = pn[k / 12][k % 12];
    }
    float (&pa)[12] = pp[0], (&pb)[12] = pp[1];
    fence_async_smem();
    bar_sync(NB_PHIK, 256);
    wg_fence();
#pragma unroll
    for (int j = 0; j < 2; j++) {
      const uint64_t ad = mkdesc(sb + OFF_PHK + (r * 2 + j) * 10240, 640, 128, 0), vd = mkdesc(sb + OFF_V + (r * 2 + j) * 3072, 384, 128, 0);
#pragma unroll
      for (int ks = 0; ks < 8; ks++) mma_n24_ss_tatb(j ? pb : pa, ad + ks * 80, vd + (ks >> 2) * 768 + (ks & 3) * 48, ks);
    }
    wg_commit();
    wg_wait<0>();
    pin(pa); pin(pb);
    bar_sync(NB_WG + wg, 128);
    float2* dst = (float2*)(smem + OFF_PHK + r * 20480) + w4 * 192 + lane;
    if (w4 < 3) {
      dst[0] = make_float2(pa[0], pa[1]); dst[32] = make_float2(pa[4], pa[5]); dst[64] = make_float2(pa[8], pa[9]);
      dst[1280] = make_float2(pb[0], pb[1]); dst[1312] = make_float2(pb[4], pb[5]); dst[1344] = make_float2(pb[8], pb[9]);
    }
    if (w4 < 2) {
      dst[96] = make_float2(pa[2], pa[3]); dst[128] = make_float2(pa[6], pa[7]); dst[160] = make_float2(pa[10], pa[11]);
      dst[1376] = make_float2(pb[2], pb[3]); dst[1408] = make_float2(pb[6], pb[7]); dst[1440] = make_float2(pb[10], pb[11]);
    }
    fence_async_smem();
    bar_arrive(NB_TAIL, 288);
  }
  {
    const uint32_t gate = sb + OFF_GATE + (r * 64 + w4 * 16 + (lane >> 2)) * 8, qs = sb + OFF_Q + r * 12288;
    const uint32_t kb = bars + u * 64;
    AttnDesc d0;
    d0.k = mkdesc(sb + u * KV_CHUNK, 128, 384, 0); d0.k2 = mkdesc(sb + u * KV_CHUNK + 256, 0, 384, 0);
    d0.v = mkdesc(sb + u * KV_CHUNK + 6144, 384, 128, 0);
    const uint32_t qa = qs + u * 3072 + w4 * 768 + lane * 4;
#pragma unroll 1
    for (int pass = 0; pass < 2; pass++) {
      float o[12], s0[32];
      uint32_t q[8];
      load_q(q, qa + pass * 6144);
      q[6] = q[7] = neg1 + 1;
      if (!slow) {
        uint32_t p0[16], p1[16] = {};
        mbar_wait_u(kb + B_KF, 0);
        wg_fence();
        issue_qk(s0, q, d0, 0);
        wg_commit();
        wg_wait<0>();
        pin(s0);
#pragma unroll 1
        for (int turn = 0; turn < 4; turn++) {
          const int ph = turn & 1;
          AttnDesc d;
          asm volatile("mov.b64 %0, %3;\nmov.b64 %1, %4;\nmov.b64 %2, %5;" : "=l"(d.k), "=l"(d.k2), "=l"(d.v) : "l"(d0.k), "l"(d0.k2), "l"(d0.v));
          attn_chunk<0>(s0, p0, p1, o, q, d, turn, kb + B_KF + 8, ph, kb, lead && turn, cm, neg1);
          attn_chunk<1>(s0, p0, p1, o, q, d, 1, kb + B_KF + 16, ph, kb, lead, cm, neg1);
          attn_chunk<2>(s0, p0, p1, o, q, d, 1, kb + B_KF + 24, ph, kb, lead, cm, neg1);
          attn_chunk<3>(s0, p0, p1, o, q, d, 1, kb + B_KF + (turn == 3 ? 24 : 0), turn == 3 ? 1 : ph ^ 1, kb, lead, cm, neg1);
        }
        wg_wait<0>();
        pin(o); pin(p1); pin(q);
        mbar_arrive_if(kb + B_KE + 24, lead);
      } else {
        uint32_t p[16];
        float m0 = -INFINITY, m1 = -INFINITY;
#pragma unroll
        for (int i = 0; i < 12; i++) o[i] = 0.f;
#pragma unroll 1
        for (int j = 0; j < 32; j++) {
          const int slot = (j >> 1) & 3;
          const uint32_t co = slot * 1536 + (j & 1) * 192, neg = (POLY_MASK >> ((j & 1) * 8)) & 0xFF;
          mbar_wait_u(kb + B_KF + 8 * slot, (j >> 3) & 1);
          wg_fence();
          issue_qk(s0, q, d0, co);
          wg_commit();
          wg_wait<0>();
          pin(s0);
          float n0 = m0, n1 = m1;
#pragma unroll
          for (int g = 0; g < 8; g++) { n0 = fmaxf(n0, fmaxf(s0[4 * g], s0[4 * g + 1])); n1 = fmaxf(n1, fmaxf(s0[4 * g + 2], s0[4 * g + 3])); }
          n0 = fmaxf(n0, __shfl_xor_sync(~0u, n0, 1)); n1 = fmaxf(n1, __shfl_xor_sync(~0u, n1, 1));
          n0 = fmaxf(n0, __shfl_xor_sync(~0u, n0, 2)); n1 = fmaxf(n1, __shfl_xor_sync(~0u, n1, 2));
          const float c0 = ex2(m0 - n0), c1 = ex2(m1 - n1);
          m0 = n0; m1 = n1;
#pragma unroll
          for (int i = 0; i < 3; i++) { o[4 * i] *= c0; o[4 * i + 1] *= c0; o[4 * i + 2] *= c1; o[4 * i + 3] *= c1; }
#pragma unroll
          for (int g = 0; g < 8; g++) {
            const uint32_t sg = ((neg >> g) & 1) ? 0x80008000u : 0u;
            p[2 * g] = packbf(ex2(s0[4 * g] - m0), ex2(s0[4 * g + 1] - m0)) ^ sg;
            p[2 * g + 1] = packbf(ex2(s0[4 * g + 2] - m1), ex2(s0[4 * g + 3] - m1)) ^ sg;
          }
          wg_fence();
          issue_pv(o, p, d0.v + co, 1);
          wg_commit();
          wg_wait<0>();
          pin(o); pin(p);
          mbar_arrive_if(kb + B_KE + 8 * slot, lead && (j & 1));
        }
      }
      mbar_wait_u(bars + B_G, 0);
      stage_o(o, u, qs + pass * 6144, w4, lane, 0.f, lds_f2(gate).y, lds_f2(gate + 64).y);
      if (pass == 0) {
        if (u == 1) {
          const uint32_t aq = sb + OFF_AQ + r * 12288;
          const float g0 = lds_f2(gate).x, g1 = lds_f2(gate + 64).x;
#pragma unroll 1
          for (int j = 0; j < 2; j++) {
            float pp[2][12];
            wg_fence();
            issue_proj(pp, aq + j * 6144, sb + OFF_WPH + j * 2304);
            wg_commit();
            wg_wait<0>();
            pin(pp[0]); pin(pp[1]);
            uint32_t f[2][10];
            hedgehog2(pp, f, t);
            pin(f[0]); pin(f[1]);
            const uint64_t kvd = mkdesc(sb + OFF_V + j * 3840, 384, 128, 0), kvd2 = mkdesc(sb + OFF_V + j * 3840 + 1536, 0, 128, 0);
            wg_fence();
#pragma unroll
            for (int i = 0; i < 2; i++) {
              mma_n24_rs_tb(pp[i], f[i][0], f[i][1], f[i][2], f[i][3], kvd + i * 120, 0);
              mma_n24_rs_tb(pp[i], f[i][4], f[i][5], f[i][6], f[i][7], kvd + i * 120 + 48, 1);
              mma_n24_rs_tb(pp[i], f[i][8], f[i][9], 0u, 0u, kvd2 + i * 120, 1);
            }
            wg_commit();
            wg_wait<0>();
            pin(pp[0]); pin(pp[1]); pin(f[0]); pin(f[1]);
            stage_o(pp[0], 0, aq + j * 5120, w4, lane, 1e-6f, g0, g1);
            stage_o(pp[1], 1, aq + j * 5120, w4, lane, 1e-6f, g0, g1);
          }
        }
        fence_async_smem();
        bar_arrive(NB_READ, 544);
      }
    }
    fence_async_smem();
    bar_arrive(NB_LAST, 544);
  }
}

__global__ void __cluster_dims__(2, 1, 1) __launch_bounds__(640, 1)
fused_block(const __grid_constant__ Maps maps, const __nv_bfloat16* __restrict__ x, const __nv_bfloat16* __restrict__ wphi,
            const __nv_bfloat16* __restrict__ gate_w, const uint8_t* __restrict__ woa, const uint8_t* __restrict__ wob, uint32_t cm, uint32_t neg1) {
  extern __shared__ __align__(1024) uint8_t smem[];
  const uint32_t sb = smem_u32(smem), bars = sb + OFF_BAR;
  const int warp = __shfl_sync(~0u, threadIdx.x >> 5, 0), lane = threadIdx.x & 31, wg = warp >> 2;
  const int bid = blockIdx.x;
  const int mt = (bid & 1) + 2 * (bid >> 4), hg = (bid >> 1) & 7;
  const int half = bid & 1, nt = (bid >> 1) & 3, mt3 = bid >> 3;
  if (warp == 16) {
    if (lane == 0) {
#pragma unroll
      for (int i = 0; i < W_NST; i++) { mbar_init(bars + B_WF + 8 * i, 1); mbar_init(bars + B_WE + 8 * i, 4); }
      mbar_init(bars + B_Z, 1);
      mbar_init(bars + B_X, 1);
      mbar_init(bars + B_F, 1);
      *(uint4*)(smem + OFF_MISC) = make_uint4(0u, 0u, 0u, 0u);
      *(uint4*)(smem + OFF_MISC + 16) = make_uint4(0u, 0u, 0u, 0u);
      asm volatile("fence.mbarrier_init.release.cluster;" ::: "memory");
      mbar_expect(bars + B_WF, W_STAGE);
    }
    __syncwarp();
  }
  asm volatile("barrier.cluster.arrive.relaxed.aligned;" ::: "memory");
  if ((warp | 1) == 17) {
    bar_sync(0, 64);
    if (lane == 0) w_load<false>(maps, 0, sb, bars + B_WF, hg, warp & 1);
    __syncwarp();
  }

  if (wg == 4) {
    reg_dec<32>();
    asm volatile("barrier.cluster.wait.aligned;" ::: "memory");
    if (warp == 16) {
      if (lane == 0) {
        for (int it = 1; it < 20; it++) {
          const int s = it % W_NST;
          if (it >= W_NST) mbar_wait(bars + B_WE + 8 * s, ((it / W_NST) - 1) & 1);
          mbar_expect(bars + B_WF + 8 * s, W_STAGE);
          w_load<true>(maps, it, sb + s * W_STAGE, bars + B_WF + 8 * s, hg, half);
        }
      }
      __syncwarp();
      bar_sync(NB_HELP, 128);
      const uint32_t epoch = *(volatile uint32_t*)(smem + OFF_MISC + 16);
      if (lane == 0) {
        kv_stream(sb, hg, 0, epoch);
        cnt_wait(C_WO, NCTA * epoch);
        cnt_wait(C_OA + mt3, 8 * epoch);
        mbar_wait(bars + B_RF, 0);
        const uint8_t* ga = g_OAB + (size_t)mt3 * 327680 + half * 5 * 8192;
        for (int it = 0; it < 10; it++) {
          const int s = it % 5, ks = it < 5 ? it : it + 5;
          if (it >= 2 && it < 5) {
            mbar_wait(bars + B_P1, 0);
            mbar_wait(bars + B_KE + 8 * (it - 1), 0);
            mbar_wait(bars + B_KE + 64 + 8 * (it - 1), 0);
          }
          if (it >= 5) mbar_wait(bars + B_OE + 8 * s, 0);
          const uint32_t d = sb + o_stage(s), da = sb + o_stage_a(s), b = bars + B_OF + 8 * s;
          if (it == 1) {
            mbar_expect(bars + B_OF + 32, O_STAGE);
            bulk_g2s(sb + o_stage_a(4), ga + 4 * 8192, 8192, bars + B_OF + 32);
            bulk_g2s(sb + o_stage_a(4) + 8192, ga + 4 * 8192 + 163840, 8192, bars + B_OF + 32);
          }
          if (it != 4) mbar_expect(b, O_STAGE);
          bulk_g2s(d + 16384, g_WOI + (size_t)nt * 409600 + (ks + half * 5) * 20480, 20480, b);
          if (it == 7) { cnt_wait(C_OB + mt3, 8 * epoch); }
          if (it == 4) continue;
          bulk_g2s(da, ga + ks * 8192, 8192, b);
          bulk_g2s(da + 8192, ga + ks * 8192 + 163840, 8192, b);
        }
      }
    } else if (warp == 17) {
      uint32_t epoch = 0;
      if (lane == 0) {
#pragma unroll
        for (int i = 0; i < 8; i++) { mbar_init(bars + B_KF + (i >> 2) * 64 + 8 * (i & 3), 1); mbar_init(bars + B_KE + (i >> 2) * 64 + 8 * (i & 3), 2); }
#pragma unroll
        for (int i = 0; i < 5; i++) { mbar_init(bars + B_OF + 8 * i, 1); mbar_init(bars + B_OE + 8 * i, 2); }
        mbar_init(bars + B_RF, 1);
        mbar_init(bars + B_G, 1);
        mbar_init(bars + B_P1, 1);
        mbar_init(bars + B_R, 1);
        fence_async_smem();
        epoch = atomicAdd(g_CNT + C_START * 8, 1u) / NCTA + 1;
        *(volatile uint32_t*)(smem + OFF_MISC + 16) = epoch;
      }
      epoch = __shfl_sync(~0u, epoch, 0);
      if (lane < 30) { uint4* z = (uint4*)(g_KVA + hg * 1920 + mt * 120) + lane * 2; z[0] = z[1] = make_uint4(0u, 0u, 0u, 0u); }
      __syncwarp();
      asm volatile("fence.acq_rel.gpu;" ::: "memory");
      bar_arrive(NB_HELP, 128);
#pragma unroll 1
      for (int e = lane; e < 96; e += 32) {
        const int i = e / 24, slot = e % 24;
        int d = -1;
        if (i & 1) { if (slot < 16) d = slot + 4; else if (slot >= 20) d = slot - 20; }
        else if (slot < 20) d = slot;
        uint2 v[5] = {};
        if (d >= 0) {
#pragma unroll
          for (int u = 0; u < 5; u++) v[u] = __ldg((const uint2*)(wphi + ((hg * 4 + i) * 20 + d) * 20) + u);
        }
        uint8_t* dst = smem + OFF_WPH + i * 1152 + (slot >> 3) * 384 + (slot & 7) * 16;
        *(uint4*)dst = make_uint4(v[0].x, v[0].y, v[1].x, v[1].y);
        *(uint4*)(dst + 128) = make_uint4(v[2].x, v[2].y, v[3].x, v[3].y);
        *(uint4*)(dst + 256) = make_uint4(v[4].x, v[4].y, v[4].x, v[4].y);
      }
      fence_async_smem();
      bar_sync(NB_STAGED, 544);
      if (lane == 0) {
#pragma unroll 1
        for (int i = 0; i < 16; i++) {
          bulk_s2g(g_KV + (size_t)((i >> 3) * NH + hg * 4 + (i & 3)) * IMG_HEAD + (mt * 2 + ((i >> 2) & 1)) * 3072,
                   sb + (i < 8 ? OFF_AQ : OFF_V) + (i & 7) * 3072, 3072);
          __nanosleep(100);
        }
      }
      __syncwarp();
      bar_sync(NB_NORM, 288);
      if (lane == 0) {
        bulk_s2g(g_KMAX + hg * 16 + mt, sb + OFF_MISC, 16);
        bulk_commit_wait();
        cnt_add_done(C_KV + hg);
      }
      if (lane == 0) { mbar_arrive(bars + B_F); cnt_wait(C_KV + hg, 16 * epoch); }
      __syncwarp();
      {
        uint4 v = ldg_cg4(g_KMAX + hg * 16 + (lane & 15));
        v.x = __reduce_max_sync(~0u, v.x); v.y = __reduce_max_sync(~0u, v.y); v.z = __reduce_max_sync(~0u, v.z); v.w = __reduce_max_sync(~0u, v.w);
        if (lane < 4) *(volatile float*)(smem + OFF_MISC + lane * 4) =
            sqrt_ap(__uint_as_float(lane == 0 ? v.x : lane == 1 ? v.y : lane == 2 ? v.z : v.w)) * 1.01f;
      }
      bar_arrive(NB_BOUND, 288);
      bar_sync(NB_TAIL, 288);
      if (lane == 0) {
#pragma unroll 1
        for (int i = 0; i < 4; i++)
          asm volatile("cp.reduce.async.bulk.global.shared::cta.bulk_group.add.f32 [%0], [%1], %2;" ::"l"(g_KVA + (hg * 4 + i) * 480),
                       "r"(sb + OFF_PHK + i * 10240), "r"(3840) : "memory");
        bulk_commit_wait();
        cnt_add_done(C_KVP + hg);
        cnt_wait(C_GATE + mt, 8 * epoch);
      }
      __syncwarp();
      {
        const uint4 g0 = ldg_cg4(g_GATE + mt * 128 + lane * 2), g1 = ldg_cg4(g_GATE + mt * 128 + 64 + lane * 2);
        *(uint4*)(smem + OFF_GATE + lane * 16) = g0;
        *(uint4*)(smem + OFF_GATE + 512 + lane * 16) = g1;
      }
      if (lane == 0) {
        cnt_wait(C_KVP + hg, 16 * epoch);
        mbar_expect(bars + B_R, 15360);
        bulk_g2s(sb + OFF_KVS, g_KVA + hg * 1920, 15360, bars + B_R);
      }
      mbar_wait(bars + B_R, 0);
#pragma unroll 4
      for (int e = lane; e < 960; e += 32) {
        const float4 v = *(const float4*)(smem + OFF_KVS + e * 16);
        *(uint2*)(smem + OFF_V + e * 8) = make_uint2(packbf(v.x, v.y), packbf(v.z, v.w));
      }
      fence_async_smem();
      __syncwarp();
      if (lane == 0) mbar_arrive(bars + B_G);
      uint8_t* og = g_OAB + (size_t)mt * 327680;
      bar_sync(NB_READ, 544);
      if (lane == 0) {
#pragma unroll 1
        for (int w = 0; w < 2; w++) {
          bulk_s2g(og + w * 163840 + hg * 10240, sb + OFF_AQ + w * 12288, 10240);
          bulk_s2g(og + w * 163840 + (80 + bgroup(hg * 10)) * 1024, sb + OFF_Q + w * 12288, 5120);
        }
        bulk_commit_wait();
        mbar_arrive(bars + B_RF);
        cnt_add_done(C_OA + mt);
      }
      __syncwarp();
      bar_sync(NB_LAST, 544);
      if (lane == 0) {
        bulk_s2g(og + (80 + bgroup(hg * 10 + 5)) * 1024, sb + OFF_Q + 6144, 5120);
        bulk_s2g(og + 163840 + (80 + bgroup(hg * 10 + 5)) * 1024, sb + OFF_Q + 12288 + 6144, 5120);
        bulk_commit_wait();
        cnt_add_done(C_OB + mt);
      }
    } else if (warp == 18) {
      bar_sync(NB_HELP, 128);
      if (lane == 0) { kv_stream(sb, hg, 1, *(volatile uint32_t*)(smem + OFF_MISC + 16)); mbar_arrive(bars + B_P1); }
    } else {
      bar_sync(NB_HELP, 128);
#pragma unroll 1
      for (int kg = bid; kg < 160; kg += NCTA) {
        const uint8_t* src = (kg < 80 ? woa + (size_t)kg * 10240 : wob + (size_t)(kg - 80) * 10240) + (lane & 7) * 1280 + (lane >> 3) * 16;
        uint8_t* dst = g_WOI + (kg < 80 ? kg : 80 + bgroup(kg - 80)) * 2560 + (lane & 7) * 16 + (lane >> 3) * 128;
#pragma unroll 1
        for (int n4 = 0; n4 < 4; n4++) {
          uint4 v[5];
#pragma unroll
          for (int u = 0; u < 5; u++) v[u] = __ldg((const uint4*)(src + (n4 * 20 + u * 4) * 16));
#pragma unroll
          for (int u = 0; u < 5; u++) *(uint4*)(dst + (size_t)n4 * 409600 + u * 512) = v[u];
        }
      }
      __syncwarp();
      if (lane == 0) cnt_add(C_WO);
    }
  } else {
    const int w4 = warp & 3;
    const uint32_t lead = (threadIdx.x & 127) == 0;
    uint32_t k[2][10] = {};
    if (wg >= 2) {
      const int ht = threadIdx.x - 256;
      reg_dec<24>();
      asm volatile("barrier.cluster.wait.aligned;" ::: "memory");
      __nanosleep(2500);
      {
        const int row = mt * 128 + hg * 16 + (ht >> 4);
        const uint4* xr = (const uint4*)(x + (size_t)row * DM) + (ht & 15);
        const uint4* gr = (const uint4*)gate_w + (ht & 15);
        float acc = 0.f;
#pragma unroll 1
        for (int i = 0; i < 5; i++) {
          const uint4 a = __ldg(xr + i * 16), g = __ldg(gr + i * 16);
          const uint32_t av[4] = {a.x, a.y, a.z, a.w}, gv[4] = {g.x, g.y, g.z, g.w};
#pragma unroll
          for (int j = 0; j < 4; j++) {
            uint32_t p;
            asm("mul.rn.bf16x2 %0, %1, %2;" : "=r"(p) : "r"(av[j]), "r"(gv[j]));
            acc += bf_lo(p) + bf_hi(p);
          }
        }
#pragma unroll
        for (int o = 8; o; o >>= 1) acc += __shfl_xor_sync(~0u, acc, o);
        if ((ht & 15) == 0) {
          const float g = bf_round(__fdividef(1.f, 1.f + __expf(-bf_round(acc))));
          g_GATE[row] = make_float2(g, bf_round(1.f - g));
        }
      }
      bar_sync(NB_BG, 256);
      if (ht == 0) { cnt_add(C_GATE + mt); }
      {
        const int row = ht & 127, hp = ht >> 7;
        const uint32_t off = (row >> 6) * 12288 + hp * 6144 + ((row >> 3) & 7) * 384 + (row & 7) * 16;
        bar_sync(NB_STAGED, 544);
#pragma unroll
        for (int i = 0; i < 2; i++) {
          const uint32_t m = __reduce_max_sync(~0u, __float_as_uint(row_norm2(smem + OFF_AQ + off + i * 3072, i)));
          if (lane == 0) asm volatile("red.shared.max.u32 [%0], %1;" ::"r"(sb + OFF_MISC + (hp * 2 + i) * 4), "r"(m) : "memory");
        }
        fence_async_smem();
        bar_arrive(NB_NORM, 288);
        const float q0 = sqrt_ap(row_norm2(smem + OFF_Q + off, 0)), q1 = sqrt_ap(row_norm2(smem + OFF_Q + off + 3072, 1));
        bar_sync(NB_BOUND, 288);
        const float2 km = *(const float2*)(smem + OFF_MISC + hp * 8);
        const float b0 = q0 * km.x, b1 = q1 * km.y;
        if (__any_sync(~0u, !(b0 <= FAST_BOUND && b1 <= FAST_BOUND)) && lane == 0) *(volatile uint32_t*)(smem + OFF_MISC + 20 + (row >> 6) * 4) = 1;
        bar_sync(NB_BG, 256);
        if (!*(volatile uint32_t*)(smem + OFF_MISC + 20 + (row >> 6) * 4)) {
          *(uint2*)(smem + OFF_Q + off + 256 + 8) = make_uint2(packbf(-b0, 1.f), BF_ONE);
          *(uint2*)(smem + OFF_Q + off + 3072 + 256) = make_uint2(packbf(-b1, 1.f), BF_ONE);
        }
      }
      bar_sync(NB_EPI, 512);
      reg_inc<112>();
    } else {
    const uint8_t* xp = (const uint8_t*)x + (size_t)(mt * 128 + warp * 16 + (lane >> 2)) * 1280 + (lane & 3) * 16;
    uint4 xa[4], xb[4];
    x_load(xa, xp, 0);
    x_load(xb, xp, 1);
    reg_inc<200>();
    asm volatile("barrier.cluster.wait.aligned;" ::: "memory");
    const int t = lane & 3, mi = lane >> 3;
    {
      const uint32_t sbase = sb + wg * 12288 + (w4 * 2 + (mi & 1)) * 384 + (lane & 7) * 16;
      const uint32_t ad01 = sbase + (mi >> 1) * 128, ad2 = sbase + (mi >> 1) * 3072 + 256;
      float a1[2][64], a2[24];
      uint32_t fa[4][4] = {}, fb[4][4] = {};
#pragma unroll 1
      for (int tile = 0; tile < 2; tile++) {
#pragma unroll 1
        for (int ks = 0; ks < 10; ks += 2) {
          gemm_step(a1, a2, xa, fa, fb, xp, tile * 10 + ks, ks, sb, bars, lead);
          gemm_step(a1, a2, xb, fb, fa, xp, tile * 10 + ks + 1, 1, sb, bars, lead);
        }
        wg_wait<0>();
        pin(a1[0]); pin(*(float(*)[32])a1[1]); pin(a2);
#pragma unroll
        for (int i = 0; i < 4; i++) pin(fb[i]);
        mbar_arrive_pair(bars + B_WE + 8 * 4, lead && tile == 0);
        if (tile == 0) {
          if (hg & 1) epilogue0<4>(a1, a2, warp * 2, t, ad01, ad2);
          else epilogue0<0>(a1, a2, warp * 2, t, ad01, ad2);
          fence_async_smem();
          bar_arrive(NB_STAGED, 544);
        }
      }
      mbar_wait_u(bars + B_F, 0);
#pragma unroll
      for (int s = 0; s < 8; s++) mbar_arrive_if(bars + B_KE + (s < 4 ? 64 : 0) + 8 * (s & 3), lead);
      if (hg & 1) epilogue1<4>(a1, a2, k, t, ad01, ad2);
      else epilogue1<0>(a1, a2, k, t, ad01, ad2);
      pin(k[0]); pin(k[1]);
      fence_async_smem();
      reg_dec<112>();
      bar_sync(NB_EPI, 512);
    }
    }
    middle(smem, k, wg, w4, lane, cm, neg1);
    if (wg >= 2) { reg_dec<24>(); return; }
    {
      if (lane == 0) asm volatile("prefetch.tensormap [%0];" ::"l"(&maps.out) : "memory");
      __syncwarp();
      asm volatile("barrier.cluster.arrive.relaxed.aligned;" ::: "memory");
      reg_inc<160>();
      float acc[80];
      uint32_t fa[4][4] = {}, fb[4][4] = {};
      const uint32_t arow = wg * 8192 + (lane >> 4) * 1024 + w4 * 256 + (lane & 15) * 16;
#pragma unroll 1
      for (int it = 0; it < 10; it += 2) {
        out_step(acc, fa, fb, it, it, sb, arow, bars, lead);
        out_step(acc, fb, fa, it + 1, 1, sb, arow, bars, lead);
      }
      wg_wait<0>();
      pin(acc);
#pragma unroll
      for (int i = 0; i < 4; i++) pin(fb[i]);
      asm volatile("barrier.cluster.wait.aligned;" ::: "memory");
      uint32_t remote, rbar;
      asm volatile("mapa.shared::cluster.u32 %0, %1, %2;" : "=r"(remote) : "r"(sb + OFF_Q + threadIdx.x * 16), "r"(half ^ 1));
      asm volatile("mapa.shared::cluster.u32 %0, %1, %2;" : "=r"(rbar) : "r"(bars + B_X), "r"(half ^ 1));
      if (threadIdx.x == 0) mbar_expect(bars + B_X, 20480);
#pragma unroll
      for (int j = 0; j < 5; j++) {
        uint32_t v[4];
#pragma unroll
        for (int u = 0; u < 4; u++) v[u] = half ? packbf(acc[8 * j + 2 * u], acc[8 * j + 2 * u + 1]) : packbf(acc[40 + 8 * j + 2 * u], acc[41 + 8 * j + 2 * u]);
        asm volatile("st.async.weak.shared::cluster.mbarrier::complete_tx::bytes.v4.b32 [%0], {%1,%2,%3,%4}, [%5];" ::"r"(remote + j * 4096), "r"(v[0]),
                     "r"(v[1]), "r"(v[2]), "r"(v[3]), "r"(rbar) : "memory");
      }
      mbar_wait_u(bars + B_OE, 1);
      mbar_wait_u(bars + B_X, 0);
      const uint32_t ob = sb + OFF_V + warp * 2560;
      const uint32_t oa = ob + (lane & 15) * 160 + (lane >> 4) * 16;
      uint32_t pk[20];
#pragma unroll
      for (int j = 0; j < 5; j++) {
        const uint4 r = *(const uint4*)(smem + OFF_Q + j * 4096 + threadIdx.x * 16);
        const uint32_t rv[4] = {r.x, r.y, r.z, r.w};
#pragma unroll
        for (int u = 0; u < 4; u++) {
          const float v0 = half ? acc[40 + 8 * j + 2 * u] : acc[8 * j + 2 * u], v1 = half ? acc[41 + 8 * j + 2 * u] : acc[8 * j + 2 * u + 1];
          pk[4 * j + u] = packbf(v0 + bf_lo(rv[u]), v1 + bf_hi(rv[u]));
        }
      }
#pragma unroll
      for (int j = 0; j < 10; j += 2) stsm4(oa + j * 16, pk[2 * j], pk[2 * j + 1], pk[2 * j + 2], pk[2 * j + 3]);
      fence_async_smem();
      __syncwarp();
      if (lane == 0) {
        asm volatile("cp.async.bulk.tensor.2d.global.shared::cta.bulk_group [%0, {%2,%3}], [%1];" ::"l"(&maps.out), "r"(ob), "r"(nt * 160 + half * 80),
                     "r"(mt3 * 128 + warp * 16) : "memory");
        asm volatile("cp.async.bulk.commit_group;" ::: "memory");
        asm volatile("cp.async.bulk.wait_group.read 0;" ::: "memory");
      }
    }
  }
}

typedef CUresult (*EncodeFn)(CUtensorMap*, CUtensorMapDataType, cuuint32_t, void*, const cuuint64_t*, const cuuint64_t*, const cuuint32_t*,
                             const cuuint32_t*, CUtensorMapInterleave, CUtensorMapSwizzle, CUtensorMapL2promotion, CUtensorMapFloatOOBfill);

void encode(EncodeFn fn, CUtensorMap* m, const void* p, int rank, const cuuint64_t* dims, const cuuint64_t* strides, const cuuint32_t* box,
            CUtensorMapSwizzle sw) {
  const cuuint32_t es[5] = {1, 1, 1, 1, 1};
  fn(m, CU_TENSOR_MAP_DATA_TYPE_BFLOAT16, rank, const_cast<void*>(p), dims, strides, box, es, CU_TENSOR_MAP_INTERLEAVE_NONE, sw,
     CU_TENSOR_MAP_L2_PROMOTION_L2_128B, CU_TENSOR_MAP_FLOAT_OOB_FILL_NONE);
}

}

extern "C" void kernel_launch(void* const* d_in, const int* in_sizes, int n_in, void* d_out, int out_size) {
  (void)in_sizes; (void)n_in; (void)out_size;
  static EncodeFn enc = nullptr;
  if (!enc) {
    void* fn = nullptr;
    cudaDriverEntryPointQueryResult qr;
    cudaGetDriverEntryPoint("cuTensorMapEncodeTiled", &fn, cudaEnableDefault, &qr);
    enc = (EncodeFn)fn;
    cudaFuncSetAttribute(fused_block, cudaFuncAttributeMaxDynamicSharedMemorySize, SMEM_BYTES);
  }
  Maps maps;
  {
    const cuuint64_t dx[2] = {640, 2048}, sx[1] = {1280};
    const cuuint32_t bo[2] = {80, 16};
    encode(enc, &maps.out, d_out, 2, dx, sx, bo, CU_TENSOR_MAP_SWIZZLE_NONE);
    const cuuint64_t dw[5] = {1920, 2, 4, 4, 20}, sw[4] = {3840, 8 * 3840, 2 * 3840, 32 * 3840};
    const cuuint32_t b64[5] = {64, 2, 4, 4, 1}, b16[5] = {16, 2, 4, 4, 1};
    encode(enc, &maps.a64, d_in[1], 5, dw, sw, b64, CU_TENSOR_MAP_SWIZZLE_128B);
    encode(enc, &maps.a16, d_in[1], 5, dw, sw, b16, CU_TENSOR_MAP_SWIZZLE_32B);
    encode(enc, &maps.b64, d_in[5], 5, dw, sw, b64, CU_TENSOR_MAP_SWIZZLE_128B);
    encode(enc, &maps.b16, d_in[5], 5, dw, sw, b16, CU_TENSOR_MAP_SWIZZLE_32B);
  }
  fused_block<<<NCTA, 640, SMEM_BYTES, cudaStreamPerThread>>>(maps, (const __nv_bfloat16*)d_in[0], (const __nv_bfloat16*)d_in[2],
                                                               (const __nv_bfloat16*)d_in[7],
                                                               (const uint8_t*)d_in[3], (const uint8_t*)d_in[6], 0x1F801F80u, 0xFFFFFFFFu);
}
```

```cpp
#include <cuda_runtime.h>
#include <cuda_bf16.h>
#include <cuda.h>
#include <stdint.h>

namespace {

constexpr int SEQ = 2048, DM = 640, NH = 32, NCTA = 128;
constexpr int IMG_HEAD = SEQ * 48;
#define POLY_MASK 0xF8F8u
constexpr float LOG2E = 1.4426950408889634f;
constexpr float QSCALE = 0.22360679774997896f * 1.4426950408889634f;
constexpr uint32_t BF_ONE = 0x3F80u;
constexpr uint32_t BF_MAGIC = 0x43E0u;
constexpr uint32_t BF_MU_HI = 0x4025u;
constexpr uint32_t BF_MU_LO = 0x3B8Bu;
constexpr float FAST_BOUND = 40.0f;

__device__ __align__(1024) uint8_t g_KV[2 * NH * IMG_HEAD];
__device__ __align__(1024) float2 g_KVA[NH * 480];
__device__ __align__(1024) float4 g_KMAX[8 * 16];
__device__ __align__(1024) float2 g_GATE[SEQ];
__device__ __align__(1024) uint8_t g_OAB[16 * 2 * 160 * 1024];
__device__ __align__(1024) uint8_t g_WOI[4 * 409600];
__device__ __align__(1024) uint32_t g_CNT[74 * 8];
constexpr int C_START = 0, C_WO = 1, C_KV = 2, C_KVP = 10, C_GATE = 26, C_OA = 42, C_OB = 58;

#define SPIN_LIMIT (1ll << 29)
#define SPIN_FAIL(code) __trap()
__device__ __forceinline__ uint32_t smem_u32(const void* p) { return (uint32_t)__cvta_generic_to_shared(p); }
__device__ __forceinline__ void mbar_init(uint32_t a, uint32_t c) { asm volatile("mbarrier.init.shared::cta.b64 [%0], %1;" ::"r"(a), "r"(c) : "memory"); }
__device__ __forceinline__ void mbar_expect(uint32_t a, uint32_t b) { asm volatile("mbarrier.arrive.expect_tx.shared::cta.b64 _, [%0], %1;" ::"r"(a), "r"(b) : "memory"); }
__device__ __forceinline__ void mbar_arrive(uint32_t a) { asm volatile("mbarrier.arrive.shared::cta.b64 _, [%0];" ::"r"(a) : "memory"); }
__device__ __forceinline__ uint32_t mbar_try(uint32_t a, uint32_t ph) {
  uint32_t ok;
  asm volatile("{\n.reg .pred p;\nmbarrier.try_wait.parity.shared::cta.b64 p, [%1], %2;\nselp.u32 %0, 1, 0, p;\n}\n" : "=r"(ok) : "r"(a), "r"(ph) : "memory");
  return ok;
}
__device__ __forceinline__ void mbar_wait(uint32_t a, uint32_t ph) {
  if (mbar_try(a, ph)) return;
  const long long t0 = clock64();
  while (!mbar_try(a, ph))
    if (clock64() - t0 > SPIN_LIMIT) { SPIN_FAIL(1000 + (a & 0x1FF) * 2 + ph); break; }
}
__device__ __forceinline__ void mbar_wait_u(uint32_t a, uint32_t ph) {
#pragma unroll 1
  for (int n = 0; n < (1 << 18); n++)
    if (__all_sync(~0u, mbar_try(a, ph))) break;
}
__device__ __forceinline__ uint32_t mbar_test(uint32_t a, uint32_t ph) {
  uint32_t ok;
  asm volatile("{\n.reg .pred p;\nmbarrier.test_wait.parity.shared::cta.b64 p, [%1], %2;\nselp.u32 %0, 1, 0, p;\n}\n" : "=r"(ok) : "r"(a), "r"(ph) : "memory");
  return ok;
}
__device__ __forceinline__ void mbar_arrive_if(uint32_t a, uint32_t flag) {
  asm volatile("{\n.reg .pred p;\nsetp.ne.u32 p, %1, 0;\n@p mbarrier.arrive.shared::cta.b64 _, [%0];\n}\n" ::"r"(a), "r"(flag) : "memory");
}
__device__ __forceinline__ void cnt_add(int slot) {
  asm volatile("fence.acq_rel.gpu;\nred.relaxed.gpu.global.add.u32 [%0], 1;" ::"l"(g_CNT + slot * 8) : "memory");
}
__device__ __forceinline__ void cnt_add_bulk(int slot) {
  asm volatile("fence.proxy.async.global;" ::: "memory");
  cnt_add(slot);
}
__device__ __forceinline__ void cnt_wait(int slot, uint32_t target) {
  uint32_t v;
  long long t0 = 0;
  for (;;) {
    asm volatile("ld.relaxed.gpu.global.u32 %0, [%1];" : "=r"(v) : "l"(g_CNT + slot * 8) : "memory");
    if ((int32_t)(v - target) >= 0) break;
    __nanosleep(40);
    if (!t0) t0 = clock64();
    else if (clock64() - t0 > SPIN_LIMIT) { SPIN_FAIL(slot); break; }
  }
  asm volatile("ld.acquire.gpu.global.u32 %0, [%1];" : "=r"(v) : "l"(g_CNT + slot * 8) : "memory");
  asm volatile("fence.proxy.async.global;" ::: "memory");
}
__device__ __forceinline__ void bulk_commit_wait() { asm volatile("cp.async.bulk.commit_group;\ncp.async.bulk.wait_group 0;" ::: "memory"); }
template <bool MC>
__device__ __forceinline__ void tma5(uint32_t dst, const CUtensorMap* m, int c0, int c4, uint32_t bar) {
  if (MC)
    asm volatile("cp.async.bulk.tensor.5d.shared::cluster.global.mbarrier::complete_tx::bytes.multicast::cluster [%0], [%1, {%3,%5,%5,%5,%4}], [%2], %6;"
                 ::"r"(dst), "l"(m), "r"(bar), "r"(c0), "r"(c4), "r"(0), "h"((uint16_t)3) : "memory");
  else
    asm volatile("cp.async.bulk.tensor.5d.shared::cluster.global.mbarrier::complete_tx::bytes [%0], [%1, {%3,%5,%5,%5,%4}], [%2];"
                 ::"r"(dst), "l"(m), "r"(bar), "r"(c0), "r"(c4), "r"(0) : "memory");
}
__device__ __forceinline__ void mbar_arrive_pair(uint32_t a, uint32_t flag) {
  asm volatile("{\n.reg .pred p;\n.reg .b32 r0, r1;\nsetp.ne.u32 p, %1, 0;\nmapa.shared::cluster.u32 r0, %0, 0;\nmapa.shared::cluster.u32 r1, %0, 1;\n"
               "@p mbarrier.arrive.relaxed.cluster.shared::cluster.b64 _, [r0];\n@p mbarrier.arrive.relaxed.cluster.shared::cluster.b64 _, [r1];\n}\n" ::"r"(a), "r"(flag) : "memory");
}
__device__ __forceinline__ void bulk_g2s(uint32_t dst, const void* src, uint32_t bytes, uint32_t bar) {
  asm volatile("cp.async.bulk.shared::cluster.global.mbarrier::complete_tx::bytes [%0], [%1], %2, [%3];" ::"r"(dst), "l"(src), "r"(bytes), "r"(bar) : "memory");
}
__device__ __forceinline__ void fence_async_smem() { asm volatile("fence.proxy.async.shared::cta;" ::: "memory"); }
__device__ __forceinline__ void bar_sync(int id, int n) { asm volatile("bar.sync %0, %1;" ::"r"(id), "r"(n) : "memory"); }
__device__ __forceinline__ void bar_arrive(int id, int n) { asm volatile("bar.arrive %0, %1;" ::"r"(id), "r"(n) : "memory"); }
__device__ __forceinline__ void wg_fence() { asm volatile("wgmma.fence.sync.aligned;" ::: "memory"); }
__device__ __forceinline__ void wg_commit() { asm volatile("wgmma.commit_group.sync.aligned;" ::: "memory"); }
template <int N> __device__ __forceinline__ void wg_wait() { asm volatile("wgmma.wait_group.sync.aligned %0;" ::"n"(N) : "memory"); }
template <int N> __device__ __forceinline__ void reg_inc() { asm volatile("setmaxnreg.inc.sync.aligned.u32 %0;" ::"n"(N)); }
template <int N> __device__ __forceinline__ void reg_dec() { asm volatile("setmaxnreg.dec.sync.aligned.u32 %0;" ::"n"(N)); }
template <int N> __device__ __forceinline__ void pin(float (&r)[N]) {
#pragma unroll
  for (int i = 0; i < N; i++) asm volatile("" : "+f"(r[i])::"memory");
}
template <int N> __device__ __forceinline__ void pin(uint32_t (&r)[N]) {
#pragma unroll
  for (int i = 0; i < N; i++) asm volatile("" : "+r"(r[i])::"memory");
}
__device__ __forceinline__ uint64_t mkdesc(uint32_t addr, uint32_t lbo, uint32_t sbo, uint32_t swz) {
  return (uint64_t)((addr & 0x3FFFF) >> 4) | ((uint64_t)(lbo >> 4) << 16) | ((uint64_t)(sbo >> 4) << 32) | ((uint64_t)swz << 62);
}
__device__ __forceinline__ float ex2(float x) { float y; asm("ex2.approx.ftz.f32 %0, %1;" : "=f"(y) : "f"(x)); return y; }
__device__ __forceinline__ float rcp(float x) { float y; asm("rcp.approx.ftz.f32 %0, %1;" : "=f"(y) : "f"(x)); return y; }
__device__ __forceinline__ float sqrt_ap(float x) { float y; asm("sqrt.approx.f32 %0, %1;" : "=f"(y) : "f"(x)); return y; }
__device__ __forceinline__ uint32_t packbf(float lo, float hi) { uint32_t d; asm("cvt.rn.bf16x2.f32 %0, %1, %2;" : "=r"(d) : "f"(hi), "f"(lo)); return d; }
__device__ __forceinline__ float bf_lo(uint32_t v) { return __uint_as_float(v << 16); }
__device__ __forceinline__ float bf_hi(uint32_t v) { return __uint_as_float(v & 0xFFFF0000u); }
__device__ __forceinline__ float bf_round(float x) { return bf_lo(packbf(x, 0.f)); }
__device__ __forceinline__ uint4 ldg_cg4(const void* p) { uint4 v; asm volatile("ld.global.cg.v4.b32 {%0,%1,%2,%3}, [%4];" : "=r"(v.x), "=r"(v.y), "=r"(v.z), "=r"(v.w) : "l"(p) : "memory"); return v; }
__device__ __forceinline__ void sts32(uint32_t a, uint32_t v) { asm volatile("st.shared.b32 [%0], %1;" ::"r"(a), "r"(v) : "memory"); }
__device__ __forceinline__ void stsm4(uint32_t a, uint32_t r0, uint32_t r1, uint32_t r2, uint32_t r3) {
  asm volatile("stmatrix.sync.aligned.m8n8.x4.shared.b16 [%0], {%1,%2,%3,%4};" ::"r"(a), "r"(r0), "r"(r1), "r"(r2), "r"(r3) : "memory");
}

__device__ __forceinline__ void stsm2(uint32_t a, uint32_t r0, uint32_t r1) {
  asm volatile("stmatrix.sync.aligned.m8n8.x2.shared.b16 [%0], {%1,%2};" ::"r"(a), "r"(r0), "r"(r1) : "memory");
}
__device__ __forceinline__ uint4 ldg_x(const void* p) {
  uint4 v;
  asm volatile("ld.global.nc.L1::no_allocate.L2::128B.v4.b32 {%0,%1,%2,%3}, [%4];" : "=r"(v.x), "=r"(v.y), "=r"(v.z), "=r"(v.w) : "l"(p));
  return v;
}
__device__ __forceinline__ float2 lds_f2(uint32_t a) { float2 v; asm volatile("ld.shared.v2.f32 {%0,%1}, [%2];" : "=f"(v.x), "=f"(v.y) : "r"(a) : "memory"); return v; }
__device__ __forceinline__ void bulk_s2g(void* dst, uint32_t src, uint32_t bytes) {
  asm volatile("cp.async.bulk.global.shared::cta.bulk_group [%0], [%1], %2;" ::"l"(dst), "r"(src), "r"(bytes) : "memory");
}

__device__ __forceinline__ void mma_n24_ss_tb(float (&d)[12], uint64_t adesc, uint64_t bdesc, int acc) {
  asm volatile("{\n.reg .pred p;\nsetp.ne.b32 p, %14, 0;\n"
      "wgmma.mma_async.sync.aligned.m64n24k16.f32.bf16.bf16 "
      "{%0,%1,%2,%3,%4,%5,%6,%7,%8,%9,%10,%11}, "
      "%12, %13, p, 1, 1, 0, 1;\n}\n"
      : "+f"(d[0]), "+f"(d[1]), "+f"(d[2]), "+f"(d[3]), "+f"(d[4]), "+f"(d[5]), "+f"(d[6]), "+f"(d[7]),
        "+f"(d[8]), "+f"(d[9]), "+f"(d[10]), "+f"(d[11])
      : "l"(adesc), "l"(bdesc), "r"(acc));
}
__device__ __forceinline__ void mma_n128_rs_tb(float (&d)[64], uint32_t a0, uint32_t a1, uint32_t a2, uint32_t a3, uint64_t bdesc, int acc) {
  asm volatile("{\n.reg .pred p;\nsetp.ne.b32 p, %69, 0;\n"
      "wgmma.mma_async.sync.aligned.m64n128k16.f32.bf16.bf16 "
      "{%0,%1,%2,%3,%4,%5,%6,%7,%8,%9,%10,%11,%12,%13,%14,%15,"
      "%16,%17,%18,%19,%20,%21,%22,%23,%24,%25,%26,%27,%28,%29,%30,%31,"
      "%32,%33,%34,%35,%36,%37,%38,%39,%40,%41,%42,%43,%44,%45,%46,%47,"
      "%48,%49,%50,%51,%52,%53,%54,%55,%56,%57,%58,%59,%60,%61,%62,%63}, "
      "{%64,%65,%66,%67}, %68, p, 1, 1, 1;\n}\n"
      : "+f"(d[0]), "+f"(d[1]), "+f"(d[2]), "+f"(d[3]), "+f"(d[4]), "+f"(d[5]), "+f"(d[6]), "+f"(d[7]),
        "+f"(d[8]), "+f"(d[9]), "+f"(d[10]), "+f"(d[11]), "+f"(d[12]), "+f"(d[13]), "+f"(d[14]), "+f"(d[15]),
        "+f"(d[16]), "+f"(d[17]), "+f"(d[18]), "+f"(d[19]), "+f"(d[20]), "+f"(d[21]), "+f"(d[22]), "+f"(d[23]),
        "+f"(d[24]), "+f"(d[25]), "+f"(d[26]), "+f"(d[27]), "+f"(d[28]), "+f"(d[29]), "+f"(d[30]), "+f"(d[31]),
        "+f"(d[32]), "+f"(d[33]), "+f"(d[34]), "+f"(d[35]), "+f"(d[36]), "+f"(d[37]), "+f"(d[38]), "+f"(d[39]),
        "+f"(d[40]), "+f"(d[41]), "+f"(d[42]), "+f"(d[43]), "+f"(d[44]), "+f"(d[45]), "+f"(d[46]), "+f"(d[47]),
        "+f"(d[48]), "+f"(d[49]), "+f"(d[50]), "+f"(d[51]), "+f"(d[52]), "+f"(d[53]), "+f"(d[54]), "+f"(d[55]),
        "+f"(d[56]), "+f"(d[57]), "+f"(d[58]), "+f"(d[59]), "+f"(d[60]), "+f"(d[61]), "+f"(d[62]), "+f"(d[63])
      : "r"(a0), "r"(a1), "r"(a2), "r"(a3), "l"(bdesc), "r"(acc));
}
__device__ __forceinline__ void mma_n64_rs_tb(float (&d)[32], uint32_t a0, uint32_t a1, uint32_t a2, uint32_t a3, uint64_t bdesc, int acc) {
  asm volatile("{\n.reg .pred p;\nsetp.ne.b32 p, %37, 0;\n"
      "wgmma.mma_async.sync.aligned.m64n64k16.f32.bf16.bf16 "
      "{%0,%1,%2,%3,%4,%5,%6,%7,%8,%9,%10,%11,%12,%13,%14,%15,"
      "%16,%17,%18,%19,%20,%21,%22,%23,%24,%25,%26,%27,%28,%29,%30,%31}, "
      "{%32,%33,%34,%35}, %36, p, 1, 1, 1;\n}\n"
      : "+f"(d[0]), "+f"(d[1]), "+f"(d[2]), "+f"(d[3]), "+f"(d[4]), "+f"(d[5]), "+f"(d[6]), "+f"(d[7]),
        "+f"(d[8]), "+f"(d[9]), "+f"(d[10]), "+f"(d[11]), "+f"(d[12]), "+f"(d[13]), "+f"(d[14]), "+f"(d[15]),
        "+f"(d[16]), "+f"(d[17]), "+f"(d[18]), "+f"(d[19]), "+f"(d[20]), "+f"(d[21]), "+f"(d[22]), "+f"(d[23]),
        "+f"(d[24]), "+f"(d[25]), "+f"(d[26]), "+f"(d[27]), "+f"(d[28]), "+f"(d[29]), "+f"(d[30]), "+f"(d[31])
      : "r"(a0), "r"(a1), "r"(a2), "r"(a3), "l"(bdesc), "r"(acc));
}
__device__ __forceinline__ void mma_n48_rs_tb(float (&d)[24], uint32_t a0, uint32_t a1, uint32_t a2, uint32_t a3, uint64_t bdesc, int acc) {
  asm volatile("{\n.reg .pred p;\nsetp.ne.b32 p, %29, 0;\n"
      "wgmma.mma_async.sync.aligned.m64n48k16.f32.bf16.bf16 "
      "{%0,%1,%2,%3,%4,%5,%6,%7,%8,%9,%10,%11,%12,%13,%14,%15,"
      "%16,%17,%18,%19,%20,%21,%22,%23}, "
      "{%24,%25,%26,%27}, %28, p, 1, 1, 1;\n}\n"
      : "+f"(d[0]), "+f"(d[1]), "+f"(d[2]), "+f"(d[3]), "+f"(d[4]), "+f"(d[5]), "+f"(d[6]), "+f"(d[7]),
        "+f"(d[8]), "+f"(d[9]), "+f"(d[10]), "+f"(d[11]), "+f"(d[12]), "+f"(d[13]), "+f"(d[14]), "+f"(d[15]),
        "+f"(d[16]), "+f"(d[17]), "+f"(d[18]), "+f"(d[19]), "+f"(d[20]), "+f"(d[21]), "+f"(d[22]), "+f"(d[23])
      : "r"(a0), "r"(a1), "r"(a2), "r"(a3), "l"(bdesc), "r"(acc));
}
__device__ __forceinline__ void mma_n64_rs(float (&d)[32], uint32_t a0, uint32_t a1, uint32_t a2, uint32_t a3, uint64_t bdesc, int acc) {
  asm volatile("{\n.reg .pred p;\nsetp.ne.b32 p, %37, 0;\n"
      "wgmma.mma_async.sync.aligned.m64n64k16.f32.bf16.bf16 "
      "{%0,%1,%2,%3,%4,%5,%6,%7,%8,%9,%10,%11,%12,%13,%14,%15,"
      "%16,%17,%18,%19,%20,%21,%22,%23,%24,%25,%26,%27,%28,%29,%30,%31}, "
      "{%32,%33,%34,%35}, %36, p, 1, 1, 0;\n}\n"
      : "+f"(d[0]), "+f"(d[1]), "+f"(d[2]), "+f"(d[3]), "+f"(d[4]), "+f"(d[5]), "+f"(d[6]), "+f"(d[7]),
        "+f"(d[8]), "+f"(d[9]), "+f"(d[10]), "+f"(d[11]), "+f"(d[12]), "+f"(d[13]), "+f"(d[14]), "+f"(d[15]),
        "+f"(d[16]), "+f"(d[17]), "+f"(d[18]), "+f"(d[19]), "+f"(d[20]), "+f"(d[21]), "+f"(d[22]), "+f"(d[23]),
        "+f"(d[24]), "+f"(d[25]), "+f"(d[26]), "+f"(d[27]), "+f"(d[28]), "+f"(d[29]), "+f"(d[30]), "+f"(d[31])
      : "r"(a0), "r"(a1), "r"(a2), "r"(a3), "l"(bdesc), "r"(acc));
}
__device__ __forceinline__ void mma_n80_rs_tb(float (&d)[40], uint32_t a0, uint32_t a1, uint32_t a2, uint32_t a3, uint64_t bdesc, int acc) {
  asm volatile("{\n.reg .pred p;\nsetp.ne.b32 p, %45, 0;\n"
      "wgmma.mma_async.sync.aligned.m64n80k16.f32.bf16.bf16 "
      "{%0,%1,%2,%3,%4,%5,%6,%7,%8,%9,%10,%11,%12,%13,%14,%15,"
      "%16,%17,%18,%19,%20,%21,%22,%23,%24,%25,%26,%27,%28,%29,%30,%31,"
      "%32,%33,%34,%35,%36,%37,%38,%39}, "
      "{%40,%41,%42,%43}, %44, p, 1, 1, 1;\n}\n"
      : "+f"(d[0]), "+f"(d[1]), "+f"(d[2]), "+f"(d[3]), "+f"(d[4]), "+f"(d[5]), "+f"(d[6]), "+f"(d[7]),
        "+f"(d[8]), "+f"(d[9]), "+f"(d[10]), "+f"(d[11]), "+f"(d[12]), "+f"(d[13]), "+f"(d[14]), "+f"(d[15]),
        "+f"(d[16]), "+f"(d[17]), "+f"(d[18]), "+f"(d[19]), "+f"(d[20]), "+f"(d[21]), "+f"(d[22]), "+f"(d[23]),
        "+f"(d[24]), "+f"(d[25]), "+f"(d[26]), "+f"(d[27]), "+f"(d[28]), "+f"(d[29]), "+f"(d[30]), "+f"(d[31]),
        "+f"(d[32]), "+f"(d[33]), "+f"(d[34]), "+f"(d[35]), "+f"(d[36]), "+f"(d[37]), "+f"(d[38]), "+f"(d[39])
      : "r"(a0), "r"(a1), "r"(a2), "r"(a3), "l"(bdesc), "r"(acc));
}
__device__ __forceinline__ void mma_n24_rs_tb(float (&d)[12], uint32_t a0, uint32_t a1, uint32_t a2, uint32_t a3, uint64_t bdesc, int acc) {
  asm volatile("{\n.reg .pred p;\nsetp.ne.b32 p, %17, 0;\n"
      "wgmma.mma_async.sync.aligned.m64n24k16.f32.bf16.bf16 "
      "{%0,%1,%2,%3,%4,%5,%6,%7,%8,%9,%10,%11}, "
      "{%12,%13,%14,%15}, %16, p, 1, 1, 1;\n}\n"
      : "+f"(d[0]), "+f"(d[1]), "+f"(d[2]), "+f"(d[3]), "+f"(d[4]), "+f"(d[5]), "+f"(d[6]), "+f"(d[7]),
        "+f"(d[8]), "+f"(d[9]), "+f"(d[10]), "+f"(d[11])
      : "r"(a0), "r"(a1), "r"(a2), "r"(a3), "l"(bdesc), "r"(acc));
}
__device__ __forceinline__ void mma_n24_ss_tatb(float (&d)[12], uint64_t adesc, uint64_t bdesc, int acc) {
  asm volatile("{\n.reg .pred p;\nsetp.ne.b32 p, %14, 0;\n"
      "wgmma.mma_async.sync.aligned.m64n24k16.f32.bf16.bf16 "
      "{%0,%1,%2,%3,%4,%5,%6,%7,%8,%9,%10,%11}, "
      "%12, %13, p, 1, 1, 1, 1;\n}\n"
      : "+f"(d[0]), "+f"(d[1]), "+f"(d[2]), "+f"(d[3]), "+f"(d[4]), "+f"(d[5]), "+f"(d[6]), "+f"(d[7]),
        "+f"(d[8]), "+f"(d[9]), "+f"(d[10]), "+f"(d[11])
      : "l"(adesc), "l"(bdesc), "r"(acc));
}

constexpr int W_STAGE = 30720, W_NST = 5;
constexpr int KV_CHUNK = 12288, KV_SLOT = 2 * KV_CHUNK;
constexpr int O_STAGE = 36864;
constexpr int OFF_PHK = 4 * KV_SLOT;
constexpr int OFF_KVS = OFF_PHK + 2 * 10240 + 4096;
constexpr int OFF_GATE = 112640;
constexpr int OFF_Q = W_NST * W_STAGE;
constexpr int OFF_V = OFF_Q + 24576;
constexpr int OFF_AQ = OFF_V + 24576;
constexpr int OFF_WPH = OFF_AQ + 24576;
constexpr int OFF_BAR = OFF_WPH + 4608;
constexpr int B_WF = 0, B_WE = 40, B_KF = 80, B_KE = 112, B_OF = 208, B_OE = 248, B_RF = 288, B_Z = 296, B_G = 304, B_X = 312, B_P1 = 320, B_R = 328, B_F = 336;
constexpr int OFF_MISC = OFF_BAR + 352;
constexpr int SMEM_BYTES = OFF_MISC + 32;
__device__ __forceinline__ uint32_t o_stage(int s) { return s == 0 ? OFF_V : s == 1 ? OFF_Q - O_STAGE : (s - 2) * O_STAGE; }
__device__ __forceinline__ uint32_t o_stage_a(int s) { return s == 4 ? OFF_V + O_STAGE : o_stage(s); }
constexpr int NB_STAGED = 1, NB_WG = 3, NB_BG = 7, NB_NORM = 13, NB_BOUND = 14, NB_EPI = 15, NB_PHIK = 8, NB_TAIL = 9, NB_READ = 10, NB_LAST = 11, NB_HELP = 12;

template <int SEC, int J, int HF>
__device__ __forceinline__ float2 grp(const float (&a1)[2][64], const float (&a2)[24]) {
  constexpr int S = SEC & 3, J1 = (SEC & 4) ? J - 2 : J, J2 = (SEC & 4) ? J : J - 8;
  if constexpr (J1 >= 0 && J1 < 8) return make_float2(a1[S >> 1][(8 * (S & 1) + J1) * 4 + 2 * HF], a1[S >> 1][(8 * (S & 1) + J1) * 4 + 2 * HF + 1]);
  else return make_float2(a2[(2 * S + J2) * 4 + 2 * HF], a2[(2 * S + J2) * 4 + 2 * HF + 1]);
}
__device__ __forceinline__ uint32_t pks(float2 v, float s) { return packbf(v.x * s, v.y * s); }

template <int SEC, int PR>
__device__ __forceinline__ void stage_pair(const float (&a1)[2][64], const float (&a2)[24], float sc0, float sc1, float sm, uint32_t xe0, uint32_t xe1,
                                           uint32_t xo0, uint32_t xo1, uint32_t ad01, uint32_t ad2, int t) {
  const uint32_t off = 2 * PR * 3072;
  stsm4(ad01 + off, pks(grp<SEC, 5 * PR, 0>(a1, a2), sc0), pks(grp<SEC, 5 * PR, 1>(a1, a2), sc1), pks(grp<SEC, 5 * PR + 1, 0>(a1, a2), sc0),
        pks(grp<SEC, 5 * PR + 1, 1>(a1, a2), sc1));
  stsm4(ad01 + off + 3072, pks(grp<SEC, 5 * PR + 3, 0>(a1, a2), sc0), pks(grp<SEC, 5 * PR + 3, 1>(a1, a2), sc1),
        pks(grp<SEC, 5 * PR + 4, 0>(a1, a2), sc0), pks(grp<SEC, 5 * PR + 4, 1>(a1, a2), sc1));
  const uint32_t m0 = pks(grp<SEC, 5 * PR + 2, 0>(a1, a2), sc0 * sm), m1 = pks(grp<SEC, 5 * PR + 2, 1>(a1, a2), sc1 * sm);
  const bool lo = t < 2;
  stsm4(ad2 + off, lo ? m0 : xe0, lo ? m1 : xe1, lo ? xo0 : m0, lo ? xo1 : m1);
}

template <bool EXACT>
__device__ __forceinline__ bool hedgehog(const float (&p)[12], uint32_t (&f)[10], int t) {
  const bool lo = t < 2;
  bool safe = true;
#pragma unroll
  for (int hf = 0; hf < 2; hf++) {
    const float v[6] = {p[2 * hf], p[2 * hf + 1], p[4 + 2 * hf], p[5 + 2 * hf], p[8 + 2 * hf], p[9 + 2 * hf]};
    float ep[4], en[4], m0, m1;
    const float sg = lo ? LOG2E : -LOG2E;
    if (EXACT) {
      float mx = fmaxf(fmaxf(fmaxf(v[0], v[1]), fmaxf(v[2], v[3])), fmaxf(v[4], v[5]));
      float mn = fminf(fminf(fminf(v[0], v[1]), fminf(v[2], v[3])), fminf(v[4], v[5]));
      mx = fmaxf(mx, __shfl_xor_sync(~0u, mx, 1)); mn = fminf(mn, __shfl_xor_sync(~0u, mn, 1));
      mx = fmaxf(mx, __shfl_xor_sync(~0u, mx, 2)); mn = fminf(mn, __shfl_xor_sync(~0u, mn, 2));
      const float bp = -mx * LOG2E, bn = mn * LOG2E, bm = lo ? bp : bn;
#pragma unroll
      for (int i = 0; i < 4; i++) { ep[i] = ex2(fmaf(v[i], LOG2E, bp)); en[i] = ex2(fmaf(v[i], -LOG2E, bn)); }
      m0 = ex2(fmaf(v[4], sg, bm)); m1 = ex2(fmaf(v[5], sg, bm));
    } else {
#pragma unroll
      for (int i = 0; i < 4; i++) ep[i] = ex2(v[i] * LOG2E);
      const float r0 = rcp(ep[0] * ep[1]), r1 = rcp(ep[2] * ep[3]);
      en[0] = r0 * ep[1]; en[1] = r0 * ep[0]; en[2] = r1 * ep[3]; en[3] = r1 * ep[2];
      m0 = ex2(v[4] * sg); m1 = ex2(v[5] * sg);
    }
    const float ms = m0 + m1;
    float sp = (ep[0] + ep[1]) + (ep[2] + ep[3]) + (lo ? ms : 0.f);
    float sn = (en[0] + en[1]) + (en[2] + en[3]) + (lo ? 0.f : ms);
    sp += __shfl_xor_sync(~0u, sp, 1); sn += __shfl_xor_sync(~0u, sn, 1);
    sp += __shfl_xor_sync(~0u, sp, 2); sn += __shfl_xor_sync(~0u, sn, 2);
    safe = safe && sp <= 1.0e12f && sn <= 1.0e12f;
    const float r = rcp(sp * sn), rp = r * sn, rn = r * sp, rm = lo ? rp : rn;
    f[0 + hf] = packbf(ep[0] * rp, ep[1] * rp);
    f[2 + hf] = packbf(ep[2] * rp, ep[3] * rp);
    f[4 + hf] = packbf(m0 * rm, m1 * rm);
    f[6 + hf] = packbf(en[0] * rn, en[1] * rn);
    f[8 + hf] = packbf(en[2] * rn, en[3] * rn);
  }
  return safe;
}
__device__ __forceinline__ void hedgehog2(const float (&p)[2][12], uint32_t (&f)[2][10], int t) {
  const bool s0 = hedgehog<false>(p[0], f[0], t), s1 = hedgehog<false>(p[1], f[1], t);
  if (!__all_sync(~0u, s0 && s1)) { hedgehog<true>(p[0], f[0], t); hedgehog<true>(p[1], f[1], t); }
}

template <int O>
__device__ __forceinline__ void epilogue0(const float (&a1)[2][64], const float (&a2)[24], int rg, int t, uint32_t ad01, uint32_t ad2) {
  const bool p0 = (POLY_MASK >> rg) & 1, p1 = (POLY_MASK >> (rg + 1)) & 1;
  const uint32_t kp = (t & 1) ? 0u : (BF_ONE | (BF_MAGIC << 16)), km = (t & 1) ? BF_MU_LO : (BF_ONE | (BF_MU_HI << 16));
  const uint32_t vp = (t & 1) ? 0u : (BF_ONE | 0x8000u), vm = (t & 1) ? 0u : BF_ONE;
  const uint32_t k0 = p0 ? kp : km, k1 = p1 ? kp : km, v0 = p0 ? vp : vm, v1 = p1 ? vp : vm;
  const float s0 = p0 ? -1.f : 1.f, s1 = p1 ? -1.f : 1.f;
  stage_pair<O + 1, 0>(a1, a2, 1.f, 1.f, 1.f, k0, k1, k0, k1, ad01 + OFF_AQ, ad2 + OFF_AQ, t);
  stage_pair<O + 1, 1>(a1, a2, 1.f, 1.f, 1.f, k0, k1, k0, k1, ad01 + OFF_AQ, ad2 + OFF_AQ, t);
  stage_pair<O + 2, 0>(a1, a2, s0, s1, 1.f, v0, v1, v0, v1, ad01 + OFF_V, ad2 + OFF_V, t);
  stage_pair<O + 2, 1>(a1, a2, s0, s1, 1.f, v0, v1, v0, v1, ad01 + OFF_V, ad2 + OFF_V, t);
  stage_pair<O + 0, 0>(a1, a2, QSCALE, QSCALE, 1.f, 0u, 0u, 0u, 0u, ad01 + OFF_Q, ad2 + OFF_Q, t);
  stage_pair<O + 0, 1>(a1, a2, QSCALE, QSCALE, 1.f, 0u, 0u, 0u, 0u, ad01 + OFF_Q, ad2 + OFF_Q, t);
}
template <int O, int PR>
__device__ __forceinline__ void pack_pair(const float (&a1)[2][64], const float (&a2)[24], uint32_t (&k)[10]) {
#pragma unroll
  for (int hf = 0; hf < 2; hf++) {
    k[0 + hf] = pks(hf ? grp<O + 1, 5 * PR, 1>(a1, a2) : grp<O + 1, 5 * PR, 0>(a1, a2), 1.f);
    k[2 + hf] = pks(hf ? grp<O + 1, 5 * PR + 1, 1>(a1, a2) : grp<O + 1, 5 * PR + 1, 0>(a1, a2), 1.f);
    k[4 + hf] = pks(hf ? grp<O + 1, 5 * PR + 3, 1>(a1, a2) : grp<O + 1, 5 * PR + 3, 0>(a1, a2), 1.f);
    k[6 + hf] = pks(hf ? grp<O + 1, 5 * PR + 4, 1>(a1, a2) : grp<O + 1, 5 * PR + 4, 0>(a1, a2), 1.f);
    k[8 + hf] = pks(hf ? grp<O + 1, 5 * PR + 2, 1>(a1, a2) : grp<O + 1, 5 * PR + 2, 0>(a1, a2), 1.f);
  }
}
template <int O>
__device__ __forceinline__ void epilogue1(const float (&a1)[2][64], const float (&a2)[24], uint32_t (&k)[2][10], int t, uint32_t ad01, uint32_t ad2) {
  stage_pair<O + 0, 0>(a1, a2, 1.f, 1.f, 0.5f, 0u, 0u, 0u, 0u, ad01 + OFF_AQ, ad2 + OFF_AQ, t);
  stage_pair<O + 0, 1>(a1, a2, 1.f, 1.f, 0.5f, 0u, 0u, 0u, 0u, ad01 + OFF_AQ, ad2 + OFF_AQ, t);
  const uint32_t one = (t & 1) ? 0u : BF_ONE;
  stage_pair<O + 2, 0>(a1, a2, 1.f, 1.f, 1.f, one, one, one, one, ad01 + OFF_V, ad2 + OFF_V, t);
  stage_pair<O + 2, 1>(a1, a2, 1.f, 1.f, 1.f, one, one, one, one, ad01 + OFF_V, ad2 + OFF_V, t);
  pack_pair<O, 0>(a1, a2, k[0]);
  pack_pair<O, 1>(a1, a2, k[1]);
}
__device__ __forceinline__ float row_norm2(const uint8_t* a, int odd) {
  float n = 0.f;
#pragma unroll
  for (int c = 0; c < 2; c++) {
    const uint4 v = *(const uint4*)(a + c * 128);
    const uint32_t w[4] = {v.x, v.y, v.z, v.w};
#pragma unroll
    for (int i = 0; i < 4; i++) n = fmaf(bf_lo(w[i]), bf_lo(w[i]), fmaf(bf_hi(w[i]), bf_hi(w[i]), n));
  }
  const uint2 v = *(const uint2*)(a + 256 + odd * 8);
  n = fmaf(bf_lo(v.x), bf_lo(v.x), fmaf(bf_hi(v.x), bf_hi(v.x), n));
  return fmaf(bf_lo(v.y), bf_lo(v.y), fmaf(bf_hi(v.y), bf_hi(v.y), n));
}

__device__ __forceinline__ void issue_proj(float (&p)[2][12], uint32_t img, uint32_t wph) {
  const uint64_t ad = mkdesc(img, 128, 384, 0), ad2 = mkdesc(img + 256, 0, 384, 0), wd = mkdesc(wph, 384, 128, 0), wd2 = mkdesc(wph + 768, 0, 128, 0);
#pragma unroll
  for (int i = 0; i < 2; i++) {
    mma_n24_ss_tb(p[i], ad + i * 192, wd + i * 72, 0);
    mma_n24_ss_tb(p[i], ad2 + i * 192, wd2 + i * 72, 1);
  }
}

__device__ __forceinline__ uint32_t exp2_bits(float y0, float y1, uint32_t cm, uint32_t neg1) {
  uint32_t w, m, r;
  asm("prmt.b32 %0, %1, %2, 0x6521;" : "=r"(w) : "f"(y0), "f"(y1));
  asm("lop3.b32 %0, %1, 0x007F007F, %2, 0xEA;" : "=r"(m) : "r"(w), "r"(cm));
  const uint32_t e = m * neg1 + w;
  asm("fma.rn.bf16x2 %0, %1, %2, %3;" : "=r"(r) : "r"(w), "r"(m), "r"(e));
  return r;
}
template <int HI>
__device__ __forceinline__ void exp_tile(const float (&s)[32], uint32_t (&p)[16], uint32_t cm, uint32_t neg1) {
#pragma unroll
  for (int g = 0; g < 8; g++) {
    if ((POLY_MASK >> (g + 8 * HI)) & 1) {
      p[2 * g] = exp2_bits(s[4 * g], s[4 * g + 1], cm, neg1);
      p[2 * g + 1] = exp2_bits(s[4 * g + 2], s[4 * g + 3], cm, neg1);
    } else {
      p[2 * g] = packbf(ex2(s[4 * g]), ex2(s[4 * g + 1]));
      p[2 * g + 1] = packbf(ex2(s[4 * g + 2]), ex2(s[4 * g + 3]));
    }
  }
}
struct AttnDesc { uint64_t k, k2, v; };
__device__ __forceinline__ void issue_qk(float (&s)[32], const uint32_t (&q)[8], const AttnDesc& d, uint32_t ko) {
  mma_n64_rs(s, q[0], q[1], q[2], q[3], d.k + ko, 0);
  mma_n64_rs(s, q[4], q[5], q[6], q[7], d.k2 + ko, 1);
}
__device__ __forceinline__ void issue_pv(float (&o)[12], const uint32_t (&p)[16], uint64_t vd, int acc) {
#pragma unroll
  for (int kk = 0; kk < 4; kk++) mma_n24_rs_tb(o, p[4 * kk], p[4 * kk + 1], p[4 * kk + 2], p[4 * kk + 3], vd + kk * 48, acc | kk);
}
__device__ __forceinline__ void load_q(uint32_t (&q)[8], uint32_t a) {
#pragma unroll
  for (int i = 0; i < 6; i++) asm volatile("ld.shared.b32 %0, [%1];" : "=r"(q[i]) : "r"(a + (i >> 1) * 128 + (i & 1) * 384) : "memory");
}
template <int SL>
__device__ __forceinline__ void attn_chunk(float (&s)[32], uint32_t (&p0)[16], uint32_t (&p1)[16], float (&o)[12], const uint32_t (&q)[8],
                                           const AttnDesc& d, int acc, uint32_t full_next, uint32_t ph_next,
                                           uint32_t bars, uint32_t release, uint32_t cm, uint32_t neg1) {
  exp_tile<0>(s, p0, cm, neg1);
  wg_fence();
  issue_qk(s, q, d, SL * 1536 + 192);
  wg_commit();
  issue_pv(o, p0, d.v + SL * 1536, acc);
  wg_commit();
  wg_wait<1>();
  pin(s); pin(p1);
  mbar_arrive_if(bars + B_KE + 8 * ((SL + 3) & 3), release);
  const uint32_t ready = mbar_test(full_next, ph_next);
  exp_tile<1>(s, p1, cm, neg1);
  pin(p1);
  if (!__all_sync(~0u, ready)) mbar_wait_u(full_next, ph_next);
  wg_fence();
  issue_qk(s, q, d, ((SL + 1) & 3) * 1536);
  wg_commit();
  issue_pv(o, p1, d.v + SL * 1536 + 192, 1);
  wg_commit();
  wg_wait<1>();
  pin(s); pin(p0);
}
__device__ __forceinline__ int bgroup(int G) {
  const int hg = G / 10, j = G % 10;
  return (hg >> 2) * 40 + (j / 5) * 20 + (hg & 3) * 5 + j % 5;
}
__device__ __forceinline__ void stage_o(const float (&o)[12], int odd, uint32_t pair, int w4, int lane, float eps, float s0, float s1) {
  const int src = (lane & ~3) | (odd ? 0 : 2);
  const float l0 = __shfl_sync(~0u, o[8], src) + eps, l1 = __shfl_sync(~0u, o[10], src) + eps;
  const float r0 = s0 * rcp(l0), r1 = s1 * rcp(l1);
  const uint32_t base = pair + w4 * 256;
  stsm4(base + (odd ? 3072 : 0) + (lane >> 4) * 1024 + (lane & 15) * 16, packbf(o[0] * r0, o[1] * r0), packbf(o[2] * r1, o[3] * r1),
        packbf(o[4] * r0, o[5] * r0), packbf(o[6] * r1, o[7] * r1));
  if (((lane & 3) < 2) != (odd != 0)) {
    sts32(base + 2048 + lane * 4, packbf(o[8] * r0, o[9] * r0));
    sts32(base + 2048 + 128 + lane * 4, packbf(o[10] * r1, o[11] * r1));
  }
}
__device__ __forceinline__ void store_o(const float (&o)[12], int odd, uint8_t* pair, int w4, int lane, float s0, float s1) {
  const int src = (lane & ~3) | (odd ? 0 : 2);
  const float r0 = s0 * rcp(__shfl_sync(~0u, o[8], src)), r1 = s1 * rcp(__shfl_sync(~0u, o[10], src));
  uint32_t* base = (uint32_t*)(pair + w4 * 256) + lane;
  uint32_t* c = base + (odd ? 768 : 0);
  c[0] = packbf(o[0] * r0, o[1] * r0); c[32] = packbf(o[2] * r1, o[3] * r1);
  c[256] = packbf(o[4] * r0, o[5] * r0); c[288] = packbf(o[6] * r1, o[7] * r1);
  if (((lane & 3) < 2) != (odd != 0)) { base[512] = packbf(o[8] * r0, o[9] * r0); base[544] = packbf(o[10] * r1, o[11] * r1); }
}

struct Maps { CUtensorMap a64, a16, b64, b16, out; };

template <bool MC>
__device__ __forceinline__ void w_load(const Maps& m, int it, uint32_t d, uint32_t b, int hg, int rank) {
  const int kb = (it % 10) * 2 + rank, c = hg * 80 + (hg & 1) * 16, c2 = hg * 80 + ((hg & 1) ? 0 : 64);
  const CUtensorMap *m64 = it < 10 ? &m.b64 : &m.a64, *m16 = it < 10 ? &m.b16 : &m.a16;
  const uint32_t d1 = d + rank * 4096, d2 = d + 24576 + rank * 1024;
#pragma unroll
  for (int sec = 0; sec < 3; sec++) tma5<MC>(d1 + sec * 8192, m64, sec * 640 + c, kb, b);
#pragma unroll
  for (int sec = 0; sec < 3; sec++) tma5<MC>(d2 + sec * 2048, m16, sec * 640 + c2, kb, b);
}
__device__ __forceinline__ void x_load(uint4 (&v)[4], const uint8_t* p, int it) {
  const uint8_t* q = p + (it % 10) * 128;
  v[0] = ldg_x(q); v[1] = ldg_x(q + 8 * 1280); v[2] = ldg_x(q + 64); v[3] = ldg_x(q + 8 * 1280 + 64);
}
__device__ __forceinline__ void gemm_step(float (&a1)[2][64], float (&a2)[24], uint4 (&xv)[4], uint32_t (&f)[4][4], uint32_t (&fp)[4][4],
                                          const uint8_t* xp, int it, int acc, uint32_t sb, uint32_t bars, uint32_t lead) {
  const int s = it % W_NST;
  const uint32_t z = mbar_test(bars + B_Z, 1) - 1;
  f[0][0] = xv[0].x ^ z; f[0][1] = xv[1].x ^ z; f[0][2] = xv[0].y ^ z; f[0][3] = xv[1].y ^ z;
  f[1][0] = xv[0].z ^ z; f[1][1] = xv[1].z ^ z; f[1][2] = xv[0].w ^ z; f[1][3] = xv[1].w ^ z;
  f[2][0] = xv[2].x ^ z; f[2][1] = xv[3].x ^ z; f[2][2] = xv[2].y ^ z; f[2][3] = xv[3].y ^ z;
  f[3][0] = xv[2].z ^ z; f[3][1] = xv[3].z ^ z; f[3][2] = xv[2].w ^ z; f[3][3] = xv[3].w ^ z;
#pragma unroll
  for (int i = 0; i < 4; i++) pin(f[i]);
  x_load(xv, xp, it + 2);
  mbar_wait_u(bars + B_WF + 8 * s, (it / W_NST) & 1);
  const uint64_t b1 = mkdesc(sb + s * W_STAGE, 8192, 1024, 1), b2 = mkdesc(sb + s * W_STAGE + 24576, 2048, 256, 3);
  wg_fence();
#pragma unroll
  for (int kk = 0; kk < 4; kk++) {
    mma_n128_rs_tb(a1[0], f[kk][0], f[kk][1], f[kk][2], f[kk][3], b1 + kk * 128, acc | kk);
    mma_n64_rs_tb(*(float(*)[32])a1[1], f[kk][0], f[kk][1], f[kk][2], f[kk][3], b1 + 1024 + kk * 128, acc | kk);
    mma_n48_rs_tb(a2, f[kk][0], f[kk][1], f[kk][2], f[kk][3], b2 + kk * 32, acc | kk);
  }
  wg_commit();
  wg_wait<1>();
#pragma unroll
  for (int i = 0; i < 4; i++) pin(fp[i]);
  mbar_arrive_pair(bars + B_WE + 8 * ((it + W_NST - 1) % W_NST), lead && acc);
}

__device__ __forceinline__ void kv_stream(uint32_t sb, int hg, int u, uint32_t epoch) {
  const uint32_t bars = sb + OFF_BAR + u * 64;
  cnt_wait(C_KV + hg, 16 * epoch);
  for (int c = 0; c < 32; c++) {
    const int s = c & 3;
    const uint8_t* src = g_KV + (size_t)(hg * 4 + (c >> 4) * 2 + u) * IMG_HEAD + (c & 15) * 6144;
    mbar_wait(bars + B_KE + 8 * s, (c >> 2) & 1);
    mbar_expect(bars + B_KF + 8 * s, 12288);
    bulk_g2s(sb + s * KV_SLOT + u * KV_CHUNK, src, 6144, bars + B_KF + 8 * s);
    bulk_g2s(sb + s * KV_SLOT + u * KV_CHUNK + 6144, src + (size_t)NH * IMG_HEAD, 6144, bars + B_KF + 8 * s);
  }
}

__device__ __forceinline__ void out_step(float (&acc)[80], uint32_t (&f)[4][4], uint32_t (&fp)[4][4], int it, int accum, uint32_t sb, uint32_t arow,
                                         uint32_t bars, uint32_t lead) {
  const int s = it % 5;
  mbar_wait_u(bars + B_OF + 8 * s, it / 5);
  const uint32_t st = sb + o_stage(s);
#pragma unroll
  for (int kk = 0; kk < 4; kk++)
    asm volatile("ldmatrix.sync.aligned.m8n8.x4.shared.b16 {%0,%1,%2,%3}, [%4];"
                 : "=r"(f[kk][0]), "=r"(f[kk][1]), "=r"(f[kk][2]), "=r"(f[kk][3]) : "r"(sb + o_stage_a(s) + arow + kk * 2048) : "memory");
  const uint64_t bd = mkdesc(st + 16384, 2560, 128, 0);
  wg_fence();
#pragma unroll
  for (int kk = 0; kk < 4; kk++) {
    mma_n80_rs_tb(*(float(*)[40])acc, f[kk][0], f[kk][1], f[kk][2], f[kk][3], bd + kk * 320, accum | kk);
    mma_n80_rs_tb(*(float(*)[40])(acc + 40), f[kk][0], f[kk][1], f[kk][2], f[kk][3], bd + kk * 320 + 80, accum | kk);
  }
  wg_commit();
  wg_wait<1>();
#pragma unroll
  for (int i = 0; i < 4; i++) pin(fp[i]);
  mbar_arrive_if(bars + B_OE + 8 * ((it + 4) % 5), lead && accum);
}

__device__ __forceinline__ void middle(uint8_t* smem, const uint32_t (&k)[2][10], uint8_t* olate, int wg, int w4, int lane, uint32_t cm, uint32_t neg1) {
  const uint32_t sb = smem_u32(smem), bars = sb + OFF_BAR, lead = (threadIdx.x & 127) == 0;
  const int t = lane & 3, mi = lane >> 3, r = wg & 1, u = wg >> 1;
  const bool slow = __any_sync(~0u, *(volatile uint32_t*)(smem + OFF_MISC + 20 + r * 4));
  if (u == 0) {
    const uint32_t pka = sb + OFF_PHK + (r * 8 + w4 * 2 + (mi & 1)) * 640 + (mi >> 1) * 128 + (lane & 7) * 16;
    const uint64_t wd = mkdesc(sb + OFF_WPH, 384, 128, 0), wd2 = mkdesc(sb + OFF_WPH + 768, 0, 128, 0);
    float pp[2][12], pn[2][12];
    uint32_t c2[4][2];
#pragma unroll
    for (int i = 0; i < 8; i++) c2[i >> 1][i & 1] = ((t < 2) == !(i & 2)) ? k[i >> 2][8 + (i & 1)] : 0u;
#pragma unroll
    for (int i = 0; i < 4; i++) pin(c2[i]);
    wg_fence();
#pragma unroll
    for (int i = 0; i < 4; i++) {
      float (&p)[12] = i < 2 ? pp[i & 1] : pn[i & 1];
      const uint32_t* kk = &k[i >> 1][(i & 1) * 4];
      mma_n24_rs_tb(p, kk[0], kk[1], kk[2], kk[3], wd + i * 72, 0);
      mma_n24_rs_tb(p, c2[i][0], c2[i][1], 0u, 0u, wd2 + i * 72, 1);
    }
    wg_commit();
    wg_wait<0>();
    pin(pp[0]); pin(pp[1]); pin(pn[0]); pin(pn[1]);
#pragma unroll 1
    for (int i = 0; i < 4; i += 2) {
      uint32_t f[2][10];
      hedgehog2(pp, f, t);
#pragma unroll
      for (int j = 0; j < 2; j++) {
        stsm4(pka + (i + j) * 10240, f[j][0], f[j][1], f[j][2], f[j][3]);
        stsm4(pka + (i + j) * 10240 + 256, f[j][4], f[j][5], f[j][6], f[j][7]);
        stsm2(pka + (i + j) * 10240 + 512, f[j][8], f[j][9]);
      }
#pragma unroll
      for (int k = 0; k < 24; k++) pp[k / 12][k % 12] = pn[k / 12][k % 12];
    }
    float (&pa)[12] = pp[0], (&pb)[12] = pp[1];
    fence_async_smem();
    bar_sync(NB_PHIK, 256);
    wg_fence();
#pragma unroll
    for (int j = 0; j < 2; j++) {
      const uint64_t ad = mkdesc(sb + OFF_PHK + (r * 2 + j) * 10240, 640, 128, 0), vd = mkdesc(sb + OFF_V + (r * 2 + j) * 3072, 384, 128, 0);
#pragma unroll
      for (int ks = 0; ks < 8; ks++) mma_n24_ss_tatb(j ? pb : pa, ad + ks * 80, vd + (ks >> 2) * 768 + (ks & 3) * 48, ks);
    }
    wg_commit();
    wg_wait<0>();
    pin(pa); pin(pb);
    bar_sync(NB_WG + wg, 128);
    float2* dst = (float2*)(smem + OFF_PHK + r * 20480) + w4 * 192 + lane;
    if (w4 < 3) {
      dst[0] = make_float2(pa[0], pa[1]); dst[32] = make_float2(pa[4], pa[5]); dst[64] = make_float2(pa[8], pa[9]);
      dst[1280] = make_float2(pb[0], pb[1]); dst[1312] = make_float2(pb[4], pb[5]); dst[1344] = make_float2(pb[8], pb[9]);
    }
    if (w4 < 2) {
      dst[96] = make_float2(pa[2], pa[3]); dst[128] = make_float2(pa[6], pa[7]); dst[160] = make_float2(pa[10], pa[11]);
      dst[1376] = make_float2(pb[2], pb[3]); dst[1408] = make_float2(pb[6], pb[7]); dst[1440] = make_float2(pb[10], pb[11]);
    }
    fence_async_smem();
    bar_arrive(NB_TAIL, 288);
  }
  {
    const uint32_t gate = sb + OFF_GATE + (r * 64 + w4 * 16 + (lane >> 2)) * 8, qs = sb + OFF_Q + r * 12288;
    const uint32_t kb = bars + u * 64;
    AttnDesc d0;
    d0.k = mkdesc(sb + u * KV_CHUNK, 128, 384, 0); d0.k2 = mkdesc(sb + u * KV_CHUNK + 256, 0, 384, 0);
    d0.v = mkdesc(sb + u * KV_CHUNK + 6144, 384, 128, 0);
    const uint32_t qa = qs + u * 3072 + w4 * 768 + lane * 4;
#pragma unroll 1
    for (int pass = 0; pass < 2; pass++) {
      float o[12], s0[32];
      uint32_t q[8];
      load_q(q, qa + pass * 6144);
      q[6] = q[7] = neg1 + 1;
      if (!slow) {
        uint32_t p0[16], p1[16] = {};
        mbar_wait_u(kb + B_KF, 0);
        wg_fence();
        issue_qk(s0, q, d0, 0);
        wg_commit();
        wg_wait<0>();
        pin(s0);
#pragma unroll 1
        for (int turn = 0; turn < 4; turn++) {
          const int ph = turn & 1;
          AttnDesc d;
          asm volatile("mov.b64 %0, %3;\nmov.b64 %1, %4;\nmov.b64 %2, %5;" : "=l"(d.k), "=l"(d.k2), "=l"(d.v) : "l"(d0.k), "l"(d0.k2), "l"(d0.v));
          attn_chunk<0>(s0, p0, p1, o, q, d, turn, kb + B_KF + 8, ph, kb, lead && turn, cm, neg1);
          attn_chunk<1>(s0, p0, p1, o, q, d, 1, kb + B_KF + 16, ph, kb, lead, cm, neg1);
          attn_chunk<2>(s0, p0, p1, o, q, d, 1, kb + B_KF + 24, ph, kb, lead, cm, neg1);
          attn_chunk<3>(s0, p0, p1, o, q, d, 1, kb + B_KF + (turn == 3 ? 24 : 0), turn == 3 ? 1 : ph ^ 1, kb, lead, cm, neg1);
        }
        wg_wait<0>();
        pin(o); pin(p1); pin(q);
        mbar_arrive_if(kb + B_KE + 24, lead);
      } else {
        uint32_t p[16];
        float m0 = -INFINITY, m1 = -INFINITY;
#pragma unroll
        for (int i = 0; i < 12; i++) o[i] = 0.f;
#pragma unroll 1
        for (int j = 0; j < 32; j++) {
          const int slot = (j >> 1) & 3;
          const uint32_t co = slot * 1536 + (j & 1) * 192, neg = (POLY_MASK >> ((j & 1) * 8)) & 0xFF;
          mbar_wait_u(kb + B_KF + 8 * slot, (j >> 3) & 1);
          wg_fence();
          issue_qk(s0, q, d0, co);
          wg_commit();
          wg_wait<0>();
          pin(s0);
          float n0 = m0, n1 = m1;
#pragma unroll
          for (int g = 0; g < 8; g++) { n0 = fmaxf(n0, fmaxf(s0[4 * g], s0[4 * g + 1])); n1 = fmaxf(n1, fmaxf(s0[4 * g + 2], s0[4 * g + 3])); }
          n0 = fmaxf(n0, __shfl_xor_sync(~0u, n0, 1)); n1 = fmaxf(n1, __shfl_xor_sync(~0u, n1, 1));
          n0 = fmaxf(n0, __shfl_xor_sync(~0u, n0, 2)); n1 = fmaxf(n1, __shfl_xor_sync(~0u, n1, 2));
          const float c0 = ex2(m0 - n0), c1 = ex2(m1 - n1);
          m0 = n0; m1 = n1;
#pragma unroll
          for (int i = 0; i < 3; i++) { o[4 * i] *= c0; o[4 * i + 1] *= c0; o[4 * i + 2] *= c1; o[4 * i + 3] *= c1; }
#pragma unroll
          for (int g = 0; g < 8; g++) {
            const uint32_t sg = ((neg >> g) & 1) ? 0x80008000u : 0u;
            p[2 * g] = packbf(ex2(s0[4 * g] - m0), ex2(s0[4 * g + 1] - m0)) ^ sg;
            p[2 * g + 1] = packbf(ex2(s0[4 * g + 2] - m1), ex2(s0[4 * g + 3] - m1)) ^ sg;
          }
          wg_fence();
          issue_pv(o, p, d0.v + co, 1);
          wg_commit();
          wg_wait<0>();
          pin(o); pin(p);
          mbar_arrive_if(kb + B_KE + 8 * slot, lead && (j & 1));
        }
      }
      mbar_wait_u(bars + B_G, 0);
      if (pass == 0) stage_o(o, u, qs, w4, lane, 0.f, lds_f2(gate).y, lds_f2(gate + 64).y);
      else store_o(o, u, olate + r * 163840, w4, lane, lds_f2(gate).y, lds_f2(gate + 64).y);
      if (pass == 0) {
        if (u == 1) {
          const uint32_t aq = sb + OFF_AQ + r * 12288;
          const float g0 = lds_f2(gate).x, g1 = lds_f2(gate + 64).x;
#pragma unroll 1
          for (int j = 0; j < 2; j++) {
            float pp[2][12];
            wg_fence();
            issue_proj(pp, aq + j * 6144, sb + OFF_WPH + j * 2304);
            wg_commit();
            wg_wait<0>();
            pin(pp[0]); pin(pp[1]);
            uint32_t f[2][10];
            hedgehog2(pp, f, t);
            pin(f[0]); pin(f[1]);
            const uint64_t kvd = mkdesc(sb + OFF_V + j * 3840, 384, 128, 0), kvd2 = mkdesc(sb + OFF_V + j * 3840 + 1536, 0, 128, 0);
            wg_fence();
#pragma unroll
            for (int i = 0; i < 2; i++) {
              mma_n24_rs_tb(pp[i], f[i][0], f[i][1], f[i][2], f[i][3], kvd + i * 120, 0);
              mma_n24_rs_tb(pp[i], f[i][4], f[i][5], f[i][6], f[i][7], kvd + i * 120 + 48, 1);
              mma_n24_rs_tb(pp[i], f[i][8], f[i][9], 0u, 0u, kvd2 + i * 120, 1);
            }
            wg_commit();
            wg_wait<0>();
            pin(pp[0]); pin(pp[1]); pin(f[0]); pin(f[1]);
            stage_o(pp[0], 0, aq + j * 5120, w4, lane, 1e-6f, g0, g1);
            stage_o(pp[1], 1, aq + j * 5120, w4, lane, 1e-6f, g0, g1);
          }
        }
        fence_async_smem();
        bar_arrive(NB_READ, 544);
      }
    }
    bar_arrive(NB_LAST, 544);
  }
}

__global__ void __cluster_dims__(2, 1, 1) __launch_bounds__(640, 1)
fused_block(const __grid_constant__ Maps maps, const __nv_bfloat16* __restrict__ x, const __nv_bfloat16* __restrict__ wphi,
            const __nv_bfloat16* __restrict__ gate_w, const uint8_t* __restrict__ woa, const uint8_t* __restrict__ wob, uint32_t cm, uint32_t neg1) {
  extern __shared__ __align__(1024) uint8_t smem[];
  const uint32_t sb = smem_u32(smem), bars = sb + OFF_BAR;
  const int warp = __shfl_sync(~0u, threadIdx.x >> 5, 0), lane = threadIdx.x & 31, wg = warp >> 2;
  const int bid = blockIdx.x;
  const int mt = (bid & 1) + 2 * (bid >> 4), hg = (bid >> 1) & 7;
  const int half = bid & 1, nt = (bid >> 1) & 3, mt3 = bid >> 3;
  if (warp == 16) {
    if (lane == 0) {
#pragma unroll
      for (int i = 0; i < W_NST; i++) { mbar_init(bars + B_WF + 8 * i, 1); mbar_init(bars + B_WE + 8 * i, 4); }
      mbar_init(bars + B_Z, 1);
      mbar_init(bars + B_X, 1);
      mbar_init(bars + B_F, 1);
      *(uint4*)(smem + OFF_MISC) = make_uint4(0u, 0u, 0u, 0u);
      *(uint4*)(smem + OFF_MISC + 16) = make_uint4(0u, 0u, 0u, 0u);
      asm volatile("fence.mbarrier_init.release.cluster;" ::: "memory");
      mbar_expect(bars + B_WF, W_STAGE);
    }
    __syncwarp();
  }
  asm volatile("barrier.cluster.arrive.relaxed.aligned;" ::: "memory");
  if ((warp | 1) == 17) {
    bar_sync(0, 64);
    if (lane == 0) w_load<false>(maps, 0, sb, bars + B_WF, hg, warp & 1);
    __syncwarp();
  }

  if (wg == 4) {
    reg_dec<32>();
    asm volatile("barrier.cluster.wait.aligned;" ::: "memory");
    if (warp == 16) {
      if (lane == 0) {
        for (int it = 1; it < 20; it++) {
          const int s = it % W_NST;
          if (it >= W_NST) mbar_wait(bars + B_WE + 8 * s, ((it / W_NST) - 1) & 1);
          mbar_expect(bars + B_WF + 8 * s, W_STAGE);
          w_load<true>(maps, it, sb + s * W_STAGE, bars + B_WF + 8 * s, hg, half);
        }
      }
      __syncwarp();
      bar_sync(NB_HELP, 128);
      const uint32_t epoch = *(volatile uint32_t*)(smem + OFF_MISC + 16);
      if (lane == 0) {
        kv_stream(sb, hg, 0, epoch);
        cnt_wait(C_WO, NCTA * epoch);
        cnt_wait(C_OA + mt3, 8 * epoch);
        mbar_wait(bars + B_RF, 0);
        const uint8_t* ga = g_OAB + (size_t)mt3 * 327680 + half * 5 * 8192;
        for (int it = 0; it < 10; it++) {
          const int s = it % 5, ks = it < 5 ? it : it + 5;
          if (it >= 2 && it < 5) {
            mbar_wait(bars + B_P1, 0);
            mbar_wait(bars + B_KE + 8 * (it - 1), 0);
            mbar_wait(bars + B_KE + 64 + 8 * (it - 1), 0);
          }
          if (it >= 5) mbar_wait(bars + B_OE + 8 * s, 0);
          const uint32_t d = sb + o_stage(s), da = sb + o_stage_a(s), b = bars + B_OF + 8 * s;
          if (it == 1) {
            mbar_expect(bars + B_OF + 32, O_STAGE);
            bulk_g2s(sb + o_stage_a(4), ga + 4 * 8192, 8192, bars + B_OF + 32);
            bulk_g2s(sb + o_stage_a(4) + 8192, ga + 4 * 8192 + 163840, 8192, bars + B_OF + 32);
          }
          if (it != 4) mbar_expect(b, O_STAGE);
          bulk_g2s(d + 16384, g_WOI + (size_t)nt * 409600 + (ks + half * 5) * 20480, 20480, b);
          if (it == 7) { cnt_wait(C_OB + mt3, 8 * epoch); }
          if (it == 4) continue;
          bulk_g2s(da, ga + ks * 8192, 8192, b);
          bulk_g2s(da + 8192, ga + ks * 8192 + 163840, 8192, b);
        }
      }
    } else if (warp == 17) {
      uint32_t epoch = 0;
      if (lane == 0) {
#pragma unroll
        for (int i = 0; i < 8; i++) { mbar_init(bars + B_KF + (i >> 2) * 64 + 8 * (i & 3), 1); mbar_init(bars + B_KE + (i >> 2) * 64 + 8 * (i & 3), 2); }
#pragma unroll
        for (int i = 0; i < 5; i++) { mbar_init(bars + B_OF + 8 * i, 1); mbar_init(bars + B_OE + 8 * i, 2); }
        mbar_init(bars + B_RF, 1);
        mbar_init(bars + B_G, 1);
        mbar_init(bars + B_P1, 1);
        mbar_init(bars + B_R, 1);
        fence_async_smem();
        epoch = atomicAdd(g_CNT + C_START * 8, 1u) / NCTA + 1;
        *(volatile uint32_t*)(smem + OFF_MISC + 16) = epoch;
      }
      epoch = __shfl_sync(~0u, epoch, 0);
      if (lane < 30) { uint4* z = (uint4*)(g_KVA + hg * 1920 + mt * 120) + lane * 2; z[0] = z[1] = make_uint4(0u, 0u, 0u, 0u); }
      __syncwarp();
      asm volatile("fence.acq_rel.gpu;" ::: "memory");
      bar_arrive(NB_HELP, 128);
#pragma unroll 1
      for (int e = lane; e < 96; e += 32) {
        const int i = e / 24, slot = e % 24;
        int d = -1;
        if (i & 1) { if (slot < 16) d = slot + 4; else if (slot >= 20) d = slot - 20; }
        else if (slot < 20) d = slot;
        uint2 v[5] = {};
        if (d >= 0) {
#pragma unroll
          for (int u = 0; u < 5; u++) v[u] = __ldg((const uint2*)(wphi + ((hg * 4 + i) * 20 + d) * 20) + u);
        }
        uint8_t* dst = smem + OFF_WPH + i * 1152 + (slot >> 3) * 384 + (slot & 7) * 16;
        *(uint4*)dst = make_uint4(v[0].x, v[0].y, v[1].x, v[1].y);
        *(uint4*)(dst + 128) = make_uint4(v[2].x, v[2].y, v[3].x, v[3].y);
        *(uint4*)(dst + 256) = make_uint4(v[4].x, v[4].y, v[4].x, v[4].y);
      }
      fence_async_smem();
      bar_sync(NB_STAGED, 544);
      if (lane == 0) {
#pragma unroll 1
        for (int i = 0; i < 16; i++) {
          bulk_s2g(g_KV + (size_t)((i >> 3) * NH + hg * 4 + (i & 3)) * IMG_HEAD + (mt * 2 + ((i >> 2) & 1)) * 3072,
                   sb + (i < 8 ? OFF_AQ : OFF_V) + (i & 7) * 3072, 3072);
          __nanosleep(100);
        }
      }
      __syncwarp();
      bar_sync(NB_NORM, 288);
      if (lane == 0) {
        bulk_s2g(g_KMAX + hg * 16 + mt, sb + OFF_MISC, 16);
        bulk_commit_wait();
        cnt_add_bulk(C_KV + hg);
      }
      if (lane == 0) { mbar_arrive(bars + B_F); cnt_wait(C_KV + hg, 16 * epoch); }
      __syncwarp();
      {
        uint4 v = ldg_cg4(g_KMAX + hg * 16 + (lane & 15));
        v.x = __reduce_max_sync(~0u, v.x); v.y = __reduce_max_sync(~0u, v.y); v.z = __reduce_max_sync(~0u, v.z); v.w = __reduce_max_sync(~0u, v.w);
        if (lane < 4) *(volatile float*)(smem + OFF_MISC + lane * 4) =
            sqrt_ap(__uint_as_float(lane == 0 ? v.x : lane == 1 ? v.y : lane == 2 ? v.z : v.w)) * 1.01f;
      }
      bar_arrive(NB_BOUND, 288);
      bar_sync(NB_TAIL, 288);
      if (lane == 0) {
#pragma unroll 1
        for (int i = 0; i < 4; i++)
          asm volatile("cp.reduce.async.bulk.global.shared::cta.bulk_group.add.f32 [%0], [%1], %2;" ::"l"(g_KVA + (hg * 4 + i) * 480),
                       "r"(sb + OFF_PHK + i * 10240), "r"(3840) : "memory");
        bulk_commit_wait();
        cnt_add_bulk(C_KVP + hg);
        cnt_wait(C_GATE + mt, 8 * epoch);
      }
      __syncwarp();
      {
        const uint4 g0 = ldg_cg4(g_GATE + mt * 128 + lane * 2), g1 = ldg_cg4(g_GATE + mt * 128 + 64 + lane * 2);
        *(uint4*)(smem + OFF_GATE + lane * 16) = g0;
        *(uint4*)(smem + OFF_GATE + 512 + lane * 16) = g1;
      }
      if (lane == 0) {
        cnt_wait(C_KVP + hg, 16 * epoch);
        mbar_expect(bars + B_R, 15360);
        bulk_g2s(sb + OFF_KVS, g_KVA + hg * 1920, 15360, bars + B_R);
      }
      mbar_wait(bars + B_R, 0);
#pragma unroll 4
      for (int e = lane; e < 960; e += 32) {
        const float4 v = *(const float4*)(smem + OFF_KVS + e * 16);
        *(uint2*)(smem + OFF_V + e * 8) = make_uint2(packbf(v.x, v.y), packbf(v.z, v.w));
      }
      fence_async_smem();
      __syncwarp();
      if (lane == 0) mbar_arrive(bars + B_G);
      uint8_t* og = g_OAB + (size_t)mt * 327680;
      bar_sync(NB_READ, 544);
      if (lane == 0) {
#pragma unroll 1
        for (int w = 0; w < 2; w++) {
          bulk_s2g(og + w * 163840 + hg * 10240, sb + OFF_AQ + w * 12288, 10240);
          bulk_s2g(og + w * 163840 + (80 + bgroup(hg * 10)) * 1024, sb + OFF_Q + w * 12288, 5120);
        }
        bulk_commit_wait();
        mbar_arrive(bars + B_RF);
        cnt_add_bulk(C_OA + mt);
      }
      __syncwarp();
      bar_sync(NB_LAST, 544);
      if (lane == 0) cnt_add(C_OB + mt);
    } else if (warp == 18) {
      bar_sync(NB_HELP, 128);
      if (lane == 0) { kv_stream(sb, hg, 1, *(volatile uint32_t*)(smem + OFF_MISC + 16)); mbar_arrive(bars + B_P1); }
    } else {
      bar_sync(NB_HELP, 128);
#pragma unroll 1
      for (int kg = bid; kg < 160; kg += NCTA) {
        const uint8_t* src = (kg < 80 ? woa + (size_t)kg * 10240 : wob + (size_t)(kg - 80) * 10240) + (lane & 7) * 1280 + (lane >> 3) * 16;
        uint8_t* dst = g_WOI + (kg < 80 ? kg : 80 + bgroup(kg - 80)) * 2560 + (lane & 7) * 16 + (lane >> 3) * 128;
#pragma unroll 1
        for (int n4 = 0; n4 < 4; n4++) {
          uint4 v[5];
#pragma unroll
          for (int u = 0; u < 5; u++) v[u] = __ldg((const uint4*)(src + (n4 * 20 + u * 4) * 16));
#pragma unroll
          for (int u = 0; u < 5; u++) *(uint4*)(dst + (size_t)n4 * 409600 + u * 512) = v[u];
        }
      }
      __syncwarp();
      if (lane == 0) cnt_add(C_WO);
    }
  } else {
    const int w4 = warp & 3;
    const uint32_t lead = (threadIdx.x & 127) == 0;
    uint32_t k[2][10] = {};
    if (wg >= 2) {
      const int ht = threadIdx.x - 256;
      reg_dec<24>();
      asm volatile("barrier.cluster.wait.aligned;" ::: "memory");
      __nanosleep(2500);
      {
        const int row = mt * 128 + hg * 16 + (ht >> 4);
        const uint4* xr = (const uint4*)(x + (size_t)row * DM) + (ht & 15);
        const uint4* gr = (const uint4*)gate_w + (ht & 15);
        float acc = 0.f;
#pragma unroll 1
        for (int i = 0; i < 5; i++) {
          const uint4 a = __ldg(xr + i * 16), g = __ldg(gr + i * 16);
          const uint32_t av[4] = {a.x, a.y, a.z, a.w}, gv[4] = {g.x, g.y, g.z, g.w};
#pragma unroll
          for (int j = 0; j < 4; j++) {
            uint32_t p;
            asm("mul.rn.bf16x2 %0, %1, %2;" : "=r"(p) : "r"(av[j]), "r"(gv[j]));
            acc += bf_lo(p) + bf_hi(p);
          }
        }
#pragma unroll
        for (int o = 8; o; o >>= 1) acc += __shfl_xor_sync(~0u, acc, o);
        if ((ht & 15) == 0) {
          const float g = bf_round(__fdividef(1.f, 1.f + __expf(-bf_round(acc))));
          g_GATE[row] = make_float2(g, bf_round(1.f - g));
        }
      }
      bar_sync(NB_BG, 256);
      if (ht == 0) { cnt_add(C_GATE + mt); }
      {
        const int row = ht & 127, hp = ht >> 7;
        const uint32_t off = (row >> 6) * 12288 + hp * 6144 + ((row >> 3) & 7) * 384 + (row & 7) * 16;
        bar_sync(NB_STAGED, 544);
#pragma unroll
        for (int i = 0; i < 2; i++) {
          const uint32_t m = __reduce_max_sync(~0u, __float_as_uint(row_norm2(smem + OFF_AQ + off + i * 3072, i)));
          if (lane == 0) asm volatile("red.shared.max.u32 [%0], %1;" ::"r"(sb + OFF_MISC + (hp * 2 + i) * 4), "r"(m) : "memory");
        }
        fence_async_smem();
        bar_arrive(NB_NORM, 288);
        const float q0 = sqrt_ap(row_norm2(smem + OFF_Q + off, 0)), q1 = sqrt_ap(row_norm2(smem + OFF_Q + off + 3072, 1));
        bar_sync(NB_BOUND, 288);
        const float2 km = *(const float2*)(smem + OFF_MISC + hp * 8);
        const float b0 = q0 * km.x, b1 = q1 * km.y;
        if (__any_sync(~0u, !(b0 <= FAST_BOUND && b1 <= FAST_BOUND)) && lane == 0) *(volatile uint32_t*)(smem + OFF_MISC + 20 + (row >> 6) * 4) = 1;
        bar_sync(NB_BG, 256);
        if (!*(volatile uint32_t*)(smem + OFF_MISC + 20 + (row >> 6) * 4)) {
          *(uint2*)(smem + OFF_Q + off + 256 + 8) = make_uint2(packbf(-b0, 1.f), BF_ONE);
          *(uint2*)(smem + OFF_Q + off + 3072 + 256) = make_uint2(packbf(-b1, 1.f), BF_ONE);
        }
      }
      bar_sync(NB_EPI, 512);
      reg_inc<112>();
    } else {
    const uint8_t* xp = (const uint8_t*)x + (size_t)(mt * 128 + warp * 16 + (lane >> 2)) * 1280 + (lane & 3) * 16;
    uint4 xa[4], xb[4];
    x_load(xa, xp, 0);
    x_load(xb, xp, 1);
    reg_inc<200>();
    asm volatile("barrier.cluster.wait.aligned;" ::: "memory");
    const int t = lane & 3, mi = lane >> 3;
    {
      const uint32_t sbase = sb + wg * 12288 + (w4 * 2 + (mi & 1)) * 384 + (lane & 7) * 16;
      const uint32_t ad01 = sbase + (mi >> 1) * 128, ad2 = sbase + (mi >> 1) * 3072 + 256;
      float a1[2][64], a2[24];
      uint32_t fa[4][4] = {}, fb[4][4] = {};
#pragma unroll 1
      for (int tile = 0; tile < 2; tile++) {
#pragma unroll 1
        for (int ks = 0; ks < 10; ks += 2) {
          gemm_step(a1, a2, xa, fa, fb, xp, tile * 10 + ks, ks, sb, bars, lead);
          gemm_step(a1, a2, xb, fb, fa, xp, tile * 10 + ks + 1, 1, sb, bars, lead);
        }
        wg_wait<0>();
        pin(a1[0]); pin(*(float(*)[32])a1[1]); pin(a2);
#pragma unroll
        for (int i = 0; i < 4; i++) pin(fb[i]);
        mbar_arrive_pair(bars + B_WE + 8 * 4, lead && tile == 0);
        if (tile == 0) {
          if (hg & 1) epilogue0<4>(a1, a2, warp * 2, t, ad01, ad2);
          else epilogue0<0>(a1, a2, warp * 2, t, ad01, ad2);
          fence_async_smem();
          bar_arrive(NB_STAGED, 544);
        }
      }
      mbar_wait_u(bars + B_F, 0);
#pragma unroll
      for (int s = 0; s < 8; s++) mbar_arrive_if(bars + B_KE + (s < 4 ? 64 : 0) + 8 * (s & 3), lead);
      if (hg & 1) epilogue1<4>(a1, a2, k, t, ad01, ad2);
      else epilogue1<0>(a1, a2, k, t, ad01, ad2);
      pin(k[0]); pin(k[1]);
      fence_async_smem();
      reg_dec<112>();
      bar_sync(NB_EPI, 512);
    }
    }
    middle(smem, k, g_OAB + (size_t)mt * 327680 + (80 + bgroup(hg * 10 + 5)) * 1024, wg, w4, lane, cm, neg1);
    if (wg >= 2) { reg_dec<24>(); return; }
    {
      if (lane == 0) asm volatile("prefetch.tensormap [%0];" ::"l"(&maps.out) : "memory");
      __syncwarp();
      asm volatile("barrier.cluster.arrive.relaxed.aligned;" ::: "memory");
      reg_inc<160>();
      float acc[80];
      uint32_t fa[4][4] = {}, fb[4][4] = {};
      const uint32_t arow = wg * 8192 + (lane >> 4) * 1024 + w4 * 256 + (lane & 15) * 16;
#pragma unroll 1
      for (int it = 0; it < 10; it += 2) {
        out_step(acc, fa, fb, it, it, sb, arow, bars, lead);
        out_step(acc, fb, fa, it + 1, 1, sb, arow, bars, lead);
      }
      wg_wait<0>();
      pin(acc);
#pragma unroll
      for (int i = 0; i < 4; i++) pin(fb[i]);
      asm volatile("barrier.cluster.wait.aligned;" ::: "memory");
      uint32_t remote, rbar;
      asm volatile("mapa.shared::cluster.u32 %0, %1, %2;" : "=r"(remote) : "r"(sb + OFF_Q + threadIdx.x * 16), "r"(half ^ 1));
      asm volatile("mapa.shared::cluster.u32 %0, %1, %2;" : "=r"(rbar) : "r"(bars + B_X), "r"(half ^ 1));
      if (threadIdx.x == 0) mbar_expect(bars + B_X, 20480);
#pragma unroll
      for (int j = 0; j < 5; j++) {
        uint32_t v[4];
#pragma unroll
        for (int u = 0; u < 4; u++) v[u] = half ? packbf(acc[8 * j + 2 * u], acc[8 * j + 2 * u + 1]) : packbf(acc[40 + 8 * j + 2 * u], acc[41 + 8 * j + 2 * u]);
        asm volatile("st.async.weak.shared::cluster.mbarrier::complete_tx::bytes.v4.b32 [%0], {%1,%2,%3,%4}, [%5];" ::"r"(remote + j * 4096), "r"(v[0]),
                     "r"(v[1]), "r"(v[2]), "r"(v[3]), "r"(rbar) : "memory");
      }
      mbar_wait_u(bars + B_OE, 1);
#pragma unroll 1
      for (int n = 0; n < (1 << 18); n++) {
        uint32_t ok;
        asm volatile("{\n.reg .pred p;\nmbarrier.try_wait.parity.acquire.cluster.shared::cta.b64 p, [%1], 0;\nselp.u32 %0, 1, 0, p;\n}\n"
                     : "=r"(ok) : "r"(bars + B_X) : "memory");
        if (__all_sync(~0u, ok)) break;
      }
      const uint32_t ob = sb + OFF_V + warp * 2560;
      const uint32_t oa = ob + (lane & 15) * 160 + (lane >> 4) * 16;
      uint32_t pk[20];
#pragma unroll
      for (int j = 0; j < 5; j++) {
        const uint4 r = *(const uint4*)(smem + OFF_Q + j * 4096 + threadIdx.x * 16);
        const uint32_t rv[4] = {r.x, r.y, r.z, r.w};
#pragma unroll
        for (int u = 0; u < 4; u++) {
          const float v0 = half ? acc[40 + 8 * j + 2 * u] : acc[8 * j + 2 * u], v1 = half ? acc[41 + 8 * j + 2 * u] : acc[8 * j + 2 * u + 1];
          pk[4 * j + u] = packbf(v0 + bf_lo(rv[u]), v1 + bf_hi(rv[u]));
        }
      }
#pragma unroll
      for (int j = 0; j < 10; j += 2) stsm4(oa + j * 16, pk[2 * j], pk[2 * j + 1], pk[2 * j + 2], pk[2 * j + 3]);
      fence_async_smem();
      __syncwarp();
      if (lane == 0) {
        asm volatile("cp.async.bulk.tensor.2d.global.shared::cta.bulk_group [%0, {%2,%3}], [%1];" ::"l"(&maps.out), "r"(ob), "r"(nt * 160 + half * 80),
                     "r"(mt3 * 128 + warp * 16) : "memory");
        asm volatile("cp.async.bulk.commit_group;" ::: "memory");
        asm volatile("cp.async.bulk.wait_group.read 0;" ::: "memory");
      }
    }
  }
}

typedef CUresult (*EncodeFn)(CUtensorMap*, CUtensorMapDataType, cuuint32_t, void*, const cuuint64_t*, const cuuint64_t*, const cuuint32_t*,
                             const cuuint32_t*, CUtensorMapInterleave, CUtensorMapSwizzle, CUtensorMapL2promotion, CUtensorMapFloatOOBfill);

void encode(EncodeFn fn, CUtensorMap* m, const void* p, int rank, const cuuint64_t* dims, const cuuint64_t* strides, const cuuint32_t* box,
            CUtensorMapSwizzle sw) {
  const cuuint32_t es[5] = {1, 1, 1, 1, 1};
  fn(m, CU_TENSOR_MAP_DATA_TYPE_BFLOAT16, rank, const_cast<void*>(p), dims, strides, box, es, CU_TENSOR_MAP_INTERLEAVE_NONE, sw,
     CU_TENSOR_MAP_L2_PROMOTION_L2_128B, CU_TENSOR_MAP_FLOAT_OOB_FILL_NONE);
}

}

extern "C" void kernel_launch(void* const* d_in, const int* in_sizes, int n_in, void* d_out, int out_size) {
  (void)in_sizes; (void)n_in; (void)out_size;
  static EncodeFn enc = nullptr;
  if (!enc) {
    void* fn = nullptr;
    cudaDriverEntryPointQueryResult qr;
    cudaGetDriverEntryPoint("cuTensorMapEncodeTiled", &fn, cudaEnableDefault, &qr);
    enc = (EncodeFn)fn;
    cudaFuncSetAttribute(fused_block, cudaFuncAttributeMaxDynamicSharedMemorySize, SMEM_BYTES);
  }
  Maps maps;
  {
    const cuuint64_t dx[2] = {640, 2048}, sx[1] = {1280};
    const cuuint32_t bo[2] = {80, 16};
    encode(enc, &maps.out, d_out, 2, dx, sx, bo, CU_TENSOR_MAP_SWIZZLE_NONE);
    const cuuint64_t dw[5] = {1920, 2, 4, 4, 20}, sw[4] = {3840, 8 * 3840, 2 * 3840, 32 * 3840};
    const cuuint32_t b64[5] = {64, 2, 4, 4, 1}, b16[5] = {16, 2, 4, 4, 1};
    encode(enc, &maps.a64, d_in[1], 5, dw, sw, b64, CU_TENSOR_MAP_SWIZZLE_128B);
    encode(enc, &maps.a16, d_in[1], 5, dw, sw, b16, CU_TENSOR_MAP_SWIZZLE_32B);
    encode(enc, &maps.b64, d_in[5], 5, dw, sw, b64, CU_TENSOR_MAP_SWIZZLE_128B);
    encode(enc, &maps.b16, d_in[5], 5, dw, sw, b16, CU_TENSOR_MAP_SWIZZLE_32B);
  }
  fused_block<<<NCTA, 640, SMEM_BYTES, cudaStreamPerThread>>>(maps, (const __nv_bfloat16*)d_in[0], (const __nv_bfloat16*)d_in[2],
                                                               (const __nv_bfloat16*)d_in[7],
                                                               (const uint8_t*)d_in[3], (const uint8_t*)d_in[6], 0x1F801F80u, 0xFFFFFFFFu);
}
```
